```python
import torch

def _softmax(x, axis=-1):
    return torch.softmax(x, dim=axis)
def _gelu(x):
    return torch.nn.functional.gelu(x, approximate="tanh")
def _silu(x):
    return torch.nn.functional.silu(x)
def _sigmoid(x):
    return torch.sigmoid(x)
def _layernorm(x, axis=-1, eps=1e-5):
    m = x.mean(dim=axis, keepdim=True)
    v = x.var(dim=axis, keepdim=True, unbiased=False)
    return (x - m) / torch.sqrt(v + eps)
def _scatter_add(tgt, idx, src, axis=0):
    return tgt.clone().index_add_(axis, idx, src)
def _segment_sum(src, seg, n):
    out = torch.zeros((n,) + src.shape[1:], dtype=src.dtype)
    return out.index_add_(0, seg, src)
def _pad(x, pw):
    flat = tuple(v for pair in reversed(pw) for v in pair)
    return torch.nn.functional.pad(x, flat)

kernel_name = 'sequential_preLN__sliding_local_dilated__glu_gated_geglu__prompt'

def setup_inputs():

    _w = (lambda a: (lambda t: t.to(torch.bfloat16) if t.is_floating_point() else t)(torch.as_tensor(a)))
    def _A_setup():
        B, S, D = 1, 2048, 1024
        return {
            "x": _w((lambda *s: torch.randn(*s, dtype=torch.bfloat16) * 0.05)(B, S, D)),
            "wqkv": _w((lambda *s: torch.randn(*s, dtype=torch.bfloat16) * 0.05)(D, 3 * D)),
            "wo": _w((lambda *s: torch.randn(*s, dtype=torch.bfloat16) * 0.05)(D, D)),
        }
    _A_in = _A_setup()

    def _B_setup():
        B, S, Dm, Df = 1, 2048, 1024, 3584
        return {
            "x": _w((lambda *s: torch.randn(*s, dtype=torch.bfloat16) * 0.05)(B, S, Dm)),
            "w_gate": _w((lambda *s: torch.randn(*s, dtype=torch.bfloat16) * 0.8)(Dm, Df) * (Dm ** -0.5)),
            "w_up": _w((lambda *s: torch.randn(*s, dtype=torch.bfloat16) * 0.8)(Dm, Df) * (Dm ** -0.5)),
            "w_down": _w((lambda *s: torch.randn(*s, dtype=torch.bfloat16) * 0.8)(Df, Dm) * (Df ** -0.5)),
        }
    _B_in = _B_setup()

    return {
        "A_x": _A_in["x"],
        "A_wqkv": _A_in["wqkv"],
        "A_wo": _A_in["wo"],
        "B_x": _B_in["x"],
        "B_w_gate": _B_in["w_gate"],
        "B_w_up": _B_in["w_up"],
        "B_w_down": _B_in["w_down"],
    }

def reference(A_x, A_wqkv, A_wo, B_x, B_w_gate, B_w_up, B_w_down):
    def _A_ref(x, wqkv, wo):
        B, S, D = x.shape
        H = 32; Dh = D // H
        W, dil = 8, 2
        qkv = (lambda x, *d: x.permute(*d))((x @ wqkv).reshape(B, S, 3, H, Dh), 2, 0, 3, 1, 4)
        q, k, v = qkv[0], qkv[1], qkv[2]
        scale = Dh ** -0.5
        pos = torch.arange(S)
        off = torch.arange(W) * dil
        idx = pos[:, None] - off[None, :]
        mask = idx >= 0
        idx_c = torch.where(mask, idx, 0).reshape(-1)
        kg = k[:, :, idx_c, :].reshape(B, H, S, W, Dh)
        vg = v[:, :, idx_c, :].reshape(B, H, S, W, Dh)
        logits = torch.einsum("bhsd,bhswd->bhsw", q, kg) * scale
        logits = torch.where(mask[None, None, :, :], logits, -1e9)
        attn = _softmax(logits, axis=-1)
        o = torch.einsum("bhsw,bhswd->bhsd", attn, vg)
        return (lambda x, *d: x.permute(*d))(o, 0, 2, 1, 3).reshape(B, S, D) @ wo

    def _B_ref(x, w_gate, w_up, w_down):
        g = torch.einsum("bsd,df->bsf", x, w_gate)
        u = torch.einsum("bsd,df->bsf", x, w_up)
        h = _gelu(g) * u
        return torch.einsum("bsf,fd->bsd", h, w_down)

    x = A_x
    h = x + _A_ref(_layernorm(x, axis=-1), A_wqkv, A_wo)
    h2 = h + _B_ref(_layernorm(h, axis=-1), B_w_gate, B_w_up, B_w_down)
    return h2
```

```cpp
#include <cuda_runtime.h>
#include <cuda_bf16.h>
#include <cuda.h>
#include <stdint.h>

namespace {

constexpr int kS = 2048, kD = 1024, kF = 3584;
constexpr int kThreads = 384;

constexpr int kRing = 0;
constexpr int kStage = 163840;
constexpr int kAug = kStage + 16384;
constexpr int kOwn = kStage + 32768;
constexpr int kFill = kStage + 24576;
constexpr int kCs = kStage + 65536;
constexpr int kStat = kCs + 1536;
constexpr int kBars = kStat + 1024;
constexpr int kSmemBytes = kBars + 512;
constexpr int kResBar = 36;
constexpr int kAuxBar = 37;
constexpr int kStgBar = 39;
constexpr int kResFreeBar = 41;
constexpr int kStatBar = 42;
constexpr int kPartBar = 43;
constexpr int kWaveBar = 45;
constexpr int kHalfBar = 49;
constexpr int kSentBar = 51;
constexpr int kLandBar = 52;
constexpr int kNumBars = 58;
static_assert(kNumBars == 4 + 3 * 18, "barrier initialisation is split 4 + 3 x 18");
__host__ __device__ constexpr int bar_count(int i) {
  const int ph = i < 8 ? 0 : i < 18 ? 1 : i < 26 ? 2 : 3, base = ph * 9 - (ph & 1);
  return i < 36 ? (i - base < 4 + (ph & 1) ? 2 : ph == 0 ? 16 : 8) : i == kResFreeBar || i == kStatBar || (i >= kHalfBar && i < kLandBar) ? 4 : 1;
}
__host__ __device__ constexpr uint64_t bar_shifts(int first) {
  uint64_t m = 0;
  for (int i = 17; i >= 0; i--) {
    const int n = bar_count(first + i);
    m = m << 3 | (n == 16 ? 4 : n == 8 ? 3 : n >> 1);
  }
  return m;
}
constexpr int kScale = kBars + 464;
constexpr int kOnes = kBars + 480;
constexpr int kZero = kBars + 496;
constexpr int kRole = kBars + 508;
constexpr int kEpoch = kBars + 500;
__device__ __forceinline__ int ring_base(int ph) { return ph * 9 - (ph & 1); }
constexpr int kNbOrder = 1;
constexpr int kNbWg = 3;
constexpr int kNbPub = 5;
constexpr int kNbWin = 7;
constexpr int kNbSelf = 13;
constexpr int kNbHalo = 9;

constexpr int kFlO = 0;
constexpr int kFlPace = 1;
constexpr int kFlHH = 3;
constexpr int kFlPart = 8;
constexpr int kFlRow = 32;
constexpr int kNumFlags = 16 * kFlRow;

constexpr int kPauseG1 = 7;
constexpr int kPauseG2 = 1;
constexpr int kAhead = 2;
constexpr int kTail = 5;
constexpr int kDone = 3;
constexpr int kQuietAt = 48;
constexpr int kPfStep = 8;
constexpr int kBackoffNs = 200;
constexpr int kPaceNs = 300;
constexpr int kPartNs = 150;
constexpr int kFillNs = 500;
constexpr int kHaloNs = 150;
constexpr int kGateONs = 150;
constexpr int kGateHNs = 150;
constexpr int kHoldNs = 1200;
constexpr float kBias1 = 256.f, kBias3 = 16384.f;
constexpr int kSampleNs = 4000;
constexpr int kStatNs = 1500;

struct Scratch {
  uint32_t flags[kNumFlags];
  uint32_t epoch[32];
  uint4 stat1[kS];
  uint4 stat2[8 * kS];
  uint4 cs[7 * 8 * 96];
  uint4 halo[2 * 16 * 8 * 6 * 32];
  uint4 part[128 * 8 * 128];
};
struct Params {
  CUtensorMap x, wqkv, o, wo, h, wg, wu, hh, wd, out;
  CUtensorMap ost, hst, hhst;
  CUtensorMap o16, h16;
  const uint4 *wop, *wgp, *wup;
};

__device__ __align__(256) __nv_bfloat16 g_o[kS * kD];
__device__ __align__(256) __nv_bfloat16 g_h[kS * kD];
__device__ __align__(256) __nv_bfloat16 g_hh[kS * kF];
__device__ __align__(256) Scratch g_scratch;

template <bool BY_SM>
__device__ __forceinline__ int role_id() {
  uint32_t sm;
  asm("mov.u32 %0, %%smid;" : "=r"(sm));
  const int tpc = (BY_SM ? sm : blockIdx.x) >> 1, rank = blockIdx.x & 1;
  if ((tpc | 1) == 61) return 8 + 2 * tpc + rank;
  const int u = tpc - 32, s7 = (u * 37) >> 8;
  const int g = tpc < 32 ? tpc & 7 : tpc < 60 ? 1 + u - 7 * s7 : 0, s = tpc < 32 ? tpc >> 3 : tpc < 60 ? 4 + s7 : tpc - 58;
  return (g * 2 + rank) * 8 + s;
}
#define TS(i) do { } while (0)
#define TSK(i) do { } while (0)
#define TSS(i) do { } while (0)
#define TST(i)
#define TSG(i)

__device__ __forceinline__ uint32_t smem_u32(const void* p) { return (uint32_t)__cvta_generic_to_shared(p); }
__device__ __forceinline__ void mbar_init(uint32_t bar, uint32_t cnt) {
  asm volatile("mbarrier.init.shared::cta.b64 [%0], %1;" ::"r"(bar), "r"(cnt));
}
__device__ __forceinline__ void mbar_expect_tx(uint32_t bar, uint32_t bytes) {
  asm volatile("mbarrier.arrive.expect_tx.shared::cta.b64 _, [%0], %1;" ::"r"(bar), "r"(bytes) : "memory");
}
__device__ __forceinline__ uint32_t map_cta(uint32_t addr, uint32_t cta) {
  uint32_t r;
  asm("mapa.shared::cluster.u32 %0, %1, %2;" : "=r"(r) : "r"(addr), "r"(cta));
  return r;
}
__device__ __forceinline__ void mbar_arrive_cluster_if(uint32_t bar, bool cond) {
  asm volatile("{\n.reg .pred p;\nsetp.ne.u32 p, %1, 0;\n@p mbarrier.arrive.shared::cluster.b64 _, [%0];\n}\n"
               ::"r"(bar), "r"((uint32_t)cond) : "memory");
}
__device__ __forceinline__ void mbar_wait(uint32_t bar, uint32_t parity) {
  asm volatile("{\n.reg .pred p;\nLAB_WAIT:\nmbarrier.try_wait.parity.shared::cta.b64 p, [%0], %1;\n@!p bra LAB_WAIT;\n}\n"
               ::"r"(bar), "r"(parity) : "memory");
  return;
  asm volatile("{\n.reg .pred p;\n.reg .u32 c;\nmov.u32 c, 0;\n"
               "LAB_WAIT:\nmbarrier.try_wait.parity.shared::cta.b64 p, [%0], %1;\n@p bra LAB_DONE;\n"
               "add.u32 c, c, 1;\nsetp.lt.u32 p, c, 2000000;\n@p bra LAB_WAIT;\ntrap;\nLAB_DONE:\n}\n"
               ::"r"(bar), "r"(parity) : "memory");
}
__device__ __forceinline__ void mbar_arrive(uint32_t bar) {
  asm volatile("mbarrier.arrive.shared::cta.b64 _, [%0];" ::"r"(bar) : "memory");
}
__device__ __forceinline__ void flag_signal(uint32_t* flag) {
  asm volatile("red.release.gpu.global.add.u32 [%0], 1;" ::"l"(flag) : "memory");
}
__device__ __forceinline__ void st_b128(uint4* p, uint32_t a, uint32_t b, uint32_t c, uint32_t d) {
  asm volatile("{\n.reg .b128 t;\n.reg .b64 lo, hi;\nmov.b64 lo, {%1,%2};\nmov.b64 hi, {%3,%4};\nmov.b128 t, {lo, hi};\n"
               "st.relaxed.gpu.global.b128 [%0], t;\n}\n" ::"l"(p), "r"(a), "r"(b), "r"(c), "r"(d) : "memory");
}
__device__ __forceinline__ uint4 ld_b128(const uint4* p) {
  uint4 v;
  asm volatile("{\n.reg .b128 t;\n.reg .b64 lo, hi;\nld.relaxed.gpu.global.b128 t, [%4];\nmov.b128 {lo, hi}, t;\n"
               "mov.b64 {%0,%1}, lo;\nmov.b64 {%2,%3}, hi;\n}\n" : "=r"(v.x), "=r"(v.y), "=r"(v.z), "=r"(v.w) : "l"(p) : "memory");
  return v;
}
__device__ __forceinline__ uint32_t ld_epoch(Scratch* sc) {
  uint32_t v;
  asm volatile("ld.relaxed.gpu.global.u32 %0, [%1];" : "=r"(v) : "l"(sc->epoch) : "memory");
  return v + 1;
}
__device__ __forceinline__ void flag_wait(uint32_t* flag, uint32_t target) {
  asm volatile("{\n.reg .pred p;\n.reg .u32 c, v;\nmov.u32 c, 0;\n"
               "LAB_WAIT:\nld.relaxed.gpu.global.u32 v, [%0];\nsub.u32 v, v, %1;\nsetp.ge.s32 p, v, 0;\n@p bra LAB_DONE;\n"
               "add.u32 c, c, 1;\nsetp.lt.u32 p, c, 4000000;\n@p bra LAB_WAIT;\ntrap;\nLAB_DONE:\n}\n"
               ::"l"(flag), "r"(target) : "memory");
}
__device__ __forceinline__ int fresh_tid() {
  int v;
  asm volatile("mov.u32 %0, %%tid.x;" : "=r"(v));
  return v;
}
constexpr uint32_t kPoison = 0xFFFFFFFFu;
__device__ __forceinline__ bool elect_one() {
  uint32_t p;
  asm volatile("{\n.reg .pred P;\nelect.sync _|P, 0xffffffff;\nselp.u32 %0, 1, 0, P;\n}\n" : "=r"(p));
  return p != 0;
}
__device__ __forceinline__ void fence_async() { asm volatile("fence.acquire.gpu;\nfence.proxy.async.global;" ::: "memory"); }
__device__ __forceinline__ void fence_async_smem() { asm volatile("fence.proxy.async.shared::cta;" ::: "memory"); }
__device__ __forceinline__ void nb_sync(int id, int n) { asm volatile("bar.sync %0, %1;" ::"r"(id), "r"(n) : "memory"); }
__device__ __forceinline__ void nb_arrive(int id, int n) { asm volatile("bar.arrive %0, %1;" ::"r"(id), "r"(n) : "memory"); }

__device__ __forceinline__ void tma2d(uint32_t dst, const CUtensorMap* m, int c0, int c1, uint32_t bar) {
  asm volatile("cp.async.bulk.tensor.2d.shared::cluster.global.mbarrier::complete_tx::bytes [%0], [%1, {%3, %4}], [%2];"
               ::"r"(dst), "l"(m), "r"(bar), "r"(c0), "r"(c1) : "memory");
}
__device__ __forceinline__ void tma2d_mc(uint32_t dst, const CUtensorMap* m, int c0, int c1, uint32_t bar) {
  asm volatile("cp.async.bulk.tensor.2d.shared::cluster.global.mbarrier::complete_tx::bytes.multicast::cluster"
               " [%0], [%1, {%3, %4}], [%2], %5;"
               ::"r"(dst), "l"(m), "r"(bar), "r"(c0), "r"(c1), "h"((uint16_t)3) : "memory");
}
__device__ __forceinline__ void tma3d(uint32_t dst, const CUtensorMap* m, int c0, int c1, int c2, uint32_t bar) {
  asm volatile("cp.async.bulk.tensor.3d.shared::cluster.global.mbarrier::complete_tx::bytes [%0], [%1, {%3, %4, %5}], [%2];"
               ::"r"(dst), "l"(m), "r"(bar), "r"(c0), "r"(c1), "r"(c2) : "memory");
}
__device__ __forceinline__ void tma_store2d(const CUtensorMap* m, uint32_t src, int c0, int c1) {
  asm volatile("cp.async.bulk.tensor.2d.global.shared::cta.bulk_group [%0, {%2, %3}], [%1];"
               ::"l"(m), "r"(src), "r"(c0), "r"(c1) : "memory");
}
__device__ __forceinline__ void tma_store3d(const CUtensorMap* m, uint32_t src, int c0, int c1, int c2) {
  asm volatile("cp.async.bulk.tensor.3d.global.shared::cta.bulk_group [%0, {%2, %3, %4}], [%1];"
               ::"l"(m), "r"(src), "r"(c0), "r"(c1), "r"(c2) : "memory");
}
__device__ __forceinline__ void tma_prefetch2d(const CUtensorMap* m, int c0, int c1) {
  asm volatile("cp.async.bulk.prefetch.tensor.2d.L2.global [%0, {%1, %2}];" ::"l"(m), "r"(c0), "r"(c1) : "memory");
}
__device__ __forceinline__ void prefetch_map(const CUtensorMap* m) { asm volatile("prefetch.tensormap [%0];" ::"l"(m) : "memory"); }
__device__ __forceinline__ void bulk_commit() { asm volatile("cp.async.bulk.commit_group;" ::: "memory"); }
__device__ __forceinline__ void bulk_wait_all() { asm volatile("cp.async.bulk.wait_group 0;" ::: "memory"); }
__device__ __forceinline__ void bulk_wait_read() { asm volatile("cp.async.bulk.wait_group.read 0;" ::: "memory"); }
__device__ __forceinline__ void prefetch_l2(const void* p) { asm volatile("prefetch.global.L2 [%0];" ::"l"(p)); }
__device__ __forceinline__ void cluster_arrive() { asm volatile("barrier.cluster.arrive.relaxed.aligned;" ::: "memory"); }
__device__ __forceinline__ void cluster_wait() { asm volatile("barrier.cluster.wait.aligned;" ::: "memory"); }

__device__ __forceinline__ void wg_fence() { asm volatile("wgmma.fence.sync.aligned;" ::: "memory"); }
__device__ __forceinline__ void wg_commit() { asm volatile("wgmma.commit_group.sync.aligned;" ::: "memory"); }
template <int N> __device__ __forceinline__ void wg_wait() { asm volatile("wgmma.wait_group.sync.aligned %0;" ::"n"(N) : "memory"); }
__device__ __forceinline__ uint32_t desc_lo(uint32_t addr, uint32_t lbo) { return ((addr & 0x3FFFF) >> 4) | ((lbo >> 4) << 16); }
__device__ __forceinline__ uint64_t desc(uint32_t lo) { return (uint64_t)lo | (0x40000040ull << 32); }
constexpr int kToB = (16384 >> 4) + ((8192 - 16) >> 4 << 16);

__device__ __forceinline__ void wgmma_n128(float (&d)[96], uint64_t da, uint64_t db) {
  asm volatile(
      "wgmma.mma_async.sync.aligned.m64n128k16.f32.bf16.bf16 {"
      "%0, %1, %2, %3, %4, %5, %6, %7, %8, %9, %10, %11, %12, %13, %14, %15, "
      "%16, %17, %18, %19, %20, %21, %22, %23, %24, %25, %26, %27, %28, %29, %30, %31, "
      "%32, %33, %34, %35, %36, %37, %38, %39, %40, %41, %42, %43, %44, %45, %46, %47, "
      "%48, %49, %50, %51, %52, %53, %54, %55, %56, %57, %58, %59, %60, %61, %62, %63}, "
      "%64, %65, 1, 1, 1, 0, 1;\n"
      :
        "+f"(d[0]), "+f"(d[1]), "+f"(d[2]), "+f"(d[3]), "+f"(d[4]), "+f"(d[5]), "+f"(d[6]), "+f"(d[7]),
        "+f"(d[8]), "+f"(d[9]), "+f"(d[10]), "+f"(d[11]), "+f"(d[12]), "+f"(d[13]), "+f"(d[14]), "+f"(d[15]),
        "+f"(d[16]), "+f"(d[17]), "+f"(d[18]), "+f"(d[19]), "+f"(d[20]), "+f"(d[21]), "+f"(d[22]), "+f"(d[23]),
        "+f"(d[24]), "+f"(d[25]), "+f"(d[26]), "+f"(d[27]), "+f"(d[28]), "+f"(d[29]), "+f"(d[30]), "+f"(d[31]),
        "+f"(d[32]), "+f"(d[33]), "+f"(d[34]), "+f"(d[35]), "+f"(d[36]), "+f"(d[37]), "+f"(d[38]), "+f"(d[39]),
        "+f"(d[40]), "+f"(d[41]), "+f"(d[42]), "+f"(d[43]), "+f"(d[44]), "+f"(d[45]), "+f"(d[46]), "+f"(d[47]),
        "+f"(d[48]), "+f"(d[49]), "+f"(d[50]), "+f"(d[51]), "+f"(d[52]), "+f"(d[53]), "+f"(d[54]), "+f"(d[55]),
        "+f"(d[56]), "+f"(d[57]), "+f"(d[58]), "+f"(d[59]), "+f"(d[60]), "+f"(d[61]), "+f"(d[62]), "+f"(d[63])
      : "l"(da), "l"(db));
}

__device__ __forceinline__ void wgmma_n256(float (&d)[128], uint64_t da, uint64_t db) {
  asm volatile(
      "wgmma.mma_async.sync.aligned.m64n256k16.f32.bf16.bf16 {"
      "%0, %1, %2, %3, %4, %5, %6, %7, %8, %9, %10, %11, %12, %13, %14, %15, "
      "%16, %17, %18, %19, %20, %21, %22, %23, %24, %25, %26, %27, %28, %29, %30, %31, "
      "%32, %33, %34, %35, %36, %37, %38, %39, %40, %41, %42, %43, %44, %45, %46, %47, "
      "%48, %49, %50, %51, %52, %53, %54, %55, %56, %57, %58, %59, %60, %61, %62, %63, "
      "%64, %65, %66, %67, %68, %69, %70, %71, %72, %73, %74, %75, %76, %77, %78, %79, "
      "%80, %81, %82, %83, %84, %85, %86, %87, %88, %89, %90, %91, %92, %93, %94, %95, "
      "%96, %97, %98, %99, %100, %101, %102, %103, %104, %105, %106, %107, %108, %109, %110, %111, "
      "%112, %113, %114, %115, %116, %117, %118, %119, %120, %121, %122, %123, %124, %125, %126, %127}, "
      "%128, %129, 1, 1, 1, 0, 1;\n"
      :
        "+f"(d[0]), "+f"(d[1]), "+f"(d[2]), "+f"(d[3]), "+f"(d[4]), "+f"(d[5]), "+f"(d[6]), "+f"(d[7]),
        "+f"(d[8]), "+f"(d[9]), "+f"(d[10]), "+f"(d[11]), "+f"(d[12]), "+f"(d[13]), "+f"(d[14]), "+f"(d[15]),
        "+f"(d[16]), "+f"(d[17]), "+f"(d[18]), "+f"(d[19]), "+f"(d[20]), "+f"(d[21]), "+f"(d[22]), "+f"(d[23]),
        "+f"(d[24]), "+f"(d[25]), "+f"(d[26]), "+f"(d[27]), "+f"(d[28]), "+f"(d[29]), "+f"(d[30]), "+f"(d[31]),
        "+f"(d[32]), "+f"(d[33]), "+f"(d[34]), "+f"(d[35]), "+f"(d[36]), "+f"(d[37]), "+f"(d[38]), "+f"(d[39]),
        "+f"(d[40]), "+f"(d[41]), "+f"(d[42]), "+f"(d[43]), "+f"(d[44]), "+f"(d[45]), "+f"(d[46]), "+f"(d[47]),
        "+f"(d[48]), "+f"(d[49]), "+f"(d[50]), "+f"(d[51]), "+f"(d[52]), "+f"(d[53]), "+f"(d[54]), "+f"(d[55]),
        "+f"(d[56]), "+f"(d[57]), "+f"(d[58]), "+f"(d[59]), "+f"(d[60]), "+f"(d[61]), "+f"(d[62]), "+f"(d[63]),
        "+f"(d[64]), "+f"(d[65]), "+f"(d[66]), "+f"(d[67]), "+f"(d[68]), "+f"(d[69]), "+f"(d[70]), "+f"(d[71]),
        "+f"(d[72]), "+f"(d[73]), "+f"(d[74]), "+f"(d[75]), "+f"(d[76]), "+f"(d[77]), "+f"(d[78]), "+f"(d[79]),
        "+f"(d[80]), "+f"(d[81]), "+f"(d[82]), "+f"(d[83]), "+f"(d[84]), "+f"(d[85]), "+f"(d[86]), "+f"(d[87]),
        "+f"(d[88]), "+f"(d[89]), "+f"(d[90]), "+f"(d[91]), "+f"(d[92]), "+f"(d[93]), "+f"(d[94]), "+f"(d[95]),
        "+f"(d[96]), "+f"(d[97]), "+f"(d[98]), "+f"(d[99]), "+f"(d[100]), "+f"(d[101]), "+f"(d[102]), "+f"(d[103]),
        "+f"(d[104]), "+f"(d[105]), "+f"(d[106]), "+f"(d[107]), "+f"(d[108]), "+f"(d[109]), "+f"(d[110]), "+f"(d[111]),
        "+f"(d[112]), "+f"(d[113]), "+f"(d[114]), "+f"(d[115]), "+f"(d[116]), "+f"(d[117]), "+f"(d[118]), "+f"(d[119]),
        "+f"(d[120]), "+f"(d[121]), "+f"(d[122]), "+f"(d[123]), "+f"(d[124]), "+f"(d[125]), "+f"(d[126]), "+f"(d[127])
      : "l"(da), "l"(db));
}

__device__ __forceinline__ void wgmma_n256_first(float (&d)[128], uint64_t da, uint64_t db) {
  asm volatile(
      "wgmma.mma_async.sync.aligned.m64n256k16.f32.bf16.bf16 {"
      "%0, %1, %2, %3, %4, %5, %6, %7, %8, %9, %10, %11, %12, %13, %14, %15, "
      "%16, %17, %18, %19, %20, %21, %22, %23, %24, %25, %26, %27, %28, %29, %30, %31, "
      "%32, %33, %34, %35, %36, %37, %38, %39, %40, %41, %42, %43, %44, %45, %46, %47, "
      "%48, %49, %50, %51, %52, %53, %54, %55, %56, %57, %58, %59, %60, %61, %62, %63, "
      "%64, %65, %66, %67, %68, %69, %70, %71, %72, %73, %74, %75, %76, %77, %78, %79, "
      "%80, %81, %82, %83, %84, %85, %86, %87, %88, %89, %90, %91, %92, %93, %94, %95, "
      "%96, %97, %98, %99, %100, %101, %102, %103, %104, %105, %106, %107, %108, %109, %110, %111, "
      "%112, %113, %114, %115, %116, %117, %118, %119, %120, %121, %122, %123, %124, %125, %126, %127}, "
      "%128, %129, 0, 1, 1, 0, 1;\n"
      :
        "=f"(d[0]), "=f"(d[1]), "=f"(d[2]), "=f"(d[3]), "=f"(d[4]), "=f"(d[5]), "=f"(d[6]), "=f"(d[7]),
        "=f"(d[8]), "=f"(d[9]), "=f"(d[10]), "=f"(d[11]), "=f"(d[12]), "=f"(d[13]), "=f"(d[14]), "=f"(d[15]),
        "=f"(d[16]), "=f"(d[17]), "=f"(d[18]), "=f"(d[19]), "=f"(d[20]), "=f"(d[21]), "=f"(d[22]), "=f"(d[23]),
        "=f"(d[24]), "=f"(d[25]), "=f"(d[26]), "=f"(d[27]), "=f"(d[28]), "=f"(d[29]), "=f"(d[30]), "=f"(d[31]),
        "=f"(d[32]), "=f"(d[33]), "=f"(d[34]), "=f"(d[35]), "=f"(d[36]), "=f"(d[37]), "=f"(d[38]), "=f"(d[39]),
        "=f"(d[40]), "=f"(d[41]), "=f"(d[42]), "=f"(d[43]), "=f"(d[44]), "=f"(d[45]), "=f"(d[46]), "=f"(d[47]),
        "=f"(d[48]), "=f"(d[49]), "=f"(d[50]), "=f"(d[51]), "=f"(d[52]), "=f"(d[53]), "=f"(d[54]), "=f"(d[55]),
        "=f"(d[56]), "=f"(d[57]), "=f"(d[58]), "=f"(d[59]), "=f"(d[60]), "=f"(d[61]), "=f"(d[62]), "=f"(d[63]),
        "=f"(d[64]), "=f"(d[65]), "=f"(d[66]), "=f"(d[67]), "=f"(d[68]), "=f"(d[69]), "=f"(d[70]), "=f"(d[71]),
        "=f"(d[72]), "=f"(d[73]), "=f"(d[74]), "=f"(d[75]), "=f"(d[76]), "=f"(d[77]), "=f"(d[78]), "=f"(d[79]),
        "=f"(d[80]), "=f"(d[81]), "=f"(d[82]), "=f"(d[83]), "=f"(d[84]), "=f"(d[85]), "=f"(d[86]), "=f"(d[87]),
        "=f"(d[88]), "=f"(d[89]), "=f"(d[90]), "=f"(d[91]), "=f"(d[92]), "=f"(d[93]), "=f"(d[94]), "=f"(d[95]),
        "=f"(d[96]), "=f"(d[97]), "=f"(d[98]), "=f"(d[99]), "=f"(d[100]), "=f"(d[101]), "=f"(d[102]), "=f"(d[103]),
        "=f"(d[104]), "=f"(d[105]), "=f"(d[106]), "=f"(d[107]), "=f"(d[108]), "=f"(d[109]), "=f"(d[110]), "=f"(d[111]),
        "=f"(d[112]), "=f"(d[113]), "=f"(d[114]), "=f"(d[115]), "=f"(d[116]), "=f"(d[117]), "=f"(d[118]), "=f"(d[119]),
        "=f"(d[120]), "=f"(d[121]), "=f"(d[122]), "=f"(d[123]), "=f"(d[124]), "=f"(d[125]), "=f"(d[126]), "=f"(d[127])
      : "l"(da), "l"(db));
}

__device__ __forceinline__ void wgmma_n192(float (&d)[96], uint64_t da, uint64_t db) {
  asm volatile(
      "wgmma.mma_async.sync.aligned.m64n192k16.f32.bf16.bf16 {"
      "%0, %1, %2, %3, %4, %5, %6, %7, %8, %9, %10, %11, %12, %13, %14, %15, "
      "%16, %17, %18, %19, %20, %21, %22, %23, %24, %25, %26, %27, %28, %29, %30, %31, "
      "%32, %33, %34, %35, %36, %37, %38, %39, %40, %41, %42, %43, %44, %45, %46, %47, "
      "%48, %49, %50, %51, %52, %53, %54, %55, %56, %57, %58, %59, %60, %61, %62, %63, "
      "%64, %65, %66, %67, %68, %69, %70, %71, %72, %73, %74, %75, %76, %77, %78, %79, "
      "%80, %81, %82, %83, %84, %85, %86, %87, %88, %89, %90, %91, %92, %93, %94, %95}, "
      "%96, %97, 1, 1, 1, 0, 1;\n"
      :
        "+f"(d[0]), "+f"(d[1]), "+f"(d[2]), "+f"(d[3]), "+f"(d[4]), "+f"(d[5]), "+f"(d[6]), "+f"(d[7]),
        "+f"(d[8]), "+f"(d[9]), "+f"(d[10]), "+f"(d[11]), "+f"(d[12]), "+f"(d[13]), "+f"(d[14]), "+f"(d[15]),
        "+f"(d[16]), "+f"(d[17]), "+f"(d[18]), "+f"(d[19]), "+f"(d[20]), "+f"(d[21]), "+f"(d[22]), "+f"(d[23]),
        "+f"(d[24]), "+f"(d[25]), "+f"(d[26]), "+f"(d[27]), "+f"(d[28]), "+f"(d[29]), "+f"(d[30]), "+f"(d[31]),
        "+f"(d[32]), "+f"(d[33]), "+f"(d[34]), "+f"(d[35]), "+f"(d[36]), "+f"(d[37]), "+f"(d[38]), "+f"(d[39]),
        "+f"(d[40]), "+f"(d[41]), "+f"(d[42]), "+f"(d[43]), "+f"(d[44]), "+f"(d[45]), "+f"(d[46]), "+f"(d[47]),
        "+f"(d[48]), "+f"(d[49]), "+f"(d[50]), "+f"(d[51]), "+f"(d[52]), "+f"(d[53]), "+f"(d[54]), "+f"(d[55]),
        "+f"(d[56]), "+f"(d[57]), "+f"(d[58]), "+f"(d[59]), "+f"(d[60]), "+f"(d[61]), "+f"(d[62]), "+f"(d[63]),
        "+f"(d[64]), "+f"(d[65]), "+f"(d[66]), "+f"(d[67]), "+f"(d[68]), "+f"(d[69]), "+f"(d[70]), "+f"(d[71]),
        "+f"(d[72]), "+f"(d[73]), "+f"(d[74]), "+f"(d[75]), "+f"(d[76]), "+f"(d[77]), "+f"(d[78]), "+f"(d[79]),
        "+f"(d[80]), "+f"(d[81]), "+f"(d[82]), "+f"(d[83]), "+f"(d[84]), "+f"(d[85]), "+f"(d[86]), "+f"(d[87]),
        "+f"(d[88]), "+f"(d[89]), "+f"(d[90]), "+f"(d[91]), "+f"(d[92]), "+f"(d[93]), "+f"(d[94]), "+f"(d[95])
      : "l"(da), "l"(db));
}

__device__ __forceinline__ void wgmma_n192_rs(float (&d)[96], uint32_t a0, uint32_t a1, uint32_t a23, uint64_t db) {
  asm volatile(
      "wgmma.mma_async.sync.aligned.m64n192k16.f32.bf16.bf16 {"
      "%0, %1, %2, %3, %4, %5, %6, %7, %8, %9, %10, %11, %12, %13, %14, %15, "
      "%16, %17, %18, %19, %20, %21, %22, %23, %24, %25, %26, %27, %28, %29, %30, %31, "
      "%32, %33, %34, %35, %36, %37, %38, %39, %40, %41, %42, %43, %44, %45, %46, %47, "
      "%48, %49, %50, %51, %52, %53, %54, %55, %56, %57, %58, %59, %60, %61, %62, %63, "
      "%64, %65, %66, %67, %68, %69, %70, %71, %72, %73, %74, %75, %76, %77, %78, %79, "
      "%80, %81, %82, %83, %84, %85, %86, %87, %88, %89, %90, %91, %92, %93, %94, %95}, "
      "{%96, %97, %98, %98}, %99, 1, 1, 1, 1;\n"
      :
        "+f"(d[0]), "+f"(d[1]), "+f"(d[2]), "+f"(d[3]), "+f"(d[4]), "+f"(d[5]), "+f"(d[6]), "+f"(d[7]),
        "+f"(d[8]), "+f"(d[9]), "+f"(d[10]), "+f"(d[11]), "+f"(d[12]), "+f"(d[13]), "+f"(d[14]), "+f"(d[15]),
        "+f"(d[16]), "+f"(d[17]), "+f"(d[18]), "+f"(d[19]), "+f"(d[20]), "+f"(d[21]), "+f"(d[22]), "+f"(d[23]),
        "+f"(d[24]), "+f"(d[25]), "+f"(d[26]), "+f"(d[27]), "+f"(d[28]), "+f"(d[29]), "+f"(d[30]), "+f"(d[31]),
        "+f"(d[32]), "+f"(d[33]), "+f"(d[34]), "+f"(d[35]), "+f"(d[36]), "+f"(d[37]), "+f"(d[38]), "+f"(d[39]),
        "+f"(d[40]), "+f"(d[41]), "+f"(d[42]), "+f"(d[43]), "+f"(d[44]), "+f"(d[45]), "+f"(d[46]), "+f"(d[47]),
        "+f"(d[48]), "+f"(d[49]), "+f"(d[50]), "+f"(d[51]), "+f"(d[52]), "+f"(d[53]), "+f"(d[54]), "+f"(d[55]),
        "+f"(d[56]), "+f"(d[57]), "+f"(d[58]), "+f"(d[59]), "+f"(d[60]), "+f"(d[61]), "+f"(d[62]), "+f"(d[63]),
        "+f"(d[64]), "+f"(d[65]), "+f"(d[66]), "+f"(d[67]), "+f"(d[68]), "+f"(d[69]), "+f"(d[70]), "+f"(d[71]),
        "+f"(d[72]), "+f"(d[73]), "+f"(d[74]), "+f"(d[75]), "+f"(d[76]), "+f"(d[77]), "+f"(d[78]), "+f"(d[79]),
        "+f"(d[80]), "+f"(d[81]), "+f"(d[82]), "+f"(d[83]), "+f"(d[84]), "+f"(d[85]), "+f"(d[86]), "+f"(d[87]),
        "+f"(d[88]), "+f"(d[89]), "+f"(d[90]), "+f"(d[91]), "+f"(d[92]), "+f"(d[93]), "+f"(d[94]), "+f"(d[95])
      : "r"(a0), "r"(a1), "r"(a23), "l"(db));
}

__device__ __forceinline__ uint32_t pack_bf16(float lo, float hi) {
  uint32_t r;
  asm("cvt.rn.bf16x2.f32 %0, %1, %2;" : "=r"(r) : "f"(hi), "f"(lo));
  return r;
}
__device__ __forceinline__ float bf_lo(uint32_t v) { return __uint_as_float(v << 16); }
__device__ __forceinline__ float bf_hi(uint32_t v) { return __uint_as_float(v & 0xFFFF0000u); }
__device__ __forceinline__ float ex2(float x) { float r; asm("ex2.approx.ftz.f32 %0, %1;" : "=f"(r) : "f"(x)); return r; }
__device__ __forceinline__ float rcp(float x) { float r; asm("rcp.approx.ftz.f32 %0, %1;" : "=f"(r) : "f"(x)); return r; }
__device__ __forceinline__ uint32_t movm(uint32_t a) {
  uint32_t d;
  asm volatile("movmatrix.sync.aligned.m8n8.trans.b16 %0, %1;" : "=r"(d) : "r"(a));
  return d;
}
__device__ __forceinline__ void mma16816(float (&c)[4], uint32_t a0, uint32_t a1, uint32_t a2, uint32_t a3, uint32_t b0, uint32_t b1) {
  asm volatile("mma.sync.aligned.m16n8k16.row.col.f32.bf16.bf16.f32 {%0,%1,%2,%3}, {%4,%5,%6,%7}, {%8,%9}, {%0,%1,%2,%3};"
               : "+f"(c[0]), "+f"(c[1]), "+f"(c[2]), "+f"(c[3]) : "r"(a0), "r"(a1), "r"(a2), "r"(a3), "r"(b0), "r"(b1));
}
__device__ __forceinline__ void mma1688(float (&c)[4], uint32_t a0, uint32_t a1, uint32_t b0) {
  asm volatile("mma.sync.aligned.m16n8k8.row.col.f32.bf16.bf16.f32 {%0,%1,%2,%3}, {%4,%5}, {%6}, {%0,%1,%2,%3};"
               : "+f"(c[0]), "+f"(c[1]), "+f"(c[2]), "+f"(c[3]) : "r"(a0), "r"(a1), "r"(b0));
}
__device__ __forceinline__ void stsm4(uint32_t addr, uint32_t a, uint32_t b, uint32_t c, uint32_t d) {
  asm volatile("stmatrix.sync.aligned.m8n8.x4.shared.b16 [%0], {%1,%2,%3,%4};" ::"r"(addr), "r"(a), "r"(b), "r"(c), "r"(d) : "memory");
}
__device__ __forceinline__ void stsm4_t(uint32_t addr, uint32_t a, uint32_t b, uint32_t c, uint32_t d) {
  asm volatile("stmatrix.sync.aligned.m8n8.x4.trans.shared.b16 [%0], {%1,%2,%3,%4};" ::"r"(addr), "r"(a), "r"(b), "r"(c), "r"(d) : "memory");
}
__device__ __forceinline__ void ldsm4(uint32_t addr, uint32_t (&v)[4]) {
  asm volatile("ldmatrix.sync.aligned.m8n8.x4.shared.b16 {%0,%1,%2,%3}, [%4];"
               : "=r"(v[0]), "=r"(v[1]), "=r"(v[2]), "=r"(v[3]) : "r"(addr) : "memory");
}
__device__ __forceinline__ void sts128(uint32_t addr, uint4 v) {
  asm volatile("st.shared.v4.b32 [%0], {%1,%2,%3,%4};" ::"r"(addr), "r"(v.x), "r"(v.y), "r"(v.z), "r"(v.w) : "memory");
}
__device__ __forceinline__ uint4 lds128(uint32_t addr) {
  uint4 v;
  asm volatile("ld.shared.v4.b32 {%0,%1,%2,%3}, [%4];" : "=r"(v.x), "=r"(v.y), "=r"(v.z), "=r"(v.w) : "r"(addr) : "memory");
  return v;
}
__device__ __forceinline__ void sts64(uint32_t addr, uint32_t a, uint32_t b) {
  asm volatile("st.shared.v2.b32 [%0], {%1,%2};" ::"r"(addr), "r"(a), "r"(b) : "memory");
}
__device__ __forceinline__ void sts32(uint32_t addr, uint32_t a) { asm volatile("st.shared.b32 [%0], %1;" ::"r"(addr), "r"(a) : "memory"); }
__device__ __forceinline__ uint32_t lds32(uint32_t addr) {
  uint32_t v;
  asm volatile("ld.shared.b32 %0, [%1];" : "=r"(v) : "r"(addr) : "memory");
  return v;
}
__device__ __forceinline__ float2 lds64f_const(uint32_t addr) {
  float2 v;
  asm("ld.shared.v2.f32 {%0,%1}, [%2];" : "=f"(v.x), "=f"(v.y) : "r"(addr));
  return v;
}
template <int N, bool PAIR>
__device__ __forceinline__ void load_tagged(uint3 (&out)[N], const uint4* src, int stride, uint32_t tag) {
  uint32_t bad;
  int spins = 0;
  do {
    if (spins != 0) __nanosleep(kBackoffNs);
    if (++spins > 2000000) __trap();
    bad = 0;
#pragma unroll
    for (int i = 0; i < N; i++) {
      const uint4 v = ld_b128(src + i * stride);
      out[i] = make_uint3(v.x, v.y, v.z);
      bad |= (v.w ^ tag) | (PAIR ? v.z ^ tag : 0);
    }
  } while (__any_sync(~0u, bad != 0));
}
__device__ __forceinline__ void sts64f(uint32_t addr, float2 v) { sts64(addr, __float_as_uint(v.x), __float_as_uint(v.y)); }
__device__ __forceinline__ float bf_rest(float v) { return v - __uint_as_float(__float_as_uint(v) & 0xFFFF0000u); }
__device__ __forceinline__ uint32_t bf_upper(float lo, float hi) { return __byte_perm(__float_as_uint(lo), __float_as_uint(hi), 0x7632); }
__device__ __forceinline__ float low_peak(uint4 v) {
  asm("max.xorsign.abs.bf16x2 %0, %0, %1;" : "+r"(v.x) : "r"(v.y));
  asm("max.xorsign.abs.bf16x2 %0, %0, %1;" : "+r"(v.z) : "r"(v.w));
  asm("max.xorsign.abs.bf16x2 %0, %0, %1;" : "+r"(v.x) : "r"(v.z));
  asm("max.xorsign.abs.bf16x2 %0, %0, %1;" : "+r"(v.x) : "r"(v.x << 16));
  return __uint_as_float(__reduce_min_sync(~0u, v.x & 0x7FFF0000u));
}
__device__ __forceinline__ float bias_at(float v) { return __uint_as_float((__float_as_uint(fminf(v, 1e37f)) & 0x7F800000u) | 0x00400000u); }
struct RowConst {
  float nmean, k0, k1, half;
};
__device__ __forceinline__ float gate_scale(float t, const RowConst& k) {
  float th;
  asm("tanh.approx.f32 %0, %1;" : "=f"(th) : "f"(t * fmaf(t * t, k.k1, k.k0)));
  return fmaf(th, k.half, k.half);
}

template <int N>
__device__ __forceinline__ void mma_k16(float (&acc)[2][96], uint32_t a, uint32_t b, int kk) {
#pragma unroll
  for (int m = 0; m < 2; m++) {
    const uint64_t da = desc(a) + (m * 512 + kk * 2), db = desc(b) + kk * 128;
    if (N == 128) wgmma_n128(acc[m], da, db); else wgmma_n192(acc[m], da, db);
  }
}

__device__ __forceinline__ void stage_quarter(const float* acc, uint32_t frag, uint32_t frag_x, int b, const uint4* add = nullptr) {
#pragma unroll
  for (int j = 0; j < 4; j++) {
    const float* v = acc + 8 * j;
    uint32_t h[4] = {pack_bf16(v[0], v[1]), pack_bf16(v[2], v[3]), pack_bf16(v[4], v[5]), pack_bf16(v[6], v[7])};
    if (add) {
      const uint32_t a[4] = {add[j].x, add[j].y, add[j].z, add[j].w};
#pragma unroll
      for (int e = 0; e < 4; e++) asm("add.rn.bf16x2 %0, %0, %1;" : "+r"(h[e]) : "r"(a[e]));
    }
    stsm4(frag + b * 8192 + ((frag_x ^ (j * 2)) << 4), h[0], h[1], h[2], h[3]);
  }
}

__device__ __forceinline__ int g1_block(int j, int c) { return j < 16 ? j : ((j + 12) & 15) ^ (c == 5 && j >= 28 ? 2 : 0); }
__device__ __forceinline__ int g2_block(int j, int c) { return j < 8 ? j : j == 8 ? 8 + c : j - (j - 9 < c); }
__device__ __forceinline__ int g3_tile(int j) { return j < 4 ? j >> 1 : j < 18 ? 0 : j >> 4; }
__device__ __forceinline__ int g3_block(int j, int c) {
  const int i = j < 32 ? (j < 16 ? 0xDCBA976543218080ull : 0x7654321BA9FEDCFEull) >> 4 * (j & 15) : j + (~j >> 2 & 4), o = i & 7;
  return 2 * (j < 32 && (o == c || o == 0) ? c - o : o) + (i >> 3 & 1);
}
__device__ __forceinline__ bool g3_is_up(int tile, int a) { return a == 1 || (a == 2 && tile >= 2); }
__device__ __forceinline__ int g3_atom(int tile, int a, int c) { return c * 7 + (tile & 1) * 3 + (a == 2 ? 1 : tile == 4 ? 6 : tile & 2); }
__device__ __forceinline__ int g4_block(int i) {
  return i < 16 ? 7 * (i & 7) + 3 * (i >> 3) : i < 48 ? 7 * ((i & 15) >> 1) + 3 * (i >> 5) + 1 + (i & 1) : 7 * (i & 7) + (i < 56 ? 6 : 0);
}

template <int N, int TAIL>
__device__ __forceinline__ void mainloop(Scratch* sc, float (&acc)[2][96], uint32_t sb, int ph, int j0, int nsteps, int pause_at, bool last,
                                         bool hand_over, bool local, int wg, int own = -1, const CUtensorMap* out = nullptr, int out_col = 0,
                                         int out_row = 0, int warp = 0, __nv_bfloat16* outp = nullptr) {
  constexpr int NSLOT = N == 128 ? 5 : 4, SLOT = N == 128 ? 32768 : 40960;
  const int lane = fresh_tid() & 31;
  const uint32_t full = sb + kBars + 8 * ring_base(ph);
  const uint32_t empty = map_cta(full + 8 * NSLOT, lane & 1);
  const uint32_t ring = desc_lo(sb + kRing, 16);
  int bi = j0 % NSLOT, par = (j0 / NSLOT) & 1;
  const int release_end = lane < (N == 192 && !hand_over ? 4 : 2) ? (last ? nsteps - 1 - NSLOT : nsteps) : 0;
  uint32_t rel = empty;
#pragma unroll 1
  for (int i = 0; i < nsteps - (TAIL > 0 ? TAIL + 1 : 0); i++) {
    uint32_t a = ring + bi * (SLOT >> 4), b = a + kToB;
    if (TAIL > 0 && i == 0) TSG(5);
    if (i == 0) nb_sync(kNbOrder + wg, ph == 0 && wg == 0 ? 160 : 256);
    if (ph == 0 && i == 1 - 2 * wg) cluster_wait();
    if (N == 192 && local) {
      a = ring + ((kStage + i * 16384) >> 4);
      b = ring + bi * (32768 >> 4) + desc_lo(32768, 8192) - desc_lo(0, 16);
    }
    if (ph == 0 && i >> 1 == own) a = ring + ((kOwn + (i & 1) * 16384) >> 4);
    if (ph == 1 && i == 8) a = ring + ((kStage + 32768) >> 4);
    if (TAIL > 0 && i == 0) TSG(6);
    mbar_wait(full + 8 * bi, par);
    if (N == 192 && local) mbar_wait(sb + kBars + 8 * (kHalfBar + i), 0);
    if (TAIL > 0 && i == 0) TSG(7);
    if (i == pause_at + 1) nb_sync(kNbWin + 1, 256);
    wg_fence();
    mma_k16<N>(acc, a, b, 0);
    mma_k16<N>(acc, a, b, 1);
    wg_commit();
    const bool release = (uint32_t)(i - 1) < (uint32_t)release_end;
    wg_wait<1>();
    mbar_arrive_cluster_if(rel, release);
    wg_fence();
    mma_k16<N>(acc, a, b, 2);
    mma_k16<N>(acc, a, b, 3);
    wg_commit();
    rel = empty + 8 * bi;
    if (++bi == NSLOT) { bi = 0; par ^= 1; }
    if (i == pause_at) nb_arrive(kNbWin, 256);
  }
  if (TAIL < 0) return;
  if (TAIL > 0) {
    uint32_t at[TAIL + 2];
    const int t = fresh_tid() & 127;
    uint32_t frag = sb + kStage + ((t >> 5) * 16 + (t & 15)) * 128, frag_x = ((t >> 4) & 1) ^ (t & 7);
    const uint32_t back = sb + kStage + (t >> 5) * 2048 + ((t >> 3) & 3) * 128, back_x = ((t ^ (t >> 3 & 3)) & 7) << 4;
    outp += (2 * (out_row + (t >> 5) * 16 + ((t >> 3) & 3)) + (blockIdx.x & 1)) * kD + out_col + (t & 7) * 8;
    static_assert(kTail == 5, "");
    uint4 part[8];
    mbar_wait(full + 8 * bi, par);
#pragma unroll
    for (int hf = 0; hf < 2; hf++) {
      const uint32_t a = ring + bi * (SLOT >> 4), b = a + kToB;
      wg_fence();
      mma_k16<N>(acc, a, b, 2 * hf);
      mma_k16<N>(acc, a, b, 2 * hf + 1);
      wg_commit();
      if (hf == 0) {
        wg_wait<1>();
        mbar_arrive_cluster_if(rel, (t & 31) < 2);
      }
      mbar_wait(sb + kBars + 8 * (hf ? kStgBar : kPartBar), hf);
#pragma unroll
      for (int k = 4 * hf; k < 4 * hf + 4; k++) part[k] = lds128(sb + kStage + 32768 + (t >> 5) * 4096 + (t & 31) * 16 + k * 512);
    }
    if (++bi == NSLOT) { bi = 0; par ^= 1; }
    auto last_rows = [&](int i0, int i1) {
#pragma unroll
      for (int i = i0; i < i1; i++) {
        if (i == 3) continue;
        at[i] = bi * (SLOT >> 4);
        mbar_wait(full + 8 * bi, par);
        if (++bi == NSLOT) { bi = 0; par ^= 1; }
      }
      wg_fence();
#pragma unroll
      for (int i = 4 * i0; i < 4 * i1; i++)
        wgmma_n128(acc[1], desc(ring) + ((i >> 2 != 3 ? at[i >> 2] + 512 : at[2]) + (i & 3) * 2),
                   desc(ring) + ((i >> 2 != 3 ? at[i >> 2] + kToB : at[0] + ((SLOT - 16) >> 4 << 16)) + (i & 3) * 128));
      wg_commit();
    };
    last_rows(0, 2);
#pragma unroll
    for (int b = 0; b < 4; b++) {
      if (b == 0) wg_wait<1>();
      if (b == 1) last_rows(3, 4);
      if (b == 2) wg_wait<0>();
      if (!(b & 1)) {
#pragma unroll
        for (int i = 0; i < 64; i++) asm volatile("" : "+f"(acc[b >> 1][i])::"memory");
        if (t == 0) TSS(b);
      }
      stage_quarter(&acc[b >> 1][32 * (b & 1)], frag, frag_x, b, b < 2 ? &part[4 * b] : nullptr);
      if (b == 3) {
        __syncwarp();
        uint4 v[4];
#pragma unroll
        for (int i = 0; i < 4; i++) v[i] = lds128(back + b * 8192 + i * 512 + ((i & 1) ? back_x ^ 64 : back_x));
#pragma unroll
        for (int i = 0; i < 4; i++) __stcs((uint4*)(outp + ((b >> 1) * 128 + i * 8) * kD + (b & 1) * 64), v[i]);
        if (t == 0) TSS(4 + b);
        continue;
      }
      if (b < 2) last_rows(2 + 2 * b, 3 + 2 * b);
      fence_async_smem();
      __syncwarp();
      if (elect_one()) tma_store3d(out, sb + kStage + b * 8192 + warp * 2048, out_col + (b & 1) * 64, out_row + (b >> 1) * 64 + warp * 16, blockIdx.x & 1);
      __syncwarp();
      if (t == 0) TSS(4 + b);
    }
    if (elect_one()) {
      bulk_commit();
      bulk_wait_read();
    }
    if (t == 0) TSS(1);
    return;
  }
  if (hand_over) nb_arrive(kNbOrder + (wg ^ 1), 256);
  if (N == 192 && !local) {
    mbar_wait(sb + kBars + 8 * (kAuxBar + wg), j0 < 32);
    if (j0 < 32) mbar_wait(sb + kBars + 8 * kStatBar, 1);
    mbar_wait(sb + kBars + 8 * (kStgBar + wg), ((j0 >> 5) ^ wg ^ 1) & 1);
  }
  wg_wait<0>();
  mbar_arrive_cluster_if(rel, release_end == nsteps);
#pragma unroll
  for (int i = 0; i < N / 2; i++) asm volatile("" : "+f"(acc[0][i]), "+f"(acc[1][i])::"memory");
}

template <int PH>
struct Ring {
  static constexpr int NSLOT = 4 + (PH & 1), SLOT = PH & 1 ? 32768 : 40960;
  uint32_t full, dst0;
  int j = PH == 0 ? 4 : 0, bi = 0, par = PH == 0 ? 0 : 1;
  __device__ __forceinline__ Ring(uint32_t sb, uint32_t ofs) : full(sb + kBars + 8 * (PH * 9 - (PH & 1))), dst0(sb + kRing + ofs) {}
  __device__ __forceinline__ uint32_t bar() const { return full + 8 * bi; }
  __device__ __forceinline__ uint32_t dst() const { return dst0 + bi * SLOT; }
  __device__ __forceinline__ void acquire_first() const {
    const bool first = j < NSLOT;
    mbar_wait(full + (first ? 8 * min(j, 3) - 32 : 8 * (NSLOT + bi)), PH == 2 && first ? 0 : par);
  }
  __device__ __forceinline__ void acquire() const { mbar_wait(full + 8 * (NSLOT + bi), par); }
  __device__ __forceinline__ void next() {
    j++;
    if (++bi == NSLOT) { bi = 0; par ^= 1; }
  }
};

__device__ __forceinline__ void check_blocks(const Params& p, Scratch* sc, uint32_t sb, int r, int c, bool g3, uint32_t& par) {
  const int lane = fresh_tid() & 31, nslot = g3 ? 4 : 5, slot_bytes = g3 ? 40960 : 32768;
  const uint32_t mine = (lane >> 2) * 132 + (lane & 3) * 32, ring_end = sb + kRing + kStage + mine;
  const uint32_t to_full = 8 * (kLandBar - (g3 ? ring_base(2) : ring_base(1)));
  uint32_t src = sb + kRing + mine + (g3 ? 0 : 4 * 32768);
  int bi = g3 ? 0 : 4, spins = 0;
#pragma unroll 1
  for (int i = g3 ? 2 : 9; i < 16;) {
    const uint32_t land = sb + kBars + 8 * (kLandBar + bi);
    mbar_wait(land, (par >> bi) & 1);
    uint32_t v[16];
#pragma unroll
    for (int k = 0; k < 16; k++) v[k] = lds32(src + k * 1024);
#pragma unroll
    for (int k = 0; k < 5; k++) v[k] = max(max(v[3 * k + 1], v[3 * k + 2]), k ? v[3 * k] : max(v[0], v[15]));
    const bool again = __any_sync(~0u, max(max(max(v[0], v[1]), v[2]), max(v[3], v[4])) == kPoison);
    asm volatile("{\n.reg .pred p;\nsetp.eq.u32 p, %1, 0;\n@p mbarrier.arrive.shared::cta.b64 _, [%0];\n}\n"
                 ::"r"(land - to_full), "r"(lane + again) : "memory");
    par ^= 1u << bi;
    if (again) {
      if (++spins > 100000) __trap();
      if (elect_one()) {
        mbar_expect_tx(land, 16384);
        tma2d(src - mine, g3 ? &p.h : &p.o, (g3 ? g3_block(i + 2, c) : g2_block(i, c)) * 64, r * 128, land);
      }
      nb_sync(kNbSelf + 1, 32);
      continue;
    }
    if (lane == 0 && (i == 2 || i == 3 || (!g3 && (i == 9 || i == 12)))) TS(i < 4 ? 88 + 2 * i : i == 9 ? 120 : 122);
    i++;
    if (++bi == nslot) bi = 0;
    src += slot_bytes;
    if (src == ring_end) src -= kStage;
  }
}

__device__ __forceinline__ void colsum_cta(const Params& p, Scratch* sc, uint32_t sb, int warp, int bid) {
  constexpr int kSlots = 4, kSlot = 49152;
  constexpr int kRows = kTail * 32768;
  static_assert(kRows + 65536 <= kCs, "");
  const int lane = threadIdx.x & 31, c0 = (bid - 128) * 2;
  const uint32_t full = sb + kBars, empty = full + 8 * kSlots;
  const uint32_t event = full + 64, stored = full + 96, rfull = full + 128, rempty = full + 192;
  if (threadIdx.x == 0) {
#pragma unroll 1
    for (int i = 0; i < 32; i++) mbar_init(full + 8 * i, i & (i < 16 ? 4 : 8) ? 8 : 1);
    asm volatile("fence.mbarrier_init.release.cluster;" ::: "memory");
  }
  __syncthreads();
  const uint32_t ep = ld_epoch(sc);
  if (warp == 8) {
    if (elect_one()) {
#pragma unroll 1
      for (int n = 0; n < 112 + kSlots; n++) {
        const int u = n >> 4, c = c0 + ((n >> 3) & 1), k0 = (n & 7) * 128, slot = n & (kSlots - 1);
        if (n == kQuietAt) flag_wait(sc->flags + kFlPace, ep);
        const uint32_t bar = full + 8 * slot;
        mbar_wait(empty + 8 * slot, ((n / kSlots) & 1) ^ 1);
        if (n == 108) mbar_arrive(event);
        if (u == 7) continue;
        mbar_expect_tx(bar, u == 6 ? 32768 : 49152);
#pragma unroll
        for (int a = 0; a < 3; a++) {
          if (a == 2 && u == 6) break;
          const CUtensorMap* m = u < 2 ? &p.wqkv : g3_is_up(u - 2, a) ? &p.wu : &p.wg;
          const int col = (u < 2 ? a * 16 + u * 8 + c : g3_atom(u - 2, a, c)) * 64;
          tma2d(sb + slot * kSlot + a * 8192, m, col, k0, bar);
          tma2d(sb + slot * kSlot + a * 8192 + 24576, m, col, k0 + 64, bar);
        }
      }
      mbar_wait(event + 8, 0);
      fence_async();
#pragma unroll 1
      for (int n = 0, r = 0, i = 0; r < 16; n++) {
        const uint32_t bar = rfull + 8 * (n & 7);
        mbar_wait(bar + 64, ~n >> 3 & 1);
        mbar_expect_tx(bar, r ? 8192 : 40960);
        tma2d(sb + kRows + (n & 7) * 8192, &p.hhst, i * (7 * 64), r * 128, bar);
#pragma unroll 1
        for (int a = r ? 4 : 0; a < 4; a++) tma2d(sb + i * 32768 + a * 8192, &p.wd, (c0 * 2 + a) * 64, i * (7 * 64), bar);
        if (++i == kTail) { i = 0; r++; }
      }
    }
  } else if (warp < 8) {
    uint32_t src[3];
#pragma unroll
    for (int j = 0; j < 3; j++) src[j] = sb + ((warp * 3 + j) >> 3) * 8192 + lane * 128 + ((((warp * 3 + j) & 7) ^ (lane & 7)) << 4);
    const uint32_t ones = 0x3F803F80u;
#pragma unroll 1
    for (int s = 0; s < 112; s++) {
      float a[3][2][4] = {};
#pragma unroll 1
      for (;; s++) {
      const int slot = s & (kSlots - 1);
      mbar_wait(full + 8 * slot, (s / kSlots) & 1);
      uint32_t b[3][4][4];
#pragma unroll
      for (int j = 0; j < 3; j++)
#pragma unroll
        for (int k = 0; k < 4; k++)
          asm volatile("ldmatrix.sync.aligned.m8n8.x4.trans.shared.b16 {%0,%1,%2,%3}, [%4];"
                       : "=r"(b[j][k][0]), "=r"(b[j][k][1]), "=r"(b[j][k][2]), "=r"(b[j][k][3])
                       : "r"(src[j] + slot * kSlot + (k >> 1) * 24576 + (k & 1) * 4096) : "memory");
      __syncwarp();
      if (lane == 0) mbar_arrive(empty + 8 * slot);
#pragma unroll
      for (int k = 0; k < 4; k++)
#pragma unroll
        for (int j = 0; j < 3; j++) {
          mma16816(a[j][0], ones, ones, ones, ones, b[j][k][0], b[j][k][1]);
          mma16816(a[j][1], ones, ones, ones, ones, b[j][k][2], b[j][k][3]);
        }
      if ((s & 7) == 7) break;
      }
      {
        if (lane < 12) {
          const int j = lane >> 2;
          const float x = j == 0 ? a[0][0][0] + a[0][1][0] : j == 1 ? a[1][0][0] + a[1][1][0] : a[2][0][0] + a[2][1][0];
          const float y = j == 0 ? a[0][0][1] + a[0][1][1] : j == 1 ? a[1][0][1] + a[1][1][1] : a[2][0][1] + a[2][1][1];
          const float x1 = bf_rest(x), y1 = bf_rest(y);
          const bool split = s < 32;
          st_b128(sc->cs + ((s >> 4) * 8 + c0 + ((s >> 3) & 1)) * 96 + warp * 12 + lane, split ? bf_upper(x, y) : __float_as_uint(x),
                  split ? bf_upper(x1, y1) : __float_as_uint(y), bf_upper(bf_rest(x1), bf_rest(y1)), ep);
        }
        if (threadIdx.x == 0 && (s & 8)) TSK(s >> 4);
      }
    }
    const int wg = warp >> 2;
#pragma unroll 1
    for (int r = wg; r < 16; r += 2) {
      float acc[128];
      const uint32_t da = desc_lo(sb + kRows, 16);
      uint32_t db = desc_lo(sb, 8192);
      int n = r * kTail;
      if (r) nb_sync(kNbOrder + wg, 256);
      mbar_wait(rfull + 8 * (n & 7), n >> 3 & 1);
      wg_fence();
      wgmma_n256_first(acc, desc(da + (n & 7) * 512), desc(db));
#pragma unroll
      for (int k = 1; k < 4; k++) wgmma_n256(acc, desc(da + (n & 7) * 512) + k * 2, desc(db) + k * 128);
      wg_commit();
#pragma unroll 1
      for (int i = 1; i < kTail; i++) {
        const uint32_t done = rempty + 8 * (n & 7);
        n++;
        db += 2048;
        mbar_wait(rfull + 8 * (n & 7), n >> 3 & 1);
        wg_fence();
#pragma unroll
        for (int k = 0; k < 4; k++) wgmma_n256(acc, desc(da + (n & 7) * 512) + k * 2, desc(db) + k * 128);
        wg_commit();
        wg_wait<1>();
        if (lane < 2) mbar_arrive(done);
      }
      if (r < 15) nb_arrive(kNbOrder + (wg ^ 1), 256);
      wg_wait<0>();
#pragma unroll
      for (int i = 0; i < 128; i++) asm volatile("" : "+f"(acc[i])::"memory");
      if (lane < 2) mbar_arrive(rempty + 8 * (n & 7));
#pragma unroll
      for (int i = 0; i < 16; i++) {
        const float* v = &acc[8 * i];
        __stcg(sc->part + (r * 8 + c0) * 1024 + (warp & 3) * 256 + lane + (i >> 3) * 1024 + (i & 7) * 32,
               make_uint4(pack_bf16(v[0], v[1]), pack_bf16(v[2], v[3]), pack_bf16(v[4], v[5]), pack_bf16(v[6], v[7])));
      }
      __syncwarp();
      if ((r & 2) && lane == 0) mbar_arrive(stored + 8 * (r >> 2));
    }
  } else if (warp == 10) {
    mbar_wait(event, 0);
    flag_wait(sc->flags + kFlHH + (lane & 15) * kFlRow, ep * 8);
    fence_async();
    __syncwarp();
    if (lane == 0) mbar_arrive(event + 8);
  } else if (threadIdx.x == 352) {
#pragma unroll 1
    for (int r = 0; r < 16; r += 4) {
      mbar_wait(stored + 2 * r, 0);
      flag_signal(sc->flags + kFlPart + (c0 >> 1) + r * kFlRow);
    }
    TSK(7);
  }
}

#define PROF_BEGIN
template <bool BY_SM>
__global__ void __cluster_dims__(2, 1, 1) __launch_bounds__(kThreads, 1) fused_block_kernel(Scratch* sc, const __nv_bfloat16* xp, const __nv_bfloat16* wqkvp, __nv_bfloat16* outp,
                                                                   const __grid_constant__ Params p) {
  extern __shared__ __align__(1024) uint8_t smem_raw[];
  if (threadIdx.x < 56) {
    const int l = threadIdx.x & 31, b = blockIdx.x & 127;
    if (threadIdx.x < 32) prefetch_l2(xp + (b * 16 + (l & 15)) * kD + (l >> 4) * 64);
    else prefetch_l2(wqkvp + b * (3 * kD) + (l >> 3) * kD + (l & 7) * 64);
  }
  const uint32_t sb = smem_u32(smem_raw);
  const int bid = role_id<BY_SM>();
  const int r = bid >> 3, c = bid & 7, rank = blockIdx.x & 1;
  auto first_fill = [&](int j) {
    const uint32_t fb = sb + kBars + 8 * j, dst = sb + kRing + j * 40960;
    mbar_expect_tx(fb, 40960);
    tma3d(j >> 1 == c ? sb + kOwn + (j & 1) * 16384 : dst, &p.x, j * 64, (r >> 1) * 128, rank, fb);
#pragma unroll
    for (int a = 0; a < 3; a++) tma2d(dst + 16384 + a * 8192, &p.wqkv, a * kD + c * 64, j * 64, fb);
    mbar_arrive(fb);
  };
  const int tid = threadIdx.x, warp = __shfl_sync(~0u, tid >> 5, 0), wg = warp >> 2;
  if (bid >= 128) {
    if (tid == 0) PROF_BEGIN;
    colsum_cta(p, sc, sb, warp, bid);
    return;
  }
  if (wg == 2) {
    if (warp == 8 && elect_one()) {
#pragma unroll
      for (int j = 0; j < 4; j++) mbar_init(sb + kBars + 8 * j, 2);
      asm volatile("fence.mbarrier_init.release.cluster;" ::: "memory");
      first_fill(0);
      TSS(0);
    }
    __syncwarp();
    if (warp == 8) nb_arrive(kNbOrder, 160);
    asm volatile("setmaxnreg.dec.sync.aligned.u32 40;");
    if (warp == 8) {
      cluster_arrive();
      if (elect_one()) {
#pragma unroll 1
        for (int j = 1; j < 4; j++) first_fill(j);
        TSS(1);
      }
      __syncwarp();
    } else {
      if (elect_one()) {
        uint64_t shifts = warp == 9 ? bar_shifts(4) : warp == 10 ? bar_shifts(22) : bar_shifts(40);
#pragma unroll 1
        for (int i = 0; i < 18; i++, shifts >>= 3) mbar_init(sb + kBars + 8 * (18 * warp - 158 + i), 1u << (shifts & 7));
        sts32(sb + kZero, 0);
        sts32(sb + kRole, bid);
        sts128(sb + kOnes, make_uint4(0x3F803F80u, 0, 0, 0x3F803F80u));
        asm volatile("fence.mbarrier_init.release.cluster;" ::: "memory");
      }
      __syncwarp();
      cluster_arrive();
    }
    cluster_wait();
    const uint32_t ep = ld_epoch(sc);
    if (tid == 320) sts32(sb + kEpoch, ep);
    if (tid == 320) PROF_BEGIN;
    const int pw = warp & 3;
    if (pw == 0) {
      if (elect_one()) {
        const int row = r * 128;
        const uint32_t land = sb + kBars + 8 * kLandBar;
#pragma unroll 1
        for (Ring<0> q(sb, 0); q.j < 32; q.next()) {
          q.acquire();
          const int kb = g1_block(q.j, c);
          if (q.j >= 16 && (q.j < 20 || kb >> 1 == c)) { mbar_arrive(q.bar()); continue; }
          mbar_expect_tx(q.bar(), 16384);
          tma3d(kb >> 1 == c ? sb + kOwn + (kb & 1) * 16384 : q.dst(), &p.x, kb * 64, (r >> 1) * 128, rank, q.bar());
        }
        prefetch_map(&p.o);
        prefetch_map(&p.o16);
        flag_wait(sc->flags + kFlO + r * kFlRow, ep * 8);
        fence_async();
        TS(40);
#pragma unroll 1
        for (Ring<1> q(sb, 0); q.j < 16; q.next()) {
          q.acquire_first();
          if (q.j == 8) {
            prefetch_map(&p.wg);
            prefetch_map(&p.wu);
            prefetch_map(&p.h);
            prefetch_map(&p.h16);
            mbar_wait(sb + kBars + 8 * kSentBar, 0);
            mbar_arrive(q.bar());
            mbar_arrive(sb + kBars + 8 * (kStgBar + 1));
            if (bid == 0) __stcg(sc->flags + kFlPace, ep);
            __nanosleep(kGateONs);
            continue;
          }
          const uint32_t bar = q.j < 8 ? q.bar() : land + 8 * q.bi;
          if (q.j == 9) TS(41);
          mbar_expect_tx(bar, 16384);
          tma2d(q.dst(), &p.o, g2_block(q.j, c) * 64, row, bar);
        }
#pragma unroll 1
        for (Ring<2> q(sb, 0); q.j < 64; q.next()) {
          q.acquire_first();
          if ((0x000F000F003C000Full >> q.j & 1) && q.j != 28 + c) { mbar_arrive(q.bar()); continue; }
          if (q.j == 4) { __nanosleep(kGateHNs); TS(42); }
          const uint32_t bar = q.j < 18 ? land + 8 * q.bi : q.bar();
          mbar_expect_tx(bar, 16384);
          tma2d(q.dst(), &p.h, g3_block(q.j, c) * 64, row, bar);
        }
        prefetch_map(&p.hh);
        prefetch_map(&p.out);
        Ring<3> q(sb, 0);
#pragma unroll 1
        for (; q.j < 16; q.next()) {
          q.acquire_first();
          if (q.j == 0) { mbar_arrive(q.bar()); continue; }
          mbar_expect_tx(q.bar(), 16384);
          tma2d(q.dst(), &p.h, ((q.j + 9) & 15) * 64, row, q.bar());
        }
#pragma unroll 1
        for (int wv = 0; wv < 5; wv++) {
          if (wv == 3 && c < kTail) tma_prefetch2d(&p.hhst, c * (7 * 64), row + 64);
          if (wv == 0 || wv >= 3) {
            mbar_wait(sb + kBars + 8 * (kWaveBar + (wv >> 1)), 0);
            fence_async();
          }
          const int dbl = wv == 2 || wv == 3, f0 = wv == 4 ? 6 : (wv & 1) * 3 + dbl;
#pragma unroll 1
          for (int i = wv ? 0 : kTail; i < 8 << dbl; i++, q.next()) {
            q.acquire();
            mbar_expect_tx(q.bar(), 16384);
            tma2d(q.dst(), &p.hh, ((i >> dbl) * 7 + f0 + (i & dbl)) * 64, row, q.bar());
          }
        }
#pragma unroll 1
        for (int i = 0; i < kTail - 1; i++, q.next()) {
          q.acquire();
          mbar_expect_tx(q.bar(), i < 3 ? 16384 : 8192);
          tma2d(q.dst() + 8192, &p.hhst, i * (7 * 64), row + 64, q.bar());
          if (i == 2) tma2d(q.dst(), &p.hhst, (kTail - 1) * (7 * 64), row + 64, q.bar());
          if (i == rank) tma2d_mc(q.dst(), &p.wd, (c * 2 + rank) * 64, (kTail - 1) * (7 * 64), q.bar());
        }
      }
    } else if (pw == 1) {
      if (elect_one()) {
        const int rp = r >> 1;
#pragma unroll 1
        for (Ring<0> q(sb, 16384); q.j < 32; q.next()) {
          q.acquire();
          mbar_expect_tx(q.bar(), 24576);
          const int col = ((q.j >> 4) * 8 + c) * 64, k0 = g1_block(q.j, c) * 64;
          tma2d_mc(q.dst() + rank * 8192, &p.wqkv, rank * kD + col, k0, q.bar());
          if ((q.j & 1) == rank) tma2d_mc(q.dst() + 16384, &p.wqkv, 2 * kD + col, k0, q.bar());
          if (q.j == max(r, 4))
            for (int a = 0; a < 3; a++) tma_prefetch2d(&p.wqkv, a * kD + (8 + c) * 64, ((r + 12) & 15) * 64);
          if (q.j >> 1 == rp + 8) tma_prefetch2d(&p.wo, (c * 2 + rank) * 64, (q.j & 15) * 64);
        }
        if (r < 6) tma_prefetch2d(rp == 1 ? &p.wu : &p.wg, (c * 7 + 3 + (rp >> 1)) * 64, (c * 2 + rank) * 64);
#pragma unroll 1
        for (Ring<1> q(sb, 16384 + rank * 8192); q.j < 16; q.next()) {
          q.acquire_first();
          mbar_expect_tx(q.bar(), 16384);
          tma2d_mc(q.dst(), &p.wo, (c * 2 + rank) * 64, g2_block(q.j, c) * 64, q.bar());
        }
        const CUtensorMap* mine = rank ? &p.wu : &p.wg;
#pragma unroll 1
        for (Ring<2> q(sb, 16384); q.j < 64; q.next()) {
          const int tile = g3_tile(q.j), f0 = c * 7 + (tile & 1) * 3, fp = f0 + (tile & 2);
          const int k0 = g3_block(q.j, c) * 64;
          q.acquire_first();
          mbar_expect_tx(q.bar(), 24576);
          const uint32_t dst = q.j < 4 ? sb + kRing + (q.j + 1) * 32768 : q.dst();
          tma2d_mc(dst + rank * 8192, mine, fp * 64, k0, q.bar());
          if ((q.j & 1) == rank) tma2d_mc(dst + 16384, tile & 2 ? &p.wu : &p.wg, (f0 + 1) * 64, k0, q.bar());
          const int d = q.j - kPfStep - (c & 1) * 5 - (r >> 2);
          if (d == 0 || d == 11 || d == 22) {
            const int f = c * 7 + (d == 0 ? 2 : d == 11 ? 5 : 6);
            tma_prefetch2d(&p.wg, f * 64, r * 64);
            tma_prefetch2d(&p.wu, f * 64, r * 64);
            if (d != 22) tma_prefetch2d(&p.wu, (f - 1) * 64, r * 64);
            else if (rp < kTail) tma_prefetch2d(&p.wd, (c * 2 + rank) * 64, rp * (7 * 64));
          }
          if (q.j >> 1 == rp + 24) tma_prefetch2d(&p.wd, (c * 2 + rank) * 64, g4_block(q.j & 15) * 64);
        }
        Ring<3> q(sb, 16384 + rank * 8192);
#pragma unroll 1
        for (; q.j < 16; q.next()) {
          q.acquire_first();
          mbar_expect_tx(q.bar(), 16384);
          tma2d_mc(q.dst(), mine, (c * 7 + 6) * 64, ((q.j + 9) & 15) * 64, q.bar());
          if (q.j >> 1 == rp) tma_prefetch2d(&p.wd, (c * 2 + rank) * 64, g4_block(q.j + 16) * 64);
        }
#pragma unroll 1
        for (int wv = 0; wv < 6; wv++) {
          const int dbl = wv == 2 || wv == 3, f0 = wv == 4 ? 6 : wv == 5 ? 0 : (wv & 1) * 3 + dbl;
#pragma unroll 1
          for (int i = wv ? 0 : kTail; i < (wv == 5 ? kTail - 1 : 8 << dbl); i++, q.next()) {
            q.acquire();
            mbar_expect_tx(q.bar(), 16384);
            tma2d_mc(q.dst(), &p.wd, (c * 2 + rank) * 64, ((i >> dbl) * 7 + f0 + (i & dbl)) * 64, q.bar());
            if ((q.j & 15) >> 1 == rp && q.j < 40 + kTail) tma_prefetch2d(&p.wd, (c * 2 + rank) * 64, g4_block(q.j + 16) * 64);
          }
        }
      }
    } else {
      const int cw = pw - 2;
      const uint32_t stg = sb + kStage + cw * 32768, rb = sb + kBars + 8 * kResBar;
      uint32_t land_par = 0;
      if (cw == 0) {
#pragma unroll 1
        for (int i = 0; i < 16; i++) sts128(sb + kFill + i * 512 + (tid & 31) * 16, make_uint4(kPoison, kPoison, kPoison, kPoison));
        __nanosleep(kSampleNs);
        const uint32_t l15 = tid & 15;
        const uint4 os = __ldg(p.wop + ((tid & 31) * 128 + c * 16 + l15));
        const uint4 gs = __ldg((tid & 16 ? p.wup : p.wgp) + (l15 * 451 + c * 56));
        sts32(sb + kScale, __float_as_uint(low_peak(os) * kBias3 * low_peak(gs)));
      }
#pragma unroll 1
      for (int ev = -1; ev < 4; ev++) {
        const bool quads = cw == 0 && ev == 1;
        if (ev >= cw && !quads) nb_sync(kNbPub + cw, 160);
        if (ev >= cw && elect_one()) {
          if (quads) {
            mbar_wait(sb + kBars + 8 * (kHalfBar + 1), 0);
#pragma unroll 1
            for (int i = 0; i < 2; i++) {
              __nanosleep(i ? kPaceNs : kHoldNs);
              tma_store2d(&p.hst, stg + 16384 + i * 8192, c * 128 + 64, r * 128 + i * 64);
              TS(100 + i);
            }
            bulk_commit();
            bulk_wait_read();
            mbar_arrive(sb + kBars + 8 * kStgBar);
          } else {
            const int it = ev - 2 + cw, f0 = c * 7 + (1 - cw) * 3, fp = it == 2 ? c * 7 + 6 : f0 + 2 * it;
            const bool is_o = ev == 0;
            const CUtensorMap* m = is_o ? &p.ost : &p.hhst;
            const int b0 = is_o ? c : f0 + 1, b1 = fp;
#pragma unroll 1
            for (int i = is_o || it == 1 ? 0 : 2; i < (is_o ? 2 : 4); i++) {
              tma_store2d(m, stg + i * 8192, (i < 2 ? b0 : b1) * 64, r * 128 + (i & 1) * 64);
              if (!is_o) {
                bulk_commit();
                bulk_wait_read();
                __nanosleep(kPaceNs);
              }
            }
            bulk_commit();
            bulk_wait_all();
            mbar_arrive(sb + kBars + 8 * (kStgBar + cw));
            flag_signal(sc->flags + kFlHH + ev * 2 - 3 + cw + r * kFlRow);
            TS(44 + cw * 8 + ev);
            if (ev == 2 && cw) {
              mbar_expect_tx(rb, 32768);
#pragma unroll 1
              for (int i = 0; i < 2; i++) tma2d(stg + i * 16384, &p.h, c * 128 + i * 64, r * 128, rb);
            }
          }
        }
        nb_sync(kNbSelf + cw, 32);
        if (ev >= 2 && ev + cw >= 3 && elect_one()) {
          const int wv = cw == 0 ? 3 : ev == 2 ? 0 : 4;
#pragma unroll 1
          for (int i = wv; i <= max(wv, 2); i++) flag_wait(sc->flags + kFlHH + i + r * kFlRow, ep * 8);
          fence_async();
          mbar_arrive(sb + kBars + 8 * (kWaveBar + (wv >> 1)));
          if (wv == 4) {
            flag_wait(sc->flags + kFlPart + (c >> 1) + (r & 12) * kFlRow, ep);
            fence_async();
            mbar_expect_tx(sb + kBars + 8 * kPartBar, 16384);
#pragma unroll 1
            for (int i = 0; i < 2; i++) {
              asm volatile("cp.async.bulk.shared::cluster.global.mbarrier::complete_tx::bytes [%0], [%1], 8192, [%2];"
                           ::"r"(stg + i * 8192), "l"(sc->part + bid * 1024 + i * 512), "r"(sb + kBars + 8 * kPartBar) : "memory");
              __nanosleep(kPartNs);
            }
            TSK(56);
          }
        }
        nb_sync(kNbSelf + cw, 32);
#pragma unroll 1
        for (int sub = 0; ev < 3 && (ev != 0 || cw == 1); sub++) {
          nb_sync(kNbSelf + cw, 32);
          if (ev == 0) check_blocks(p, sc, sb, r, c, sub, land_par);
          const int u = ev < 0 ? cw : 2 * ev + 1 + cw, lane = fresh_tid() & 31;
          if (u == 1 && !sub) {
            uint3 st[4], pre[1];
            load_tagged<4, true>(st, sc->stat1 + r * 128 + lane, 32, ep);
#pragma unroll
            for (int i = 0; i < 4; i++) sts64(sb + kStat + (i * 32 + lane) * 8, st[i].x, st[i].y);
            load_tagged<1, true>(pre, sc->stat1 + 120 + max((r - 2) * 128 + (lane & 7), lane & 7), 0, ep);
            sts64(sb + kStat - 64 + (lane & 7) * 8, pre[0].x, pre[0].y);
            nb_sync(kNbSelf + cw, 32);
            if (lane < 4) mbar_arrive(sb + kBars + 8 * kStatBar);
            if (lane == 0) TS(17);
          }
          if (u == 1) {
            const uint4* gh = sc->halo + ((sub * 16 + r - 2) * 8 + c) * 192 + lane;
            uint4 hv[6] = {};
            nb_sync(kNbHalo, 64);
            uint32_t ns = sub ? kHaloNs : 2 * kBackoffNs;
#pragma unroll 1
            for (int spins = 0; r >= 2; spins++) {
              if (ns) __nanosleep(ns);
              ns = sub ? 0 : kBackoffNs;
              if (spins > 2000000) __trap();
#pragma unroll
              for (int i = 0; i < 6; i++) hv[i] = ld_b128(gh + i * 32);
              uint32_t bad = (hv[5].y ^ ep) | (hv[5].z ^ ep);
#pragma unroll
              for (int i = 0; i < 6; i++) bad |= hv[i].w ^ ep;
              if (!__any_sync(~0u, bad != 0)) break;
            }
            const uint32_t dst = sb + kStage + sub * 32768 + lane * 16;
            sts128(dst, make_uint4(hv[0].x, hv[0].y, hv[0].z, hv[1].x));
            sts128(dst + 512, make_uint4(hv[1].y, hv[1].z, hv[2].x, hv[2].y));
            sts128(dst + 1024, make_uint4(hv[2].z, hv[3].x, hv[3].y, hv[3].z));
            sts128(dst + 1536, make_uint4(hv[4].x, hv[4].y, hv[4].z, hv[5].x));
            nb_arrive(kNbHalo + 1, 64);
            if (lane == 0) TS(123 + sub);
          }
          if (sub) break;
          uint3 v[3];
          load_tagged<3, false>(v, sc->cs + c * 96 + (u * 768 + lane), 32, ep);
          if (u < 2) {
#pragma unroll
            for (int i = 0; i < 3; i++)
#pragma unroll
              for (int k = 0; k < 8; k++)
                sts32(sb + kAug + cw * 4096 + i * 1024 + k * 128 + ((lane * 4) ^ (k * 16)), k == 7 ? 0x3F803F80u : k == 4 || k == 6 ? v[i].z : k & 1 && k != 5 ? v[i].y : v[i].x);
            fence_async_smem();
          } else {
#pragma unroll
            for (int i = 0; i < 3; i++) sts64(sb + kCs + cw * 768 + (i * 32 + lane) * 8, v[i].x, v[i].y);
          }
          nb_sync(kNbSelf + cw, 32);
          if (lane == 0) { mbar_arrive(sb + kBars + 8 * (kAuxBar + cw)); TS(104 + u); }
        }
        nb_sync(kNbSelf + cw, 32);
        if (ev < 0 && cw == 0 && elect_one()) {
#pragma unroll 1
          for (int i = 0; i < 6; i++) {
            __nanosleep(i == 0 ? (c >> 1) * (kFillNs / 4) : kFillNs);
            tma_store2d(i < 2 ? &p.ost : &p.hst, sb + kFill, i < 2 ? (8 + c) * 64 : (c * 2 - 1 + (i >> 1)) * 64, r * 128 + (i & 1) * 64);
            bulk_commit();
          }
          uint32_t peer;
          asm volatile("ld.shared::cluster.b32 %0, [%1];" : "=r"(peer) : "r"(map_cta(sb + kRole, rank ^ 1)) : "memory");
          if (peer != (bid ^ 8)) __trap();
          TS(90);
        }
        nb_sync(kNbSelf + cw, 32);
      }
    }
  } else {
    if (tid == 0) TSS(2);
    cluster_arrive();
    float bias = 0.f;
    if (wg == 1) {
      cluster_wait();
      if (tid == 128) { TSS(5); TSK(69); }
      const int t = tid & 127;
      const __nv_bfloat16* pf = t < 64 ? xp + (size_t)(r * 128 + c * 16 + (t >> 2)) * kD + (t & 3) * 64
                                       : wqkvp + (size_t)(r * 16 + (t - 64) / 3) * (3 * kD) + ((t - 64) % 3) * kD + c * 64;
      const int pf_step = t < 64 ? 256 : 256 * 3 * kD;
      const int lane = tid & 31, lr = c * 16 + (t >> 3);
      const uint32_t src = sb + kRing + lr * 128 + (((t & 7) ^ (lr & 7)) << 4);
      const uint32_t empty = map_cta(sb + kBars + 8 * 4, lane & 1);
      const uint32_t ep = ld_epoch(sc), zero = fresh_tid() >> 10;
      float s0 = 0.f, s1 = 0.f, m0 = 0.f, m1 = 0.f;
#pragma unroll 1
      for (int j = 0; j < 16; j++) {
        mbar_wait(sb + kBars + 8 * (j & 3), (j >> 2) & 1);
        if (j < 2 && t == 0) TS(102 + j);
        const uint4 v = lds128(src + (j >> 1 == c ? kOwn + (j & 1) * 16384 : (j & 3) * 40960));
        __syncwarp();
        mbar_arrive_cluster_if(empty + 8 * (j & 3) + (v.x & zero), lane < 2);
        if ((j == 0 || j == 3 || j == 6) && t < 112) { pf += pf_step; prefetch_l2(pf); }
        const uint32_t u[4] = {v.x, v.y, v.z, v.w};
#pragma unroll
        for (int e = 0; e < 4; e++) {
          const float d0 = bf_lo(u[e]), d1 = bf_hi(u[e]);
          s0 += d0; s1 += d1;
          m0 = fmaf(d0, d0, m0); m1 = fmaf(d1, d1, m1);
        }
      }
      s0 += s1; m0 += m1;
#pragma unroll
      for (int o = 4; o > 0; o >>= 1) { s0 += __shfl_xor_sync(~0u, s0, o); m0 += __shfl_xor_sync(~0u, m0, o); }
      const float mean = s0 * (1.f / kD);
      float rstd;
      asm("rsqrt.approx.ftz.f32 %0, %1;" : "=f"(rstd) : "f"(fmaxf(m0 * (1.f / kD) - mean * mean, 0.f) + 1e-5f));
      if ((lane & 7) == 0)
        st_b128(sc->stat1 + r * 128 + lr, __float_as_uint(rstd), __float_as_uint(-mean), ep, ep);
      mbar_wait(sb + kBars, 0);
      bias = bias_at(low_peak(lds128(sb + kOwn + (warp & 3) * 2048 + (lane & 15) * 128 + (lane & 16) * 512 + (lane & 7) * 16)) * kBias1 *
                     low_peak(lds128(sb + kRing + 16384 + lane * 784)));
      if (tid == 128) TS(16);
    }
    asm volatile("setmaxnreg.inc.sync.aligned.u32 232;");
    if (tid == 0) TSS(4);
    int task;
    asm volatile("mov.u32 %0, 0;" : "=r"(task));

#pragma unroll 1
    for (task = __shfl_sync(~0u, task, 0); task < 5; task++) {
      const bool res_task = wg == 0 && (task == 1 || task == 4);
      if (res_task) {
        float acc[2][96];
        const int t = fresh_tid() & 127;
        const uint32_t frag = sb + kOwn + ((t >> 5) * 16 + (t & 15)) * 128, frag_x = ((t >> 4) & 1) ^ (t & 7);
        TSG(2);
        if (task == 4) mbar_wait(sb + kBars + 8 * kResBar, 0);
#pragma unroll
        for (int i = 0; i < 16; i++) {
          uint32_t v[4];
          ldsm4(frag + (i >> 3) * 16384 + (i & 1) * 8192 + ((frag_x ^ (i & 6)) << 4), v);
#pragma unroll
          for (int e = 0; e < 4; e++) {
            float* d = &acc[i & 1][8 * (i >> 1) + 2 * e];
            asm("shl.b32 %0, %1, 16;" : "=f"(d[0]) : "r"(v[e]));
            asm("and.b32 %0, %1, 0xFFFF0000;" : "=f"(d[1]) : "r"(v[e]));
          }
        }
        __syncwarp();
        if ((t & 31) == 0) mbar_arrive(sb + kBars + 8 * kResFreeBar);
        TSG(4);
        if ((tid & 127) == 0) TS(task == 1 ? 6 : 14);
        if (task == 4) {
          mainloop<128, kTail>(sc, acc, sb, 3, 16, 56, -2, true, false, false, 0, -1, &p.out, c * 128, (r >> 1) * 128, warp, outp);
          if ((tid & 127) == 0) TSK(15);
          if (fresh_tid() == 0) {
            if (bid == 0) __stcg(sc->epoch, lds32(sb + kEpoch));
            TSK(19);
          }
          break;
        }
        mainloop<128, -1>(sc, acc, sb, 1, 0, 15, kPauseG2, false, true, false, 0);
        const int t2 = fresh_tid() & 127;
        const uint32_t frag2 = sb + kStage + ((t2 >> 5) * 16 + (t2 & 15)) * 128, frag2_x = ((t2 >> 4) & 1) ^ (t2 & 7);
        const uint32_t empty = map_cta(sb + kBars + 8 * (ring_base(1) + 5), t2 & 1);
        mbar_wait(sb + kBars + 8 * kStgBar, 0);
        mbar_wait(sb + kBars + 8 * ring_base(1), 1);
#pragma unroll
        for (int m = 0; m < 2; m++) {
          const uint32_t a = desc_lo(sb + kRing, 16);
          wg_fence();
#pragma unroll
          for (int k = 0; k < 4; k++) wgmma_n128(acc[m], desc(a) + (m * 512 + k * 2), desc(a) + (kToB + k * 128));
          wg_commit();
          if (m) nb_arrive(kNbOrder + 1, 256);
          wg_wait<1>();
          if (!m) mbar_arrive_cluster_if(empty + 8 * 4, (t2 & 31) < 2);
        }
#pragma unroll
        for (int b = 0; b < 4; b++) {
          if (b == 1) {
            wg_wait<0>();
            if (t2 == 0) TSK(7);
          }
          if (b < 2) {
#pragma unroll
            for (int i = 0; i < 64; i++) asm volatile("" : "+f"(acc[b][i])::"memory");
          }
          stage_quarter(&acc[b & 1][32 * (b >> 1)], frag2, frag2_x, b);
          if (b & 1) {
            fence_async_smem();
            __syncwarp();
            if (elect_one()) {
              mbar_arrive(sb + kBars + 8 * (kHalfBar + (b >> 1)));
#pragma unroll
              for (int m = 0; m < 2; m++)
                if (b == 1) tma_store2d(&p.h16, sb + kStage + m * 8192 + warp * 2048, c * 128, r * 128 + m * 64 + warp * 16);
            }
            __syncwarp();
          }
        }
        if (t2 == 0) TS(8);
        continue;
      }
      float acc[2][96];
      {
        const uint32_t z = fresh_tid() >> 10;
#pragma unroll
        for (int i = 0; i < 96; i++) {
          asm("{\n.reg .b32 t;\nlop3.b32 t, %1, %2, %3, 0xEA;\nmov.b32 %0, t;\n}\n" : "=f"(acc[0][i]) : "r"(z), "r"(i + 101), "r"(__float_as_uint(bias)));
          asm("{\n.reg .b32 t;\nlop3.b32 t, %1, %2, %3, 0xEA;\nmov.b32 %0, t;\n}\n" : "=f"(acc[1][i]) : "r"(z), "r"(i + 1), "r"(__float_as_uint(bias)));
        }
      }
      if (task == 0) {
      if (tid == 0) TSS(6);
      mainloop<192, -1>(sc, acc, sb, 0, wg * 16, wg ? 16 - kAhead : 16, wg ? kPauseG1 : -2, false, wg == 0, false, wg,
                        wg ? min((c + 2) & 7, 6) : c);
      const int t = fresh_tid() & 127, w = warp & 3, lane = t & 31, g = lane >> 2, q = lane & 3;
      const uint32_t stg = sb + kStage + wg * 32768;
      auto tail = [&](int m, int k0, int k1) {
        wg_fence();
#pragma unroll
        for (int k = k0; k < k1; k++) {
          const uint64_t a = desc(desc_lo(sb + kRing, 16)) + (4 - kAhead + (k >> 2)) * (40960 >> 4);
          wgmma_n192(acc[m], a + (m * 512 + (k & 3) * 2), a + (kToB + (k & 3) * 128));
        }
      };
      auto release = [&](int j, bool cond) { mbar_arrive_cluster_if(map_cta(sb + kBars + 8 * (4 + (j & 3)), lane & 1), cond); };
      if (wg) {
#pragma unroll
        for (int j = 32 - kAhead; j < 32; j++) {
          TST(2 * (j & 1));
          mbar_wait(sb + kBars + 8 * (j & 3), 1);
          TST(2 * (j & 1) + 1);
          tail(1, 4 * (j - 32 + kAhead), 4 * (j - 31 + kAhead));
          wg_commit();
          if (j == 32 - kAhead) {
            wg_wait<1>();
            release(j - 1, lane < 4);
            mbar_wait(sb + kBars + 8 * kResFreeBar, 0);
          }
        }
      } else {
        nb_arrive(kNbOrder + 1, 256);
        wg_wait<0>();
        release(15, lane < 2);
        if (t == 0) TSK(1);
      }
      TST(4);
      mbar_wait(sb + kBars + 8 * (kAuxBar + wg), 0);
      mbar_wait(sb + kBars + 8 * kStatBar, 0);
      {
        uint32_t am[4];
#pragma unroll
        for (int i = 0; i < 4; i++) {
          const float m1 = __uint_as_float(lds32(sb + kStat + (w * 16 + g) * 8 + 4 + (i >> 1) * 512 + (i & 1) * 64));
          const float m2 = bf_rest(m1), lo = q & 1 ? m2 : m1;
          am[i] = bf_upper(lo, q == 3 ? -bias : q == 2 ? bf_rest(m2) : lo);
        }
        const uint64_t db = (uint64_t)desc_lo(sb + kAug + wg * 4096, 1024) | (0x40000000ull << 32);
        TST(5);
        wg_fence();
        wgmma_n192_rs(acc[1], am[2], am[3], 0u, db);
        wg_commit();
        TST(6);
        if (wg) {
          wg_fence();
          wgmma_n192_rs(acc[0], am[0], am[1], 0u, db);
          tail(0, 0, 4 * kAhead);
          wg_commit();
        } else {
          wg_fence();
          wgmma_n192_rs(acc[0], am[0], am[1], 0u, db);
          wg_commit();
          asm volatile("" ::: "memory");
        }
        TST(7);
        wg_wait<1>();
        TST(8);
#pragma unroll
        for (int i = 0; i < 96; i++) asm volatile("" : "+f"(acc[1][i])::"memory");
      }
      const uint32_t ep = lds32(sb + kEpoch);
      uint32_t pk[2][48];
      auto fold = [&](int pp, int jn, int hf) {
        const uint32_t v = pack_bf16(acc[pp][4 * jn + 2 * hf], acc[pp][4 * jn + 2 * hf + 1]);
        pk[pp][2 * jn + hf] = jn >= 16 ? movm(v) : v;
      };
      if (t == 96) TS(115 + wg);
#pragma unroll
      for (int jn = 8; jn < 24; jn++) fold(1, jn, 1);
      if (w < 3) {
#pragma unroll
        for (int i = 0; i < 4; i++)
          sts128(stg + (w + 5) * 2048 + i * 512 + lane * 16, make_uint4(pk[1][17 + 8 * i], pk[1][19 + 8 * i], pk[1][21 + 8 * i], pk[1][23 + 8 * i]));
      } else if (r < 14) {
        uint4* gh = sc->halo + ((wg * 16 + r) * 8 + c) * 192 + lane;
#pragma unroll
        for (int i = 0; i < 6; i++) st_b128(gh + i * 32, pk[1][17 + 6 * i], i < 5 ? pk[1][(19 + 6 * i) % 48] : ep, i < 5 ? pk[1][(21 + 6 * i) % 48] : ep, ep);
        if (wg == 0) {
#pragma unroll 1
          for (int i = 0; i < 6; i++, gh += 32) st_b128(gh + 128 * 192, 0, 0, 0, ep - 1);
        }
      }
      if (w == 3) nb_arrive(kNbHalo, 64);
      if (wg) nb_arrive(kNbOrder, 256);
      TST(9);
      if (t == 96) TS(111 + wg);
#pragma unroll
      for (int jn = 23; jn >= 0; jn--) {
        fold(1, jn, 0);
        if (jn < 8) fold(1, jn, 1);
      }
      const bool sel0 = 2 * q > g, sel1 = 2 * q + 1 > g, no_prev = (r < 2 && w == 0);
      const uint4 ones = lds128(sb + kOnes);
      const uint32_t lowmask = (sel0 ? 0x0000FFFFu : 0u) | (sel1 ? 0xFFFF0000u : 0u) | ones.y;
      float rs[4][2], rk[4][2];
#pragma unroll
      for (int i = 0; i < 4; i++) {
        const uint32_t a = sb + kStat + w * 128 + (i >> 1) * 512 + (i & 1) * 64;
        const float rq = __uint_as_float(lds32(a + g * 8)) * (0.17677669529663687f * 1.4426950408889634f);
        rk[i][0] = __uint_as_float(lds32(a + q * 16 - (sel0 ? 64 : 0)));
        rk[i][1] = __uint_as_float(lds32(a + q * 16 + 8 - (sel1 ? 64 : 0)));
        rs[i][0] = rk[i][0] * rq;
        rs[i][1] = rk[i][1] * rq;
      }
      {
        uint32_t all = ~0u;
#pragma unroll
        for (int i = 0; i < 48; i++) if (i < 16 || !(i & 1)) all &= pk[1][i];
        if (all == kPoison) sts32(sb + kZero + 8, 0);
      }
      TST(10);
      wg_wait<0>();
      TST(11);
#pragma unroll
      for (int j = 32 - kAhead; j < 32; j++) release(j, lane < 4 * wg && (w != 0 || j < 31));
#pragma unroll
      for (int i = 0; i < 96; i++) asm volatile("" : "+f"(acc[0][i])::"memory");
      if (t == 0 && wg) TSK(21);
#pragma unroll
      for (int jn = 8; jn < 24; jn++) fold(0, jn, 1);
#pragma unroll
      for (int i = 0; i < 4; i++)
        sts128(stg + (w + 1) * 2048 + i * 512 + lane * 16, make_uint4(pk[0][17 + 8 * i], pk[0][19 + 8 * i], pk[0][21 + 8 * i], pk[0][23 + 8 * i]));
#pragma unroll
      for (int jn = 23; jn >= 0; jn--) {
        fold(0, jn, 0);
        if (jn < 8) fold(0, jn, 1);
      }
      if (t == 0) TS(113 + wg);
      nb_sync(kNbWg + wg, 128);
      uint32_t hal[2][16];
      auto load_halo = [&](int m) {
#pragma unroll
        for (int i = 0; i < 4; i++) {
          const uint4 v = lds128(stg + w * 2048 + m * 8192 + i * 512 + lane * 16);
          uint32_t* h = &hal[m][i * 4];
          h[0] = v.x; h[1] = v.y; h[2] = v.z; h[3] = v.w;
        }
      };
      load_halo(1);
      if (w == 0) {
        nb_sync(kNbHalo + 1, 64);
        release(31, lane < 4 * wg);
      }
      load_halo(0);
      __syncwarp();
      if (t == 0) TS(2 + wg * 20);
      {
        uint32_t all = lowmask;
#pragma unroll
        for (int i = 0; i < 32; i++) if (i < 16 || !(i & 1)) all &= pk[0][i];
#pragma unroll
        for (int i = 0; i < 8; i++) all &= __float_as_uint(rs[i >> 1][i & 1]);
        if (all == kPoison) sts32(sb + kZero + 8, 0);
      }
      nb_sync(kNbWin, 256);
      if (t == 0) TS(9 + wg * 20);
      const uint32_t zero = lds32(sb + kZero);
      float s0[4][4], s1[4][4], s2[4][4];
#pragma unroll
      for (int k = 0; k < 4; k++) {
        pk[k >> 1][8 * (k & 1)] |= zero;
#pragma unroll
        for (int e = 0; e < 4; e++) s0[k][e] = s1[k][e] = s2[k][e] = 0.f;
      }
#pragma unroll
      for (int ks = 0; ks < 2; ks++)
#pragma unroll
        for (int k = 0; k < 4; k++) {
          const uint32_t* qf = &pk[k >> 1][8 * (k & 1) + 4 * ks];
          const uint32_t* kf = &pk[k >> 1][16 + 8 * (k & 1) + 4 * ks];
          const uint32_t* hf = &hal[k >> 1][4 * (k & 1) + 2 * ks];
          mma16816(s0[k], qf[0], qf[1], qf[2], qf[3], hf[0], hf[1]);
          mma16816(s1[k], qf[0], qf[1], qf[2], qf[3], kf[0], kf[2]);
          mma16816(s2[k], qf[0], qf[1], qf[2], qf[3], kf[1], kf[3]);
        }
      float ea[4][2], eb[4][2], ma[4], mb[4];
#pragma unroll
      for (int k = 0; k < 4; k++) {
        const float *ra = rs[k & 2], *rb = rs[(k & 2) + 1];
        if (no_prev && k < 2) s0[k][0] = s0[k][1] = -INFINITY;
        ea[k][0] = (sel0 ? s0[k][0] : s1[k][0]) * ra[0]; ea[k][1] = (sel1 ? s0[k][1] : s1[k][1]) * ra[1];
        eb[k][0] = (sel0 ? s1[k][2] : s2[k][2]) * rb[0]; eb[k][1] = (sel1 ? s1[k][3] : s2[k][3]) * rb[1];
        ma[k] = fmaxf(ea[k][0], ea[k][1]); mb[k] = fmaxf(eb[k][0], eb[k][1]);
      }
#pragma unroll
      for (int o = 1; o < 4; o <<= 1)
#pragma unroll
        for (int k = 0; k < 4; k++) {
          ma[k] = fmaxf(ma[k], __shfl_xor_sync(~0u, ma[k], o));
          mb[k] = fmaxf(mb[k], __shfl_xor_sync(~0u, mb[k], o));
        }
      float ov[4][4][4], ls[4][4];
      uint32_t all = 0;
#pragma unroll
      for (int k = 0; k < 4; k++) {
        const float *ra = rk[k & 2], *rb = rk[(k & 2) + 1];
        ea[k][0] = ex2(ea[k][0] - ma[k]); ea[k][1] = ex2(ea[k][1] - ma[k]);
        eb[k][0] = ex2(eb[k][0] - mb[k]); eb[k][1] = ex2(eb[k][1] - mb[k]);
        const uint32_t pa = pack_bf16(ea[k][0] * ra[0], ea[k][1] * ra[1]), pb = pack_bf16(eb[k][0] * rb[0], eb[k][1] * rb[1]);
        const uint32_t* vf = &pk[k >> 1][32 + 8 * (k & 1)];
        const uint32_t* hf = &hal[k >> 1][8 + 4 * (k & 1)];
#pragma unroll
        for (int d2 = 0; d2 < 2; d2++) {
#pragma unroll
          for (int e = 0; e < 4; e++) ov[k][d2][e] = ov[k][2 + d2][e] = 0.f;
          mma1688(ov[k][d2], hf[2 * d2], hf[2 * d2 + 1], pa & lowmask);
          mma1688(ov[k][2 + d2], vf[4 * d2], vf[4 * d2 + 2], pb & lowmask);
        }
#pragma unroll
        for (int d2 = 0; d2 < 2; d2++) {
          mma1688(ov[k][d2], vf[4 * d2], vf[4 * d2 + 2], pa & ~lowmask);
          mma1688(ov[k][2 + d2], vf[4 * d2 + 1], vf[4 * d2 + 3], pb & ~lowmask);
        }
        ls[k][0] = ls[k][1] = ls[k][2] = ls[k][3] = 0.f;
        mma16816(ls[k], ones.x, ones.y, ones.z, ones.w, pack_bf16(ea[k][0], ea[k][1]), pack_bf16(eb[k][0], eb[k][1]));
        if (k >= kDone) all |= pa & pb;
      }
#pragma unroll
      for (int k = 0; k < 4; k++) {
        if (k == kDone) {
          if (all == 0xFFFFFFFFu) sts32(sb + kZero + 8, 0);
          nb_arrive(kNbWin + 1, 256);
          all = 0;
        }
        all |= (__float_as_uint(ov[k][0][0]) & __float_as_uint(ov[k][1][0]) & __float_as_uint(ov[k][2][0])) &
               (__float_as_uint(ov[k][3][0]) & __float_as_uint(ls[k][0]));
      }
      const uint32_t nil = lds32(sb + kZero);
      const uint32_t frag = stg + (w * 16 + (lane & 15)) * 128, frag_x = (lane >> 4) ^ (lane & 7);
      uint32_t after = all;
#pragma unroll
      for (int k = 0; k < 4; k++) {
        uint32_t h[2][4];
#pragma unroll
        for (int hf = 0; hf < 2; hf++) {
          const float i0 = rcp(__uint_as_float(__float_as_uint(ls[k][2 * hf]) | (after & nil)));
          const float i1 = rcp(__uint_as_float(__float_as_uint(ls[k][2 * hf + 1]) | (after & nil)));
#pragma unroll
          for (int e = 0; e < 4; e++) h[e >> 1][2 * (e & 1) + hf] = pack_bf16(ov[k][2 * hf + (e >> 1)][2 * (e & 1)] * i0, ov[k][2 * hf + (e >> 1)][2 * (e & 1) + 1] * i1);
          after = h[0][hf];
        }
#pragma unroll
        for (int d2 = 0; d2 < 2; d2++) stsm4_t(frag + (k >> 1) * 8192 + ((frag_x ^ ((k & 1) * 4 + d2 * 2)) << 4), h[d2][0], h[d2][1], h[d2][2], h[d2][3]);
      }
      fence_async_smem();
      if (wg) {
        __syncwarp();
        if (elect_one()) {
          tma_store2d(&p.o16, stg + w * 2048, (8 + c) * 64, r * 128 + w * 16);
          tma_store2d(&p.o16, stg + 8192 + w * 2048, (8 + c) * 64, r * 128 + 64 + w * 16);
          bulk_commit();
          bulk_wait_read();
          mbar_arrive(sb + kBars + 8 * kSentBar);
        }
        __syncwarp();
      } else {
        nb_arrive(kNbPub, 160);
      }
      if (t == 0) TS(3 + wg * 20);
      __syncwarp();
      bias = bias_at(low_peak(lds128(stg + w * 2048 + (lane & 15) * 128 + (lane & 16) * 512 + (lane & 7) * 16)) * __uint_as_float(lds32(sb + kScale)));
      task += wg;
      continue;
      }

      {
#pragma unroll 1
        for (int part = task != 2; part < 2; part++) {
          if ((tid & 127) == 0) TS(6 + 2 * task + wg * 20);
          if (task + part == 5) {
            mainloop<128, 0>(sc, acc, sb, 3, 0, 16, -2, false, true, false, 1);
            continue;
          }
          const int j0 = task == 3 ? 48 - wg * 16 : part == 0 ? 2 - 2 * wg : 18 - 14 * wg;
          mainloop<192, 0>(sc, acc, sb, 2, j0, task != 2 ? 16 : part == 0 ? 2 : 14, -2, false, true, part == 0, wg);
          if (part == 0 && wg == 0) {
            const int t = fresh_tid() & 127;
            const uint32_t ep = lds32(sb + kEpoch);
            {
              float s = 0.f, ss = 0.f;
#pragma unroll 1
              for (int i = 0; i < 16; i++) {
                const uint4 v = lds128(sb + kStage + t * 128 + (i >> 3) * 16384 + (((i ^ t) & 7) << 4));
                const uint32_t u[4] = {v.x, v.y, v.z, v.w};
#pragma unroll
                for (int e = 0; e < 4; e++) {
                  const float d0 = bf_lo(u[e]), d1 = bf_hi(u[e]);
                  s = (s + d0) + d1;
                  ss = fmaf(d1, d1, fmaf(d0, d0, ss));
                }
              }
              st_b128(sc->stat2 + c * kS + r * 128 + t, __float_as_uint(s), __float_as_uint(ss), ep, ep);
            }
            __nanosleep(kStatNs);
            float2 sum = make_float2(0.f, 0.f);
#pragma unroll 1
            for (int i = 0; i < 2; i++) {
              uint3 a[4];
              load_tagged<4, true>(a, sc->stat2 + i * 4 * kS + r * 128 + t, kS, ep);
              sum.x += (__uint_as_float(a[0].x) + __uint_as_float(a[1].x)) + (__uint_as_float(a[2].x) + __uint_as_float(a[3].x));
              sum.y += (__uint_as_float(a[0].y) + __uint_as_float(a[1].y)) + (__uint_as_float(a[2].y) + __uint_as_float(a[3].y));
            }
            const float mean = sum.x * (1.f / kD);
            sts64f(sb + kStat + t * 8, make_float2(fmaxf(sum.y * (1.f / kD) - mean * mean, 0.f) + 1e-5f, -mean));
            __syncwarp();
            if (elect_one()) {
              bulk_commit();
              bulk_wait_read();
              mbar_arrive(sb + kBars + 8 * kStatBar);
            }
            __syncwarp();
            if (t == 0) TS(37);
          }
        }
      }
      const int t = fresh_tid() & 127, w = warp & 3, lane = t & 31, g = lane >> 2, q = lane & 3;
      const uint32_t stg = sb + kStage + wg * 32768;
      uint32_t csv = sb + kCs + wg * 768 + q * 8;
      uint32_t statv = sb + kStat + (w * 16 + g) * 8;
      const uint32_t frag = stg + (w * 16 + (lane & 15)) * 128;
      const uint32_t frag_x = (lane >> 4) ^ (lane & 7);
      const uint32_t priv = stg + w * 2048 + lane * 16;
      if (t == 0) TSK(7 + 2 * task + wg * 20);

      if (task == 4) {
        mbar_wait(sb + kBars + 8 * (kAuxBar + 1), 1);
        mbar_wait(sb + kBars + 8 * kResFreeBar, 1);
        mbar_wait(sb + kBars + 8 * (kStgBar + 1), 0);
      }
      asm volatile("" : "+r"(csv), "+r"(statv)::"memory");

      {
#pragma unroll
        for (int i = 0; i < 96; i++) asm volatile("sub.f32 %0, %0, %1;" : "+f"(acc[0][i]) : "f"(bias));
#define NEXT(i) asm volatile("sub.f32 %0, %1, %2;" : "=f"(acc[0][i]) : "f"(acc[1][i]), "f"(bias))
#pragma unroll 1
        for (int pp = 0; pp < 2; pp++) {
          TSG(pp);
          RowConst rc[2];
#pragma unroll
          for (int hf = 0; hf < 2; hf++) {
            const float2 st = lds64f_const(statv + pp * 512 + hf * 64);
            float rstd;
            asm("rsqrt.approx.ftz.f32 %0, %1;" : "=f"(rstd) : "f"(st.x));
            rc[hf] = {st.y, 0.7978845608f * rstd, 0.0356774081f * rstd * rstd * rstd, 0.5f * rstd * rstd};
          }
#pragma unroll
          for (int j2 = 0; j2 < 4; j2++) {
            uint32_t hv[4];
#pragma unroll
            for (int jj = 0; jj < 2; jj++) {
              const int jn = 2 * j2 + jj;
              const float2 cg = lds64f_const(csv + jn * 32), cu = lds64f_const(csv + 256 + jn * 32);
#pragma unroll
              for (int hf = 0; hf < 2; hf++) {
                const float nm = rc[hf].nmean;
                const float g0 = fmaf(nm, cg.x, acc[0][4 * jn + 2 * hf]), g1 = fmaf(nm, cg.y, acc[0][4 * jn + 2 * hf + 1]);
                const float u0 = fmaf(nm, cu.x, acc[0][32 + 4 * jn + 2 * hf]), u1 = fmaf(nm, cu.y, acc[0][33 + 4 * jn + 2 * hf]);
                hv[2 * jj + hf] = pack_bf16(g0 * u0 * gate_scale(g0, rc[hf]), g1 * u1 * gate_scale(g1, rc[hf]));
              }
            }
            stsm4(frag + 16384 + pp * 8192 + ((frag_x ^ (j2 * 2)) << 4), hv[0], hv[1], hv[2], hv[3]);
          }
          if (task < 4) {
            if (task == 2) {
#pragma unroll
              for (int j2 = 0; j2 < 4; j2++) {
                uint32_t hv[4];
#pragma unroll
                for (int jj = 0; jj < 2; jj++) {
                  const int jn = 16 + 2 * j2 + jj;
                  const float2 cs = lds64f_const(csv + jn * 32);
#pragma unroll
                  for (int hf = 0; hf < 2; hf++) {
                    const float nm = rc[hf].nmean;
                    const float t0 = fmaf(nm, cs.x, acc[0][4 * jn + 2 * hf]), t1 = fmaf(nm, cs.y, acc[0][4 * jn + 2 * hf + 1]);
                    hv[2 * jj + hf] = pack_bf16(t0 * gate_scale(t0, rc[hf]), t1 * gate_scale(t1, rc[hf]));
                  }
                }
                sts128(priv + pp * 8192 + j2 * 512, make_uint4(hv[0], hv[1], hv[2], hv[3]));
              }
            } else {
              uint4 park[4];
#pragma unroll
              for (int j2 = 0; j2 < 4; j2++) park[j2] = lds128(priv + pp * 8192 + j2 * 512);
              __syncwarp();
#pragma unroll
              for (int j2 = 0; j2 < 4; j2++) {
                const uint32_t pv[4] = {park[j2].x, park[j2].y, park[j2].z, park[j2].w};
                uint32_t hv[4];
#pragma unroll
                for (int jj = 0; jj < 2; jj++) {
                  const int jn = 16 + 2 * j2 + jj;
                  const float2 cs = lds64f_const(csv + jn * 32);
#pragma unroll
                  for (int hf = 0; hf < 2; hf++) {
                    const float nm = rc[hf].nmean;
                    const float t0 = fmaf(nm, cs.x, acc[0][4 * jn + 2 * hf]), t1 = fmaf(nm, cs.y, acc[0][4 * jn + 2 * hf + 1]);
                    asm("mul.rn.bf16x2 %0, %1, %2;" : "=r"(hv[2 * jj + hf]) : "r"(pack_bf16(t0, t1)), "r"(pv[2 * jj + hf]));
                  }
                }
                stsm4(frag + pp * 8192 + ((frag_x ^ (j2 * 2)) << 4), hv[0], hv[1], hv[2], hv[3]);
              }
            }
            if (pp == 1) break;
#pragma unroll
            for (int i = 64; i < 96; i++) NEXT(i);
          }
          if (pp == 1) break;
#pragma unroll
          for (int i = 0; i < 64; i++) NEXT(i);
        }
      }
      fence_async_smem();
      nb_arrive(kNbPub + wg, 160);
      if (t == 0) TS(task == 4 ? 57 : 56 + task + wg * 2);
    }
  }
}

typedef CUresult (*EncodeTiledFn)(CUtensorMap*, CUtensorMapDataType, cuuint32_t, void*, const cuuint64_t*, const cuuint64_t*,
                                  const cuuint32_t*, const cuuint32_t*, CUtensorMapInterleave, CUtensorMapSwizzle,
                                  CUtensorMapL2promotion, CUtensorMapFloatOOBfill);

void encode(EncodeTiledFn fn, CUtensorMap* m, const void* base, int rank, cuuint64_t d0, cuuint64_t d1, cuuint64_t d2,
            cuuint64_t s1, cuuint64_t s2, cuuint32_t b2, cuuint32_t b1 = 64) {
  const cuuint64_t dims[3] = {d0, d1, d2}, strides[2] = {s1, s2};
  const cuuint32_t box[3] = {64, b1, b2}, es[3] = {1, 1, 1};
  fn(m, CU_TENSOR_MAP_DATA_TYPE_BFLOAT16, rank, const_cast<void*>(base), dims, strides, box, es, CU_TENSOR_MAP_INTERLEAVE_NONE,
     CU_TENSOR_MAP_SWIZZLE_128B, CU_TENSOR_MAP_L2_PROMOTION_L2_128B, CU_TENSOR_MAP_FLOAT_OOB_FILL_NONE);
}

}

extern "C" void kernel_launch(void* const* d_in, const int* in_sizes, int n_in, void* d_out, int out_size) {
  void* fnp = nullptr;
  cudaDriverEntryPointQueryResult qr;
  cudaGetDriverEntryPoint("cuTensorMapEncodeTiled", &fnp, cudaEnableDefault, &qr);
  EncodeTiledFn fn = (EncodeTiledFn)fnp;
  void *o, *h, *hh;
  cudaGetSymbolAddress(&o, g_o);
  cudaGetSymbolAddress(&h, g_h);
  cudaGetSymbolAddress(&hh, g_hh);

  Params p;
  Scratch* sc;
  cudaGetSymbolAddress((void**)&sc, g_scratch);
  encode(fn, &p.x, d_in[0], 3, kD, kS / 2, 2, 4 * kD, 2 * kD, 1, 128);
  encode(fn, &p.out, d_out, 3, kD, kS / 2, 2, 4 * kD, 2 * kD, 1, 16);
  encode(fn, &p.wqkv, d_in[1], 2, 3 * kD, kD, 1, 6 * kD, 0, 1);
  encode(fn, &p.wo, d_in[2], 2, kD, kD, 1, 2 * kD, 0, 1);
  encode(fn, &p.wd, d_in[6], 2, kD, kF, 1, 2 * kD, 0, 1);
  encode(fn, &p.wg, d_in[4], 2, kF, kD, 1, 2 * kF, 0, 1);
  encode(fn, &p.wu, d_in[5], 2, kF, kD, 1, 2 * kF, 0, 1);
  encode(fn, &p.o, o, 2, kD, kS, 1, 2 * kD, 0, 1, 128);
  encode(fn, &p.h, h, 2, kD, kS, 1, 2 * kD, 0, 1, 128);
  encode(fn, &p.hh, hh, 2, kF, kS, 1, 2 * kF, 0, 1, 128);
  encode(fn, &p.ost, o, 2, kD, kS, 1, 2 * kD, 0, 1);
  encode(fn, &p.o16, o, 2, kD, kS, 1, 2 * kD, 0, 1, 16);
  encode(fn, &p.h16, h, 2, kD, kS, 1, 2 * kD, 0, 1, 16);
  encode(fn, &p.hst, h, 2, kD, kS, 1, 2 * kD, 0, 1);
  encode(fn, &p.hhst, hh, 2, kF, kS, 1, 2 * kF, 0, 1);
  p.wop = (const uint4*)d_in[2];
  p.wgp = (const uint4*)d_in[4];
  p.wup = (const uint4*)d_in[5];

  int dev = 0, sms = 0;
  cudaGetDevice(&dev);
  cudaDeviceGetAttribute(&sms, cudaDevAttrMultiProcessorCount, dev);
  auto* kernel = sms == 132 ? fused_block_kernel<true> : fused_block_kernel<false>;
  cudaFuncSetAttribute(kernel, cudaFuncAttributeMaxDynamicSharedMemorySize, kSmemBytes);
  kernel<<<132, kThreads, kSmemBytes, cudaStreamPerThread>>>(sc, (const __nv_bfloat16*)d_in[0], (const __nv_bfloat16*)d_in[1],
                                                                  (__nv_bfloat16*)d_out, p);
}
```

```cpp
#include <cuda_runtime.h>
#include <cuda_bf16.h>
#include <cuda.h>
#include <stdint.h>

namespace {

constexpr int kS = 2048, kD = 1024, kF = 3584;
constexpr int kThreads = 384;

constexpr int kRing = 0;
constexpr int kStage = 163840;
constexpr int kAug = kStage + 16384;
constexpr int kOwn = kStage + 32768;
constexpr int kFill = kStage + 24576;
constexpr int kCs = kStage + 65536;
constexpr int kStat = kCs + 1536;
constexpr int kBars = kStat + 1024;
constexpr int kSmemBytes = kBars + 512;
constexpr int kResBar = 36;
constexpr int kAuxBar = 37;
constexpr int kStgBar = 39;
constexpr int kResFreeBar = 41;
constexpr int kStatBar = 42;
constexpr int kPartBar = 43;
constexpr int kWaveBar = 45;
constexpr int kHalfBar = 49;
constexpr int kSentBar = 51;
constexpr int kLandBar = 52;
constexpr int kNumBars = 58;
static_assert(kNumBars == 4 + 3 * 18, "barrier initialisation is split 4 + 3 x 18");
__host__ __device__ constexpr int bar_count(int i) {
  const int ph = i < 8 ? 0 : i < 18 ? 1 : i < 26 ? 2 : 3, base = ph * 9 - (ph & 1);
  return i < 36 ? (i - base < 4 + (ph & 1) ? 2 : ph == 0 ? 16 : 8) : i == kResFreeBar || i == kStatBar || (i >= kHalfBar && i < kLandBar) ? 4 : 1;
}
__host__ __device__ constexpr uint64_t bar_shifts(int first) {
  uint64_t m = 0;
  for (int i = 17; i >= 0; i--) {
    const int n = bar_count(first + i);
    m = m << 3 | (n == 16 ? 4 : n == 8 ? 3 : n >> 1);
  }
  return m;
}
constexpr int kScale = kBars + 464;
constexpr int kOnes = kBars + 480;
constexpr int kZero = kBars + 496;
constexpr int kRole = kBars + 508;
constexpr int kEpoch = kBars + 500;
__device__ __forceinline__ int ring_base(int ph) { return ph * 9 - (ph & 1); }
constexpr int kNbOrder = 1;
constexpr int kNbWg = 3;
constexpr int kNbPub = 5;
constexpr int kNbWin = 7;
constexpr int kNbSelf = 13;
constexpr int kNbHalo = 9;

constexpr int kFlO = 0;
constexpr int kFlPace = 1;
constexpr int kFlHH = 3;
constexpr int kFlPart = 8;
constexpr int kFlRow = 32;
constexpr int kNumFlags = 16 * kFlRow;

constexpr int kPauseG1 = 7;
constexpr int kPauseG2 = 1;
constexpr int kAhead = 2;
constexpr int kTail = 5;
constexpr int kDone = 3;
constexpr int kQuietAt = 48;
constexpr int kPfStep = 8;
constexpr int kBackoffNs = 200;
constexpr int kPaceNs = 300;
constexpr int kPartNs = 150;
constexpr int kFillNs = 500;
constexpr int kHaloNs = 150;
constexpr int kGateONs = 150;
constexpr int kGateHNs = 150;
constexpr int kHoldNs = 1200;
constexpr float kBias1 = 512.f, kBias3 = 32768.f;
constexpr int kInitMix = 1000;
constexpr int kSplit = 13;
constexpr int kSampleNs = 3000;
constexpr int kStatNs = 1500;

struct Scratch {
  uint32_t flags[kNumFlags];
  uint32_t epoch[32];
  uint4 stat1[kS];
  uint4 stat2[8 * kS];
  uint4 cs[7 * 8 * 96];
  uint4 halo[2 * 16 * 8 * 6 * 32];
  uint4 part[128 * 8 * 128];
};
struct Params {
  CUtensorMap x, wqkv, o, wo, h, wg, wu, hh, wd, out;
  CUtensorMap ost, hst, hhst;
  CUtensorMap o16, h16;
  const uint4 *wop, *wgp, *wup;
};

__device__ __align__(256) __nv_bfloat16 g_o[kS * kD];
__device__ __align__(256) __nv_bfloat16 g_h[kS * kD];
__device__ __align__(256) __nv_bfloat16 g_hh[kS * kF];
__device__ __align__(256) Scratch g_scratch;

template <bool BY_SM>
__device__ __forceinline__ int role_id() {
  uint32_t sm;
  asm("mov.u32 %0, %%smid;" : "=r"(sm));
  const int tpc = (BY_SM ? sm : blockIdx.x) >> 1, rank = blockIdx.x & 1;
  if ((tpc | 1) == 61) return 8 + 2 * tpc + rank;
  const int u = tpc - 32, s7 = (u * 37) >> 8;
  const int g = tpc < 32 ? tpc & 7 : tpc < 60 ? 1 + u - 7 * s7 : 0, s = tpc < 32 ? tpc >> 3 : tpc < 60 ? 4 + s7 : tpc - 58;
  return (g * 2 + rank) * 8 + s;
}
#define TS(i) do { } while (0)
#define TSK(i) do { } while (0)
#define TSS(i) do { } while (0)
#define TST(i)
#define TSG(i)

__device__ __forceinline__ uint32_t smem_u32(const void* p) { return (uint32_t)__cvta_generic_to_shared(p); }
__device__ __forceinline__ void mbar_init(uint32_t bar, uint32_t cnt) {
  asm volatile("mbarrier.init.shared::cta.b64 [%0], %1;" ::"r"(bar), "r"(cnt));
}
__device__ __forceinline__ void mbar_expect_tx(uint32_t bar, uint32_t bytes) {
  asm volatile("mbarrier.arrive.expect_tx.shared::cta.b64 _, [%0], %1;" ::"r"(bar), "r"(bytes) : "memory");
}
__device__ __forceinline__ uint32_t map_cta(uint32_t addr, uint32_t cta) {
  uint32_t r;
  asm("mapa.shared::cluster.u32 %0, %1, %2;" : "=r"(r) : "r"(addr), "r"(cta));
  return r;
}
__device__ __forceinline__ void mbar_arrive_cluster_if(uint32_t bar, bool cond) {
  asm volatile("{\n.reg .pred p;\nsetp.ne.u32 p, %1, 0;\n@p mbarrier.arrive.shared::cluster.b64 _, [%0];\n}\n"
               ::"r"(bar), "r"((uint32_t)cond) : "memory");
}
__device__ __forceinline__ void mbar_wait(uint32_t bar, uint32_t parity) {
  asm volatile("{\n.reg .pred p;\nLAB_WAIT:\nmbarrier.try_wait.parity.shared::cta.b64 p, [%0], %1;\n@!p bra LAB_WAIT;\n}\n"
               ::"r"(bar), "r"(parity) : "memory");
  return;
  asm volatile("{\n.reg .pred p;\n.reg .u32 c;\nmov.u32 c, 0;\n"
               "LAB_WAIT:\nmbarrier.try_wait.parity.shared::cta.b64 p, [%0], %1;\n@p bra LAB_DONE;\n"
               "add.u32 c, c, 1;\nsetp.lt.u32 p, c, 2000000;\n@p bra LAB_WAIT;\ntrap;\nLAB_DONE:\n}\n"
               ::"r"(bar), "r"(parity) : "memory");
}
__device__ __forceinline__ void mbar_arrive(uint32_t bar) {
  asm volatile("mbarrier.arrive.shared::cta.b64 _, [%0];" ::"r"(bar) : "memory");
}
__device__ __forceinline__ void flag_signal(uint32_t* flag) {
  asm volatile("red.release.gpu.global.add.u32 [%0], 1;" ::"l"(flag) : "memory");
}
__device__ __forceinline__ void st_b128(uint4* p, uint32_t a, uint32_t b, uint32_t c, uint32_t d) {
  asm volatile("{\n.reg .b128 t;\n.reg .b64 lo, hi;\nmov.b64 lo, {%1,%2};\nmov.b64 hi, {%3,%4};\nmov.b128 t, {lo, hi};\n"
               "st.relaxed.gpu.global.b128 [%0], t;\n}\n" ::"l"(p), "r"(a), "r"(b), "r"(c), "r"(d) : "memory");
}
__device__ __forceinline__ uint4 ld_b128(const uint4* p) {
  uint4 v;
  asm volatile("{\n.reg .b128 t;\n.reg .b64 lo, hi;\nld.relaxed.gpu.global.b128 t, [%4];\nmov.b128 {lo, hi}, t;\n"
               "mov.b64 {%0,%1}, lo;\nmov.b64 {%2,%3}, hi;\n}\n" : "=r"(v.x), "=r"(v.y), "=r"(v.z), "=r"(v.w) : "l"(p) : "memory");
  return v;
}
__device__ __forceinline__ uint32_t ld_epoch(Scratch* sc) {
  uint32_t v;
  asm volatile("ld.relaxed.gpu.global.u32 %0, [%1];" : "=r"(v) : "l"(sc->epoch) : "memory");
  return v + 1;
}
__device__ __forceinline__ void flag_wait(uint32_t* flag, uint32_t target) {
  asm volatile("{\n.reg .pred p;\n.reg .u32 c, v;\nmov.u32 c, 0;\n"
               "LAB_WAIT:\nld.relaxed.gpu.global.u32 v, [%0];\nsub.u32 v, v, %1;\nsetp.ge.s32 p, v, 0;\n@p bra LAB_DONE;\n"
               "add.u32 c, c, 1;\nsetp.lt.u32 p, c, 4000000;\n@p bra LAB_WAIT;\ntrap;\nLAB_DONE:\n}\n"
               ::"l"(flag), "r"(target) : "memory");
}
__device__ __forceinline__ int fresh_tid() {
  int v;
  asm volatile("mov.u32 %0, %%tid.x;" : "=r"(v));
  return v;
}
constexpr uint32_t kPoison = 0xFFFFFFFFu;
__device__ __forceinline__ bool elect_one() {
  uint32_t p;
  asm volatile("{\n.reg .pred P;\nelect.sync _|P, 0xffffffff;\nselp.u32 %0, 1, 0, P;\n}\n" : "=r"(p));
  return p != 0;
}
__device__ __forceinline__ void fence_async() { asm volatile("fence.acquire.gpu;\nfence.proxy.async.global;" ::: "memory"); }
__device__ __forceinline__ void fence_async_smem() { asm volatile("fence.proxy.async.shared::cta;" ::: "memory"); }
__device__ __forceinline__ void nb_sync(int id, int n) { asm volatile("bar.sync %0, %1;" ::"r"(id), "r"(n) : "memory"); }
__device__ __forceinline__ void nb_arrive(int id, int n) { asm volatile("bar.arrive %0, %1;" ::"r"(id), "r"(n) : "memory"); }

__device__ __forceinline__ void tma2d(uint32_t dst, const CUtensorMap* m, int c0, int c1, uint32_t bar) {
  asm volatile("cp.async.bulk.tensor.2d.shared::cluster.global.mbarrier::complete_tx::bytes [%0], [%1, {%3, %4}], [%2];"
               ::"r"(dst), "l"(m), "r"(bar), "r"(c0), "r"(c1) : "memory");
}
__device__ __forceinline__ void tma2d_mc(uint32_t dst, const CUtensorMap* m, int c0, int c1, uint32_t bar) {
  asm volatile("cp.async.bulk.tensor.2d.shared::cluster.global.mbarrier::complete_tx::bytes.multicast::cluster"
               " [%0], [%1, {%3, %4}], [%2], %5;"
               ::"r"(dst), "l"(m), "r"(bar), "r"(c0), "r"(c1), "h"((uint16_t)3) : "memory");
}
__device__ __forceinline__ void tma3d(uint32_t dst, const CUtensorMap* m, int c0, int c1, int c2, uint32_t bar) {
  asm volatile("cp.async.bulk.tensor.3d.shared::cluster.global.mbarrier::complete_tx::bytes [%0], [%1, {%3, %4, %5}], [%2];"
               ::"r"(dst), "l"(m), "r"(bar), "r"(c0), "r"(c1), "r"(c2) : "memory");
}
__device__ __forceinline__ void tma_store2d(const CUtensorMap* m, uint32_t src, int c0, int c1) {
  asm volatile("cp.async.bulk.tensor.2d.global.shared::cta.bulk_group [%0, {%2, %3}], [%1];"
               ::"l"(m), "r"(src), "r"(c0), "r"(c1) : "memory");
}
__device__ __forceinline__ void tma_store3d(const CUtensorMap* m, uint32_t src, int c0, int c1, int c2) {
  asm volatile("cp.async.bulk.tensor.3d.global.shared::cta.bulk_group [%0, {%2, %3, %4}], [%1];"
               ::"l"(m), "r"(src), "r"(c0), "r"(c1), "r"(c2) : "memory");
}
__device__ __forceinline__ void tma_prefetch2d(const CUtensorMap* m, int c0, int c1) {
  asm volatile("cp.async.bulk.prefetch.tensor.2d.L2.global [%0, {%1, %2}];" ::"l"(m), "r"(c0), "r"(c1) : "memory");
}
__device__ __forceinline__ void prefetch_map(const CUtensorMap* m) { asm volatile("prefetch.tensormap [%0];" ::"l"(m) : "memory"); }
__device__ __forceinline__ void bulk_commit() { asm volatile("cp.async.bulk.commit_group;" ::: "memory"); }
__device__ __forceinline__ void bulk_wait_all() { asm volatile("cp.async.bulk.wait_group 0;" ::: "memory"); }
__device__ __forceinline__ void bulk_wait_read() { asm volatile("cp.async.bulk.wait_group.read 0;" ::: "memory"); }
__device__ __forceinline__ void prefetch_l2(const void* p) { asm volatile("prefetch.global.L2 [%0];" ::"l"(p)); }
__device__ __forceinline__ void cluster_arrive() { asm volatile("barrier.cluster.arrive.relaxed.aligned;" ::: "memory"); }
__device__ __forceinline__ void cluster_wait() { asm volatile("barrier.cluster.wait.aligned;" ::: "memory"); }

__device__ __forceinline__ void wg_fence() { asm volatile("wgmma.fence.sync.aligned;" ::: "memory"); }
__device__ __forceinline__ void wg_commit() { asm volatile("wgmma.commit_group.sync.aligned;" ::: "memory"); }
template <int N> __device__ __forceinline__ void wg_wait() { asm volatile("wgmma.wait_group.sync.aligned %0;" ::"n"(N) : "memory"); }
__device__ __forceinline__ uint32_t desc_lo(uint32_t addr, uint32_t lbo) { return ((addr & 0x3FFFF) >> 4) | ((lbo >> 4) << 16); }
__device__ __forceinline__ uint64_t desc(uint32_t lo) { return (uint64_t)lo | (0x40000040ull << 32); }
__device__ __forceinline__ uint64_t desc_kept(uint32_t lo, uint32_t sb) { return (uint64_t)lo | (uint64_t)(0x40000040u | sb >> 31) << 32; }
constexpr int kToB = (16384 >> 4) + ((8192 - 16) >> 4 << 16);

__device__ __forceinline__ void wgmma_n128(float (&d)[96], uint64_t da, uint64_t db) {
  asm volatile(
      "wgmma.mma_async.sync.aligned.m64n128k16.f32.bf16.bf16 {"
      "%0, %1, %2, %3, %4, %5, %6, %7, %8, %9, %10, %11, %12, %13, %14, %15, "
      "%16, %17, %18, %19, %20, %21, %22, %23, %24, %25, %26, %27, %28, %29, %30, %31, "
      "%32, %33, %34, %35, %36, %37, %38, %39, %40, %41, %42, %43, %44, %45, %46, %47, "
      "%48, %49, %50, %51, %52, %53, %54, %55, %56, %57, %58, %59, %60, %61, %62, %63}, "
      "%64, %65, 1, 1, 1, 0, 1;\n"
      :
        "+f"(d[0]), "+f"(d[1]), "+f"(d[2]), "+f"(d[3]), "+f"(d[4]), "+f"(d[5]), "+f"(d[6]), "+f"(d[7]),
        "+f"(d[8]), "+f"(d[9]), "+f"(d[10]), "+f"(d[11]), "+f"(d[12]), "+f"(d[13]), "+f"(d[14]), "+f"(d[15]),
        "+f"(d[16]), "+f"(d[17]), "+f"(d[18]), "+f"(d[19]), "+f"(d[20]), "+f"(d[21]), "+f"(d[22]), "+f"(d[23]),
        "+f"(d[24]), "+f"(d[25]), "+f"(d[26]), "+f"(d[27]), "+f"(d[28]), "+f"(d[29]), "+f"(d[30]), "+f"(d[31]),
        "+f"(d[32]), "+f"(d[33]), "+f"(d[34]), "+f"(d[35]), "+f"(d[36]), "+f"(d[37]), "+f"(d[38]), "+f"(d[39]),
        "+f"(d[40]), "+f"(d[41]), "+f"(d[42]), "+f"(d[43]), "+f"(d[44]), "+f"(d[45]), "+f"(d[46]), "+f"(d[47]),
        "+f"(d[48]), "+f"(d[49]), "+f"(d[50]), "+f"(d[51]), "+f"(d[52]), "+f"(d[53]), "+f"(d[54]), "+f"(d[55]),
        "+f"(d[56]), "+f"(d[57]), "+f"(d[58]), "+f"(d[59]), "+f"(d[60]), "+f"(d[61]), "+f"(d[62]), "+f"(d[63])
      : "l"(da), "l"(db));
}

__device__ __forceinline__ void wgmma_n256(float (&d)[128], uint64_t da, uint64_t db, int add) {
  asm volatile(
      "{\n.reg .pred p;\nsetp.ne.b32 p, %130, 0;\n"
      "wgmma.mma_async.sync.aligned.m64n256k16.f32.bf16.bf16 {"
      "%0, %1, %2, %3, %4, %5, %6, %7, %8, %9, %10, %11, %12, %13, %14, %15, "
      "%16, %17, %18, %19, %20, %21, %22, %23, %24, %25, %26, %27, %28, %29, %30, %31, "
      "%32, %33, %34, %35, %36, %37, %38, %39, %40, %41, %42, %43, %44, %45, %46, %47, "
      "%48, %49, %50, %51, %52, %53, %54, %55, %56, %57, %58, %59, %60, %61, %62, %63, "
      "%64, %65, %66, %67, %68, %69, %70, %71, %72, %73, %74, %75, %76, %77, %78, %79, "
      "%80, %81, %82, %83, %84, %85, %86, %87, %88, %89, %90, %91, %92, %93, %94, %95, "
      "%96, %97, %98, %99, %100, %101, %102, %103, %104, %105, %106, %107, %108, %109, %110, %111, "
      "%112, %113, %114, %115, %116, %117, %118, %119, %120, %121, %122, %123, %124, %125, %126, %127}, "
      "%128, %129, p, 1, 1, 0, 1;\n}\n"
      :
        "+f"(d[0]), "+f"(d[1]), "+f"(d[2]), "+f"(d[3]), "+f"(d[4]), "+f"(d[5]), "+f"(d[6]), "+f"(d[7]),
        "+f"(d[8]), "+f"(d[9]), "+f"(d[10]), "+f"(d[11]), "+f"(d[12]), "+f"(d[13]), "+f"(d[14]), "+f"(d[15]),
        "+f"(d[16]), "+f"(d[17]), "+f"(d[18]), "+f"(d[19]), "+f"(d[20]), "+f"(d[21]), "+f"(d[22]), "+f"(d[23]),
        "+f"(d[24]), "+f"(d[25]), "+f"(d[26]), "+f"(d[27]), "+f"(d[28]), "+f"(d[29]), "+f"(d[30]), "+f"(d[31]),
        "+f"(d[32]), "+f"(d[33]), "+f"(d[34]), "+f"(d[35]), "+f"(d[36]), "+f"(d[37]), "+f"(d[38]), "+f"(d[39]),
        "+f"(d[40]), "+f"(d[41]), "+f"(d[42]), "+f"(d[43]), "+f"(d[44]), "+f"(d[45]), "+f"(d[46]), "+f"(d[47]),
        "+f"(d[48]), "+f"(d[49]), "+f"(d[50]), "+f"(d[51]), "+f"(d[52]), "+f"(d[53]), "+f"(d[54]), "+f"(d[55]),
        "+f"(d[56]), "+f"(d[57]), "+f"(d[58]), "+f"(d[59]), "+f"(d[60]), "+f"(d[61]), "+f"(d[62]), "+f"(d[63]),
        "+f"(d[64]), "+f"(d[65]), "+f"(d[66]), "+f"(d[67]), "+f"(d[68]), "+f"(d[69]), "+f"(d[70]), "+f"(d[71]),
        "+f"(d[72]), "+f"(d[73]), "+f"(d[74]), "+f"(d[75]), "+f"(d[76]), "+f"(d[77]), "+f"(d[78]), "+f"(d[79]),
        "+f"(d[80]), "+f"(d[81]), "+f"(d[82]), "+f"(d[83]), "+f"(d[84]), "+f"(d[85]), "+f"(d[86]), "+f"(d[87]),
        "+f"(d[88]), "+f"(d[89]), "+f"(d[90]), "+f"(d[91]), "+f"(d[92]), "+f"(d[93]), "+f"(d[94]), "+f"(d[95]),
        "+f"(d[96]), "+f"(d[97]), "+f"(d[98]), "+f"(d[99]), "+f"(d[100]), "+f"(d[101]), "+f"(d[102]), "+f"(d[103]),
        "+f"(d[104]), "+f"(d[105]), "+f"(d[106]), "+f"(d[107]), "+f"(d[108]), "+f"(d[109]), "+f"(d[110]), "+f"(d[111]),
        "+f"(d[112]), "+f"(d[113]), "+f"(d[114]), "+f"(d[115]), "+f"(d[116]), "+f"(d[117]), "+f"(d[118]), "+f"(d[119]),
        "+f"(d[120]), "+f"(d[121]), "+f"(d[122]), "+f"(d[123]), "+f"(d[124]), "+f"(d[125]), "+f"(d[126]), "+f"(d[127])
      : "l"(da), "l"(db), "r"(add));
}

__device__ __forceinline__ void wgmma_n192(float (&d)[96], uint64_t da, uint64_t db, int add = 1) {
  asm volatile(
      "{\n.reg .pred p;\nsetp.ne.b32 p, %98, 0;\n"
      "wgmma.mma_async.sync.aligned.m64n192k16.f32.bf16.bf16 {"
      "%0, %1, %2, %3, %4, %5, %6, %7, %8, %9, %10, %11, %12, %13, %14, %15, "
      "%16, %17, %18, %19, %20, %21, %22, %23, %24, %25, %26, %27, %28, %29, %30, %31, "
      "%32, %33, %34, %35, %36, %37, %38, %39, %40, %41, %42, %43, %44, %45, %46, %47, "
      "%48, %49, %50, %51, %52, %53, %54, %55, %56, %57, %58, %59, %60, %61, %62, %63, "
      "%64, %65, %66, %67, %68, %69, %70, %71, %72, %73, %74, %75, %76, %77, %78, %79, "
      "%80, %81, %82, %83, %84, %85, %86, %87, %88, %89, %90, %91, %92, %93, %94, %95}, "
      "%96, %97, p, 1, 1, 0, 1;\n}\n"
      :
        "+f"(d[0]), "+f"(d[1]), "+f"(d[2]), "+f"(d[3]), "+f"(d[4]), "+f"(d[5]), "+f"(d[6]), "+f"(d[7]),
        "+f"(d[8]), "+f"(d[9]), "+f"(d[10]), "+f"(d[11]), "+f"(d[12]), "+f"(d[13]), "+f"(d[14]), "+f"(d[15]),
        "+f"(d[16]), "+f"(d[17]), "+f"(d[18]), "+f"(d[19]), "+f"(d[20]), "+f"(d[21]), "+f"(d[22]), "+f"(d[23]),
        "+f"(d[24]), "+f"(d[25]), "+f"(d[26]), "+f"(d[27]), "+f"(d[28]), "+f"(d[29]), "+f"(d[30]), "+f"(d[31]),
        "+f"(d[32]), "+f"(d[33]), "+f"(d[34]), "+f"(d[35]), "+f"(d[36]), "+f"(d[37]), "+f"(d[38]), "+f"(d[39]),
        "+f"(d[40]), "+f"(d[41]), "+f"(d[42]), "+f"(d[43]), "+f"(d[44]), "+f"(d[45]), "+f"(d[46]), "+f"(d[47]),
        "+f"(d[48]), "+f"(d[49]), "+f"(d[50]), "+f"(d[51]), "+f"(d[52]), "+f"(d[53]), "+f"(d[54]), "+f"(d[55]),
        "+f"(d[56]), "+f"(d[57]), "+f"(d[58]), "+f"(d[59]), "+f"(d[60]), "+f"(d[61]), "+f"(d[62]), "+f"(d[63]),
        "+f"(d[64]), "+f"(d[65]), "+f"(d[66]), "+f"(d[67]), "+f"(d[68]), "+f"(d[69]), "+f"(d[70]), "+f"(d[71]),
        "+f"(d[72]), "+f"(d[73]), "+f"(d[74]), "+f"(d[75]), "+f"(d[76]), "+f"(d[77]), "+f"(d[78]), "+f"(d[79]),
        "+f"(d[80]), "+f"(d[81]), "+f"(d[82]), "+f"(d[83]), "+f"(d[84]), "+f"(d[85]), "+f"(d[86]), "+f"(d[87]),
        "+f"(d[88]), "+f"(d[89]), "+f"(d[90]), "+f"(d[91]), "+f"(d[92]), "+f"(d[93]), "+f"(d[94]), "+f"(d[95])
      : "l"(da), "l"(db), "r"(add));
}

__device__ __forceinline__ void wgmma_n192_any(float (&d)[96], uint64_t da, uint64_t db) {
  asm volatile(
      "wgmma.mma_async.sync.aligned.m64n192k16.f32.bf16.bf16 {"
      "%0, %1, %2, %3, %4, %5, %6, %7, %8, %9, %10, %11, %12, %13, %14, %15, "
      "%16, %17, %18, %19, %20, %21, %22, %23, %24, %25, %26, %27, %28, %29, %30, %31, "
      "%32, %33, %34, %35, %36, %37, %38, %39, %40, %41, %42, %43, %44, %45, %46, %47, "
      "%48, %49, %50, %51, %52, %53, %54, %55, %56, %57, %58, %59, %60, %61, %62, %63, "
      "%64, %65, %66, %67, %68, %69, %70, %71, %72, %73, %74, %75, %76, %77, %78, %79, "
      "%80, %81, %82, %83, %84, %85, %86, %87, %88, %89, %90, %91, %92, %93, %94, %95}, "
      "%96, %97, 0, 1, 1, 0, 1;\n"
      :
        "=f"(d[0]), "=f"(d[1]), "=f"(d[2]), "=f"(d[3]), "=f"(d[4]), "=f"(d[5]), "=f"(d[6]), "=f"(d[7]),
        "=f"(d[8]), "=f"(d[9]), "=f"(d[10]), "=f"(d[11]), "=f"(d[12]), "=f"(d[13]), "=f"(d[14]), "=f"(d[15]),
        "=f"(d[16]), "=f"(d[17]), "=f"(d[18]), "=f"(d[19]), "=f"(d[20]), "=f"(d[21]), "=f"(d[22]), "=f"(d[23]),
        "=f"(d[24]), "=f"(d[25]), "=f"(d[26]), "=f"(d[27]), "=f"(d[28]), "=f"(d[29]), "=f"(d[30]), "=f"(d[31]),
        "=f"(d[32]), "=f"(d[33]), "=f"(d[34]), "=f"(d[35]), "=f"(d[36]), "=f"(d[37]), "=f"(d[38]), "=f"(d[39]),
        "=f"(d[40]), "=f"(d[41]), "=f"(d[42]), "=f"(d[43]), "=f"(d[44]), "=f"(d[45]), "=f"(d[46]), "=f"(d[47]),
        "=f"(d[48]), "=f"(d[49]), "=f"(d[50]), "=f"(d[51]), "=f"(d[52]), "=f"(d[53]), "=f"(d[54]), "=f"(d[55]),
        "=f"(d[56]), "=f"(d[57]), "=f"(d[58]), "=f"(d[59]), "=f"(d[60]), "=f"(d[61]), "=f"(d[62]), "=f"(d[63]),
        "=f"(d[64]), "=f"(d[65]), "=f"(d[66]), "=f"(d[67]), "=f"(d[68]), "=f"(d[69]), "=f"(d[70]), "=f"(d[71]),
        "=f"(d[72]), "=f"(d[73]), "=f"(d[74]), "=f"(d[75]), "=f"(d[76]), "=f"(d[77]), "=f"(d[78]), "=f"(d[79]),
        "=f"(d[80]), "=f"(d[81]), "=f"(d[82]), "=f"(d[83]), "=f"(d[84]), "=f"(d[85]), "=f"(d[86]), "=f"(d[87]),
        "=f"(d[88]), "=f"(d[89]), "=f"(d[90]), "=f"(d[91]), "=f"(d[92]), "=f"(d[93]), "=f"(d[94]), "=f"(d[95])
      : "l"(da), "l"(db));
}

__device__ __forceinline__ void wgmma_n192_rs(float (&d)[96], uint32_t a0, uint32_t a1, uint32_t a23, uint64_t db) {
  asm volatile(
      "wgmma.mma_async.sync.aligned.m64n192k16.f32.bf16.bf16 {"
      "%0, %1, %2, %3, %4, %5, %6, %7, %8, %9, %10, %11, %12, %13, %14, %15, "
      "%16, %17, %18, %19, %20, %21, %22, %23, %24, %25, %26, %27, %28, %29, %30, %31, "
      "%32, %33, %34, %35, %36, %37, %38, %39, %40, %41, %42, %43, %44, %45, %46, %47, "
      "%48, %49, %50, %51, %52, %53, %54, %55, %56, %57, %58, %59, %60, %61, %62, %63, "
      "%64, %65, %66, %67, %68, %69, %70, %71, %72, %73, %74, %75, %76, %77, %78, %79, "
      "%80, %81, %82, %83, %84, %85, %86, %87, %88, %89, %90, %91, %92, %93, %94, %95}, "
      "{%96, %97, %98, %98}, %99, 1, 1, 1, 1;\n"
      :
        "+f"(d[0]), "+f"(d[1]), "+f"(d[2]), "+f"(d[3]), "+f"(d[4]), "+f"(d[5]), "+f"(d[6]), "+f"(d[7]),
        "+f"(d[8]), "+f"(d[9]), "+f"(d[10]), "+f"(d[11]), "+f"(d[12]), "+f"(d[13]), "+f"(d[14]), "+f"(d[15]),
        "+f"(d[16]), "+f"(d[17]), "+f"(d[18]), "+f"(d[19]), "+f"(d[20]), "+f"(d[21]), "+f"(d[22]), "+f"(d[23]),
        "+f"(d[24]), "+f"(d[25]), "+f"(d[26]), "+f"(d[27]), "+f"(d[28]), "+f"(d[29]), "+f"(d[30]), "+f"(d[31]),
        "+f"(d[32]), "+f"(d[33]), "+f"(d[34]), "+f"(d[35]), "+f"(d[36]), "+f"(d[37]), "+f"(d[38]), "+f"(d[39]),
        "+f"(d[40]), "+f"(d[41]), "+f"(d[42]), "+f"(d[43]), "+f"(d[44]), "+f"(d[45]), "+f"(d[46]), "+f"(d[47]),
        "+f"(d[48]), "+f"(d[49]), "+f"(d[50]), "+f"(d[51]), "+f"(d[52]), "+f"(d[53]), "+f"(d[54]), "+f"(d[55]),
        "+f"(d[56]), "+f"(d[57]), "+f"(d[58]), "+f"(d[59]), "+f"(d[60]), "+f"(d[61]), "+f"(d[62]), "+f"(d[63]),
        "+f"(d[64]), "+f"(d[65]), "+f"(d[66]), "+f"(d[67]), "+f"(d[68]), "+f"(d[69]), "+f"(d[70]), "+f"(d[71]),
        "+f"(d[72]), "+f"(d[73]), "+f"(d[74]), "+f"(d[75]), "+f"(d[76]), "+f"(d[77]), "+f"(d[78]), "+f"(d[79]),
        "+f"(d[80]), "+f"(d[81]), "+f"(d[82]), "+f"(d[83]), "+f"(d[84]), "+f"(d[85]), "+f"(d[86]), "+f"(d[87]),
        "+f"(d[88]), "+f"(d[89]), "+f"(d[90]), "+f"(d[91]), "+f"(d[92]), "+f"(d[93]), "+f"(d[94]), "+f"(d[95])
      : "r"(a0), "r"(a1), "r"(a23), "l"(db));
}

__device__ __forceinline__ uint32_t pack_bf16(float lo, float hi) {
  uint32_t r;
  asm("cvt.rn.bf16x2.f32 %0, %1, %2;" : "=r"(r) : "f"(hi), "f"(lo));
  return r;
}
__device__ __forceinline__ float bf_lo(uint32_t v) { return __uint_as_float(v << 16); }
__device__ __forceinline__ float bf_hi(uint32_t v) { return __uint_as_float(v & 0xFFFF0000u); }
__device__ __forceinline__ float ex2(float x) { float r; asm("ex2.approx.ftz.f32 %0, %1;" : "=f"(r) : "f"(x)); return r; }
__device__ __forceinline__ float rcp(float x) { float r; asm("rcp.approx.ftz.f32 %0, %1;" : "=f"(r) : "f"(x)); return r; }
__device__ __forceinline__ uint32_t movm(uint32_t a) {
  uint32_t d;
  asm volatile("movmatrix.sync.aligned.m8n8.trans.b16 %0, %1;" : "=r"(d) : "r"(a));
  return d;
}
__device__ __forceinline__ void mma16816(float (&c)[4], uint32_t a0, uint32_t a1, uint32_t a2, uint32_t a3, uint32_t b0, uint32_t b1) {
  asm volatile("mma.sync.aligned.m16n8k16.row.col.f32.bf16.bf16.f32 {%0,%1,%2,%3}, {%4,%5,%6,%7}, {%8,%9}, {%0,%1,%2,%3};"
               : "+f"(c[0]), "+f"(c[1]), "+f"(c[2]), "+f"(c[3]) : "r"(a0), "r"(a1), "r"(a2), "r"(a3), "r"(b0), "r"(b1));
}
__device__ __forceinline__ void mma1688(float (&c)[4], uint32_t a0, uint32_t a1, uint32_t b0) {
  asm volatile("mma.sync.aligned.m16n8k8.row.col.f32.bf16.bf16.f32 {%0,%1,%2,%3}, {%4,%5}, {%6}, {%0,%1,%2,%3};"
               : "+f"(c[0]), "+f"(c[1]), "+f"(c[2]), "+f"(c[3]) : "r"(a0), "r"(a1), "r"(b0));
}
__device__ __forceinline__ void stsm4(uint32_t addr, uint32_t a, uint32_t b, uint32_t c, uint32_t d) {
  asm volatile("stmatrix.sync.aligned.m8n8.x4.shared.b16 [%0], {%1,%2,%3,%4};" ::"r"(addr), "r"(a), "r"(b), "r"(c), "r"(d) : "memory");
}
__device__ __forceinline__ void stsm4_t(uint32_t addr, uint32_t a, uint32_t b, uint32_t c, uint32_t d) {
  asm volatile("stmatrix.sync.aligned.m8n8.x4.trans.shared.b16 [%0], {%1,%2,%3,%4};" ::"r"(addr), "r"(a), "r"(b), "r"(c), "r"(d) : "memory");
}
__device__ __forceinline__ void ldsm4(uint32_t addr, uint32_t (&v)[4]) {
  asm volatile("ldmatrix.sync.aligned.m8n8.x4.shared.b16 {%0,%1,%2,%3}, [%4];"
               : "=r"(v[0]), "=r"(v[1]), "=r"(v[2]), "=r"(v[3]) : "r"(addr) : "memory");
}
__device__ __forceinline__ void sts128(uint32_t addr, uint4 v) {
  asm volatile("st.shared.v4.b32 [%0], {%1,%2,%3,%4};" ::"r"(addr), "r"(v.x), "r"(v.y), "r"(v.z), "r"(v.w) : "memory");
}
__device__ __forceinline__ uint4 lds128(uint32_t addr) {
  uint4 v;
  asm volatile("ld.shared.v4.b32 {%0,%1,%2,%3}, [%4];" : "=r"(v.x), "=r"(v.y), "=r"(v.z), "=r"(v.w) : "r"(addr) : "memory");
  return v;
}
__device__ __forceinline__ void sts64(uint32_t addr, uint32_t a, uint32_t b) {
  asm volatile("st.shared.v2.b32 [%0], {%1,%2};" ::"r"(addr), "r"(a), "r"(b) : "memory");
}
__device__ __forceinline__ void sts32(uint32_t addr, uint32_t a) { asm volatile("st.shared.b32 [%0], %1;" ::"r"(addr), "r"(a) : "memory"); }
__device__ __forceinline__ uint32_t lds32(uint32_t addr) {
  uint32_t v;
  asm volatile("ld.shared.b32 %0, [%1];" : "=r"(v) : "r"(addr) : "memory");
  return v;
}
__device__ __forceinline__ float2 lds64f_const(uint32_t addr) {
  float2 v;
  asm("ld.shared.v2.f32 {%0,%1}, [%2];" : "=f"(v.x), "=f"(v.y) : "r"(addr));
  return v;
}
template <int N, bool PAIR>
__device__ __forceinline__ void load_tagged(uint3 (&out)[N], const uint4* src, int stride, uint32_t tag, int last = 0) {
  uint32_t bad;
  int spins = 0;
  do {
    if (spins != 0) __nanosleep(kBackoffNs);
    if (++spins > 2000000) __trap();
    bad = 0;
#pragma unroll
    for (int i = 0; i < N; i++) {
      const uint4 v = ld_b128(src + i * stride + (i == N - 1 ? last : 0));
      out[i] = make_uint3(v.x, v.y, v.z);
      bad |= (v.w ^ tag) | (PAIR ? v.z ^ tag : 0);
    }
  } while (bad != 0);
}
__device__ __forceinline__ void sts64f(uint32_t addr, float2 v) { sts64(addr, __float_as_uint(v.x), __float_as_uint(v.y)); }
__device__ __forceinline__ float bf_rest(float v) { return v - __uint_as_float(__float_as_uint(v) & 0xFFFF0000u); }
__device__ __forceinline__ uint32_t bf_upper(float lo, float hi) { return __byte_perm(__float_as_uint(lo), __float_as_uint(hi), 0x7632); }
__device__ __forceinline__ float low_peak(uint4 v) {
  asm("max.xorsign.abs.bf16x2 %0, %0, %1;" : "+r"(v.x) : "r"(v.y));
  asm("max.xorsign.abs.bf16x2 %0, %0, %1;" : "+r"(v.z) : "r"(v.w));
  asm("max.xorsign.abs.bf16x2 %0, %0, %1;" : "+r"(v.x) : "r"(v.z));
  asm("max.xorsign.abs.bf16x2 %0, %0, %1;" : "+r"(v.x) : "r"(v.x << 16));
  return __uint_as_float(__reduce_min_sync(~0u, v.x & 0x7FFF0000u));
}
__device__ __forceinline__ float bias_at(float v) { return __uint_as_float((__float_as_uint(fminf(v, 1e37f)) & 0x7F800000u) | 0x00400000u); }
struct RowConst {
  float nmean, k0, k1, half;
};
__device__ __forceinline__ float gate_scale(float t, const RowConst& k) {
  float th;
  asm("tanh.approx.f32 %0, %1;" : "=f"(th) : "f"(t * fmaf(t * t, k.k1, k.k0)));
  return fmaf(th, k.half, k.half);
}

template <int N>
__device__ __forceinline__ void mma_k16(float (&acc)[2][96], uint32_t a, uint32_t b, int kk, int add = 1) {
#pragma unroll
  for (int m = 0; m < 2; m++) {
    const uint64_t da = desc(a) + (m * 512 + kk * 2), db = desc(b) + kk * 128;
    if (N == 128) wgmma_n128(acc[m], da, db); else wgmma_n192(acc[m], da, db, add);
  }
}

__device__ __forceinline__ void stage_quarter(const float* acc, uint32_t frag, uint32_t frag_x, int b, const uint4* add = nullptr) {
#pragma unroll
  for (int j = 0; j < 4; j++) {
    const float* v = acc + 8 * j;
    uint32_t h[4] = {pack_bf16(v[0], v[1]), pack_bf16(v[2], v[3]), pack_bf16(v[4], v[5]), pack_bf16(v[6], v[7])};
    if (add) {
      const uint32_t a[4] = {add[j].x, add[j].y, add[j].z, add[j].w};
#pragma unroll
      for (int e = 0; e < 4; e++) asm("add.rn.bf16x2 %0, %0, %1;" : "+r"(h[e]) : "r"(a[e]));
    }
    stsm4(frag + b * 8192 + ((frag_x ^ (j * 2)) << 4), h[0], h[1], h[2], h[3]);
  }
}

__device__ __forceinline__ int g1_block(int j, int c) { return j < 16 ? j : ((j + 12) & 15) ^ (c == 5 && j >= 28 ? 2 : 0); }
__device__ __forceinline__ int g2_block(int j, int c) { return j < 8 ? j : j == 8 ? 8 + c : j - (j - 9 < c); }
__device__ __forceinline__ int g3_tile(int j) { return j < 4 ? j >> 1 : j < 18 ? 0 : j >> 4; }
__device__ __forceinline__ int g3_block(int j, int c) {
  const int i = j < 32 ? (j < 16 ? 0xDCBA976543218080ull : 0x7654321BA9FEDCFEull) >> 4 * (j & 15) : j + (~j >> 2 & 4), o = i & 7;
  return 2 * (j < 32 && (o == c || o == 0) ? c - o : o) + (i >> 3 & 1);
}
__device__ __forceinline__ bool g3_is_up(int tile, int a) { return a == 1 || (a == 2 && tile >= 2); }
__device__ __forceinline__ int g3_atom(int tile, int a, int c) { return c * 7 + (tile & 1) * 3 + (a == 2 ? 1 : tile == 4 ? 6 : tile & 2); }
__device__ __forceinline__ int g4_block(int i) {
  return i < 16 ? 7 * (i & 7) + 3 * (i >> 3) : i < 48 ? 7 * ((i & 15) >> 1) + 3 * (i >> 5) + 1 + (i & 1) : 7 * (i & 7) + (i < 56 ? 6 : 0);
}

template <int N, int TAIL>
__device__ __forceinline__ void mainloop(Scratch* sc, float (&acc)[2][96], uint32_t sb, int ph, int j0, int nsteps, int pause_at, bool last,
                                         bool hand_over, bool local, int wg, int own = -1, const CUtensorMap* out = nullptr, int out_col = 0,
                                         int out_row = 0, int warp = 0, __nv_bfloat16* outp = nullptr) {
  constexpr int NSLOT = N == 128 ? 5 : 4, SLOT = N == 128 ? 32768 : 40960;
  const int lane = fresh_tid() & 31;
  const uint32_t full = sb + kBars + 8 * ring_base(ph);
  const uint32_t empty = map_cta(full + 8 * NSLOT, lane & 1);
  const uint32_t ring = desc_lo(sb + kRing, 16);
  int bi = j0 % NSLOT, par = (j0 / NSLOT) & 1;
  const int release_end = lane < (N == 192 && !hand_over ? 4 : 2) ? (last ? nsteps - 1 - NSLOT : nsteps) : 0;
  uint32_t rel = empty;
#pragma unroll 1
  for (int i = 0; i < nsteps - (TAIL > 0 ? TAIL + 1 : 0); i++) {
    uint32_t a = ring + bi * (SLOT >> 4), b = a + kToB;
    if (TAIL > 0 && i == 0) TSG(5);
    if (i == 0) nb_sync(kNbOrder + wg, ph == 0 && wg == 0 ? 160 : 256);
    if (ph == 0 && i == 1 - 2 * wg) cluster_wait();
    if (N == 192 && local) {
      a = ring + ((kStage + i * 16384) >> 4);
      b = ring + bi * (32768 >> 4) + desc_lo(32768, 8192) - desc_lo(0, 16);
    }
    if (ph == 0 && i >> 1 == own) a = ring + ((kOwn + (i & 1) * 16384) >> 4);
    if (ph == 1 && i == 8) a = ring + ((kStage + 32768) >> 4);
    if (TAIL > 0 && i == 0) TSG(6);
    mbar_wait(full + 8 * bi, par);
    if (N == 192 && local) mbar_wait(sb + kBars + 8 * (kHalfBar + i), 0);
    if (TAIL > 0 && i == 0) TSG(7);
    if (i == pause_at + 1) nb_sync(kNbWin + 1, 256);
    wg_fence();
    mma_k16<N>(acc, a, b, 0, ph == 0 ? i | wg : 1);
    mma_k16<N>(acc, a, b, 1);
    wg_commit();
    const bool release = (uint32_t)(i - 1) < (uint32_t)release_end;
    wg_wait<1>();
    mbar_arrive_cluster_if(rel, release);
    wg_fence();
    mma_k16<N>(acc, a, b, 2);
    mma_k16<N>(acc, a, b, 3);
    wg_commit();
    rel = empty + 8 * bi;
    if (++bi == NSLOT) { bi = 0; par ^= 1; }
    if (i == pause_at) nb_arrive(kNbWin, 256);
  }
  if (TAIL < 0) return;
  if (TAIL > 0) {
    uint32_t at[TAIL + 2];
    const int t = fresh_tid() & 127;
    uint32_t frag = sb + kStage + ((t >> 5) * 16 + (t & 15)) * 128, frag_x = ((t >> 4) & 1) ^ (t & 7);
    const uint32_t back = sb + kStage + (t >> 5) * 2048 + ((t >> 3) & 3) * 128, back_x = ((t ^ (t >> 3 & 3)) & 7) << 4;
    outp += (2 * (out_row + (t >> 5) * 16 + ((t >> 3) & 3)) + (blockIdx.x & 1)) * kD + out_col + (t & 7) * 8;
    static_assert(kTail == 5, "");
    uint4 part[8];
    mbar_wait(full + 8 * bi, par);
#pragma unroll
    for (int hf = 0; hf < 2; hf++) {
      const uint32_t a = ring + bi * (SLOT >> 4), b = a + kToB;
      wg_fence();
      mma_k16<N>(acc, a, b, 2 * hf);
      mma_k16<N>(acc, a, b, 2 * hf + 1);
      wg_commit();
      if (hf == 0) {
        wg_wait<1>();
        mbar_arrive_cluster_if(rel, (t & 31) < 2);
      }
      mbar_wait(sb + kBars + 8 * (hf ? kStgBar : kPartBar), hf);
#pragma unroll
      for (int k = 4 * hf; k < 4 * hf + 4; k++) part[k] = lds128(sb + kStage + 32768 + (t >> 5) * 4096 + (t & 31) * 16 + k * 512);
    }
    if (++bi == NSLOT) { bi = 0; par ^= 1; }
    auto last_rows = [&](int i0, int i1) {
#pragma unroll
      for (int i = i0; i < i1; i++) {
        if (i == 3) continue;
        at[i] = bi * (SLOT >> 4);
        mbar_wait(full + 8 * bi, par);
        if (++bi == NSLOT) { bi = 0; par ^= 1; }
      }
      wg_fence();
#pragma unroll
      for (int i = 4 * i0; i < 4 * i1; i++)
        wgmma_n128(acc[1], desc_kept(ring, sb) + ((i >> 2 != 3 ? at[i >> 2] + 512 : at[2]) + (i & 3) * 2),
                   desc_kept(ring, sb) + ((i >> 2 != 3 ? at[i >> 2] + kToB : at[0] + ((SLOT - 16) >> 4 << 16)) + (i & 3) * 128));
      wg_commit();
    };
    last_rows(0, 2);
#pragma unroll
    for (int b = 0; b < 4; b++) {
      if (b == 0) wg_wait<1>();
      if (b == 1) last_rows(3, 4);
      if (b == 2) wg_wait<0>();
      if (!(b & 1)) {
#pragma unroll
        for (int i = 0; i < 64; i++) asm volatile("" : "+f"(acc[b >> 1][i])::"memory");
        if (t == 0) TSS(b);
      }
      stage_quarter(&acc[b >> 1][32 * (b & 1)], frag, frag_x, b, b < 2 ? &part[4 * b] : nullptr);
      if (b == 3) {
        __syncwarp();
        uint4 v[4];
#pragma unroll
        for (int i = 0; i < 4; i++) v[i] = lds128(back + b * 8192 + i * 512 + ((i & 1) ? back_x ^ 64 : back_x));
#pragma unroll
        for (int i = 0; i < 4; i++) __stcs((uint4*)(outp + ((b >> 1) * 128 + i * 8) * kD + (b & 1) * 64), v[i]);
        if (t == 0) TSS(4 + b);
        continue;
      }
      if (b < 2) last_rows(2 + 2 * b, 3 + 2 * b);
      fence_async_smem();
      __syncwarp();
      if (elect_one()) tma_store3d(out, sb + kStage + b * 8192 + warp * 2048, out_col + (b & 1) * 64, out_row + (b >> 1) * 64 + warp * 16, blockIdx.x & 1);
      __syncwarp();
      if (t == 0) TSS(4 + b);
    }
    if (elect_one()) {
      bulk_commit();
      bulk_wait_read();
    }
    if (t == 0) TSS(1);
    return;
  }
  if (hand_over) nb_arrive(kNbOrder + (wg ^ 1), 256);
  if (N == 192 && !local) {
    mbar_wait(sb + kBars + 8 * (kAuxBar + wg), j0 < 32);
    if (j0 < 32) mbar_wait(sb + kBars + 8 * kStatBar, 1);
    mbar_wait(sb + kBars + 8 * (kStgBar + wg), ((j0 >> 5) ^ wg ^ 1) & 1);
  }
  wg_wait<0>();
  mbar_arrive_cluster_if(rel, release_end == nsteps);
#pragma unroll
  for (int i = 0; i < N / 2; i++) asm volatile("" : "+f"(acc[0][i]), "+f"(acc[1][i])::"memory");
}

template <int PH>
struct Ring {
  static constexpr int NSLOT = 4 + (PH & 1), SLOT = PH & 1 ? 32768 : 40960;
  uint32_t full, dst0;
  int j = PH == 0 ? 4 : 0, bi = 0, par = PH == 0 ? 0 : 1;
  __device__ __forceinline__ Ring(uint32_t sb, uint32_t ofs) : full(sb + kBars + 8 * (PH * 9 - (PH & 1))), dst0(sb + kRing + ofs) {}
  __device__ __forceinline__ uint32_t bar() const { return full + 8 * bi; }
  __device__ __forceinline__ uint32_t dst() const { return dst0 + bi * SLOT; }
  __device__ __forceinline__ void acquire_first() const {
    const bool first = j < NSLOT;
    mbar_wait(full + (first ? 8 * min(j, 3) - 32 : 8 * (NSLOT + bi)), PH == 2 && first ? 0 : par);
  }
  __device__ __forceinline__ void acquire() const { mbar_wait(full + 8 * (NSLOT + bi), par); }
  __device__ __forceinline__ void next() {
    j++;
    if (++bi == NSLOT) { bi = 0; par ^= 1; }
  }
};

__device__ __forceinline__ void check_blocks(const Params& p, Scratch* sc, uint32_t sb, int r, int c, bool g3, uint32_t& par) {
  const int lane = fresh_tid() & 31, nslot = g3 ? 4 : 5, slot_bytes = g3 ? 40960 : 32768;
  const uint32_t mine = (lane >> 2) * 132 + (lane & 3) * 32, ring_end = sb + kRing + kStage + mine;
  const uint32_t to_full = 8 * (kLandBar - (g3 ? ring_base(2) : ring_base(1)));
  uint32_t src = sb + kRing + mine + (g3 ? 0 : 4 * 32768);
  int bi = g3 ? 0 : 4, spins = 0;
#pragma unroll 1
  for (int i = g3 ? 2 : 9; i < 16;) {
    const uint32_t land = sb + kBars + 8 * (kLandBar + bi);
    mbar_wait(land, (par >> bi) & 1);
    uint32_t v[16];
#pragma unroll
    for (int k = 0; k < 16; k++) v[k] = lds32(src + k * 1024);
#pragma unroll
    for (int k = 0; k < 5; k++) v[k] = max(max(v[3 * k + 1], v[3 * k + 2]), k ? v[3 * k] : max(v[0], v[15]));
    const bool again = __any_sync(~0u, max(max(max(v[0], v[1]), v[2]), max(v[3], v[4])) == kPoison);
    asm volatile("{\n.reg .pred p;\nsetp.eq.u32 p, %1, 0;\n@p mbarrier.arrive.shared::cta.b64 _, [%0];\n}\n"
                 ::"r"(land - to_full), "r"(lane + again) : "memory");
    par ^= 1u << bi;
    if (again) {
      if (++spins > 100000) __trap();
      if (elect_one()) {
        mbar_expect_tx(land, 16384);
        tma2d(src - mine, g3 ? &p.h : &p.o, (g3 ? g3_block(i + 2, c) : g2_block(i, c)) * 64, r * 128, land);
      }
      nb_sync(kNbSelf + 1, 32);
      continue;
    }
    if (lane == 0 && (i == 2 || i == 3 || (!g3 && (i == 9 || i == 12)))) TS(i < 4 ? 88 + 2 * i : i == 9 ? 120 : 122);
    i++;
    if (++bi == nslot) bi = 0;
    src += slot_bytes;
    if (src == ring_end) src -= kStage;
  }
}

__device__ __forceinline__ void colsum_cta(const Params& p, Scratch* sc, uint32_t sb, int warp, int bid) {
  constexpr int kSlots = 4, kSlot = 49152;
  constexpr int kRows = kTail * 32768;
  static_assert(kRows + 65536 <= kCs, "");
  const int lane = threadIdx.x & 31, c0 = (bid - 128) * 2;
  const uint32_t full = sb + kBars, empty = full + 8 * kSlots;
  const uint32_t event = full + 64, stored = full + 96, rfull = full + 128, rempty = full + 192;
  if (threadIdx.x == 0) {
#pragma unroll 1
    for (int i = 0; i < 32; i++) mbar_init(full + 8 * i, i & (i < 16 ? 4 : 8) ? 8 : 1);
    asm volatile("fence.mbarrier_init.release.cluster;" ::: "memory");
  }
  __syncthreads();
  const uint32_t ep = ld_epoch(sc);
  if (warp == 8) {
    if (elect_one()) {
#pragma unroll 1
      for (int n = 0; n < 112 + kSlots; n++) {
        const int u = n >> 4, c = c0 + ((n >> 3) & 1), k0 = (n & 7) * 128, slot = n & (kSlots - 1);
        if (n == kQuietAt) flag_wait(sc->flags + kFlPace, ep);
        const uint32_t bar = full + 8 * slot;
        mbar_wait(empty + 8 * slot, ((n / kSlots) & 1) ^ 1);
        if (n == 108) mbar_arrive(event);
        if (u == 7) continue;
        mbar_expect_tx(bar, u == 6 ? 32768 : 49152);
#pragma unroll
        for (int a = 0; a < 3; a++) {
          if (a == 2 && u == 6) break;
          const CUtensorMap* m = u < 2 ? &p.wqkv : g3_is_up(u - 2, a) ? &p.wu : &p.wg;
          const int col = (u < 2 ? a * 16 + u * 8 + c : g3_atom(u - 2, a, c)) * 64;
          tma2d(sb + slot * kSlot + a * 8192, m, col, k0, bar);
          tma2d(sb + slot * kSlot + a * 8192 + 24576, m, col, k0 + 64, bar);
        }
      }
      mbar_wait(event + 8, 0);
      fence_async();
#pragma unroll 1
      for (int n = 0, r = 0, i = 0; r < 16; n++) {
        const uint32_t bar = rfull + 8 * (n & 7);
        mbar_wait(bar + 64, ~n >> 3 & 1);
        mbar_expect_tx(bar, r ? 8192 : 40960);
        tma2d(sb + kRows + (n & 7) * 8192, &p.hhst, i * (7 * 64), r * 128, bar);
#pragma unroll 1
        for (int a = r ? 4 : 0; a < 4; a++) tma2d(sb + i * 32768 + a * 8192, &p.wd, (c0 * 2 + a) * 64, i * (7 * 64), bar);
        if (++i == kTail) { i = 0; r++; }
      }
    }
  } else if (warp < 8) {
    uint32_t src[3];
#pragma unroll
    for (int j = 0; j < 3; j++) src[j] = sb + ((warp * 3 + j) >> 3) * 8192 + lane * 128 + ((((warp * 3 + j) & 7) ^ (lane & 7)) << 4);
    const uint32_t ones = 0x3F803F80u;
#pragma unroll 1
    for (int s = 0; s < 112; s++) {
      float a[3][2][4] = {};
#pragma unroll 1
      for (;; s++) {
      const int slot = s & (kSlots - 1);
      mbar_wait(full + 8 * slot, (s / kSlots) & 1);
      uint32_t b[3][4][4];
#pragma unroll
      for (int j = 0; j < 3; j++)
#pragma unroll
        for (int k = 0; k < 4; k++)
          asm volatile("ldmatrix.sync.aligned.m8n8.x4.trans.shared.b16 {%0,%1,%2,%3}, [%4];"
                       : "=r"(b[j][k][0]), "=r"(b[j][k][1]), "=r"(b[j][k][2]), "=r"(b[j][k][3])
                       : "r"(src[j] + slot * kSlot + (k >> 1) * 24576 + (k & 1) * 4096) : "memory");
      __syncwarp();
      if (lane == 0) mbar_arrive(empty + 8 * slot);
#pragma unroll
      for (int k = 0; k < 4; k++)
#pragma unroll
        for (int j = 0; j < 3; j++) {
          mma16816(a[j][0], ones, ones, ones, ones, b[j][k][0], b[j][k][1]);
          mma16816(a[j][1], ones, ones, ones, ones, b[j][k][2], b[j][k][3]);
        }
      if ((s & 7) == 7) break;
      }
      {
        if (lane < 12) {
          const int j = lane >> 2;
          const float x = j == 0 ? a[0][0][0] + a[0][1][0] : j == 1 ? a[1][0][0] + a[1][1][0] : a[2][0][0] + a[2][1][0];
          const float y = j == 0 ? a[0][0][1] + a[0][1][1] : j == 1 ? a[1][0][1] + a[1][1][1] : a[2][0][1] + a[2][1][1];
          const float x1 = bf_rest(x), y1 = bf_rest(y);
          const bool split = s < 32;
          st_b128(sc->cs + ((s >> 4) * 8 + c0 + ((s >> 3) & 1)) * 96 + warp * 12 + lane, split ? bf_upper(x, y) : __float_as_uint(x),
                  split ? bf_upper(x1, y1) : __float_as_uint(y), bf_upper(bf_rest(x1), bf_rest(y1)), ep);
        }
        if (threadIdx.x == 0 && (s & 8)) TSK(s >> 4);
      }
    }
    const int wg = warp >> 2;
#pragma unroll 1
    for (int r = wg; r < 16; r += 2) {
      float acc[128];
#pragma unroll
      for (int i = 0; i < 128; i++) asm volatile("" : "=f"(acc[i]));
      const uint32_t da = desc_lo(sb + kRows, 16);
      uint32_t db = desc_lo(sb, 8192);
      int n = r * kTail - 1;
      if (r) nb_sync(kNbOrder + wg, 256);
#pragma unroll 1
      for (int i = 0; i < kTail; i++, db += 2048) {
        const uint32_t done = rempty + 8 * (n & 7);
        n++;
        mbar_wait(rfull + 8 * (n & 7), n >> 3 & 1);
        wg_fence();
#pragma unroll
        for (int k = 0; k < 4; k++) wgmma_n256(acc, desc(da + (n & 7) * 512) + k * 2, desc(db) + k * 128, k | i);
        wg_commit();
        wg_wait<1>();
        if (lane < 2 && i) mbar_arrive(done);
      }
      if (r < 15) nb_arrive(kNbOrder + (wg ^ 1), 256);
      wg_wait<0>();
#pragma unroll
      for (int i = 0; i < 128; i++) asm volatile("" : "+f"(acc[i])::"memory");
      if (lane < 2) mbar_arrive(rempty + 8 * (n & 7));
#pragma unroll
      for (int i = 0; i < 16; i++) {
        const float* v = &acc[8 * i];
        __stcg(sc->part + (r * 8 + c0) * 1024 + (warp & 3) * 256 + lane + (i >> 3) * 1024 + (i & 7) * 32,
               make_uint4(pack_bf16(v[0], v[1]), pack_bf16(v[2], v[3]), pack_bf16(v[4], v[5]), pack_bf16(v[6], v[7])));
      }
      __syncwarp();
      if ((r & 2) && lane == 0) mbar_arrive(stored + 8 * (r >> 2));
    }
  } else if (warp == 10) {
    mbar_wait(event, 0);
    flag_wait(sc->flags + kFlHH + (lane & 15) * kFlRow, ep * 8);
    fence_async();
    __syncwarp();
    if (lane == 0) mbar_arrive(event + 8);
  } else if (threadIdx.x == 352) {
#pragma unroll 1
    for (int r = 0; r < 16; r += 4) {
      mbar_wait(stored + 2 * r, 0);
      flag_signal(sc->flags + kFlPart + (c0 >> 1) + r * kFlRow);
    }
    TSK(7);
  }
}

#define PROF_BEGIN
template <bool BY_SM>
__global__ void __cluster_dims__(2, 1, 1) __launch_bounds__(kThreads, 1) fused_block_kernel(Scratch* sc, const __nv_bfloat16* xp, const __nv_bfloat16* wqkvp, __nv_bfloat16* outp,
                                                                   const __grid_constant__ Params p) {
  extern __shared__ __align__(1024) uint8_t smem_raw[];
  if (threadIdx.x < 56) {
    const int l = threadIdx.x & 31, b = blockIdx.x & 127;
    if (threadIdx.x < 32) prefetch_l2(xp + (b * 16 + (l & 15)) * kD + (l >> 4) * 64);
    else prefetch_l2(wqkvp + b * (3 * kD) + (l >> 3) * kD + (l & 7) * 64);
  }
  const uint32_t sb = smem_u32(smem_raw);
  const int bid = role_id<BY_SM>();
  const int r = bid >> 3, c = bid & 7, rank = blockIdx.x & 1;
  auto first_fill = [&](int j) {
    const uint32_t fb = sb + kBars + 8 * j, dst = sb + kRing + j * 40960;
    mbar_expect_tx(fb, 40960);
    tma3d(j >> 1 == c ? sb + kOwn + (j & 1) * 16384 : dst, &p.x, j * 64, (r >> 1) * 128, rank, fb);
#pragma unroll
    for (int a = 0; a < 3; a++) tma2d(dst + 16384 + a * 8192, &p.wqkv, a * kD + c * 64, j * 64, fb);
    mbar_arrive(fb);
  };
  const int tid = threadIdx.x, warp = __shfl_sync(~0u, tid >> 5, 0), wg = warp >> 2;
  if (bid >= 128) {
    if (tid == 0) PROF_BEGIN;
    colsum_cta(p, sc, sb, warp, bid);
    return;
  }
  if (wg == 2) {
    if (warp == 8 && elect_one()) {
#pragma unroll
      for (int j = 0; j < 4; j++) mbar_init(sb + kBars + 8 * j, 2);
      asm volatile("fence.mbarrier_init.release.cluster;" ::: "memory");
      first_fill(0);
      TSS(0);
    }
    __syncwarp();
    if (warp == 8) nb_arrive(kNbOrder, 160);
    asm volatile("setmaxnreg.dec.sync.aligned.u32 40;");
    if (warp == 8) {
      cluster_arrive();
      if (elect_one()) {
#pragma unroll 1
        for (int j = 1; j < 4; j++) first_fill(j);
        TSS(1);
      }
      __syncwarp();
    } else {
      if (elect_one()) {
        uint64_t shifts = warp == 9 ? bar_shifts(4) : warp == 10 ? bar_shifts(22) : bar_shifts(40);
#pragma unroll 1
        for (int i = 0; i < 18; i++, shifts >>= 3) mbar_init(sb + kBars + 8 * (18 * warp - 158 + i), 1u << (shifts & 7));
        sts32(sb + kZero, 0);
        sts32(sb + kScale + 4, 0);
        sts32(sb + kRole, bid);
        sts128(sb + kOnes, make_uint4(0x3F803F80u, 0, 0, 0x3F803F80u));
        asm volatile("fence.mbarrier_init.release.cluster;" ::: "memory");
      }
      __syncwarp();
      cluster_arrive();
    }
    cluster_wait();
    const uint32_t ep = ld_epoch(sc);
    if (tid == 320) sts32(sb + kEpoch, ep);
    if (tid == 320) PROF_BEGIN;
    const int pw = warp & 3;
    if (pw == 0) {
      if (elect_one()) {
        const int row = r * 128;
        const uint32_t land = sb + kBars + 8 * kLandBar;
#pragma unroll 1
        for (Ring<0> q(sb, 0); q.j < 32; q.next()) {
          q.acquire();
          const int kb = g1_block(q.j, c);
          if (q.j >= 16 && (q.j < 20 || kb >> 1 == c)) { mbar_arrive(q.bar()); continue; }
          mbar_expect_tx(q.bar(), 16384);
          tma3d(kb >> 1 == c ? sb + kOwn + (kb & 1) * 16384 : q.dst(), &p.x, kb * 64, (r >> 1) * 128, rank, q.bar());
        }
        prefetch_map(&p.o);
        prefetch_map(&p.o16);
        flag_wait(sc->flags + kFlO + r * kFlRow, ep * 8);
        fence_async();
        TS(40);
#pragma unroll 1
        for (Ring<1> q(sb, 0); q.j < 16; q.next()) {
          q.acquire_first();
          if (q.j == 8) {
            prefetch_map(&p.wg);
            prefetch_map(&p.wu);
            prefetch_map(&p.h);
            prefetch_map(&p.h16);
            mbar_wait(sb + kBars + 8 * kSentBar, 0);
            mbar_arrive(q.bar());
            mbar_arrive(sb + kBars + 8 * (kStgBar + 1));
            if (bid == 0) __stcg(sc->flags + kFlPace, ep);
            __nanosleep(kGateONs);
            continue;
          }
          const uint32_t bar = q.j < 8 ? q.bar() : land + 8 * q.bi;
          if (q.j == 9) TS(41);
          mbar_expect_tx(bar, 16384);
          tma2d(q.dst(), &p.o, g2_block(q.j, c) * 64, row, bar);
        }
#pragma unroll 1
        for (Ring<2> q(sb, 0); q.j < 64; q.next()) {
          q.acquire_first();
          if ((0x000F000F003C000Full >> q.j & 1) && q.j != 28 + c) { mbar_arrive(q.bar()); continue; }
          if (q.j == 4) { __nanosleep(kGateHNs); TS(42); }
          const uint32_t bar = q.j < 18 ? land + 8 * q.bi : q.bar();
          mbar_expect_tx(bar, 16384);
          tma2d(q.dst(), &p.h, g3_block(q.j, c) * 64, row, bar);
        }
        prefetch_map(&p.hh);
        prefetch_map(&p.out);
        Ring<3> q(sb, 0);
#pragma unroll 1
        for (; q.j < 16; q.next()) {
          q.acquire_first();
          if (q.j == 0) { mbar_arrive(q.bar()); continue; }
          mbar_expect_tx(q.bar(), 16384);
          tma2d(q.dst(), &p.h, ((q.j + 9) & 15) * 64, row, q.bar());
        }
#pragma unroll 1
        for (int wv = 0; wv < 5; wv++) {
          if (wv == 3 && c < kTail) tma_prefetch2d(&p.hhst, c * (7 * 64), row + 64);
          if (wv == 0 || wv >= 3) {
            mbar_wait(sb + kBars + 8 * (kWaveBar + (wv >> 1)), 0);
            fence_async();
          }
          const int dbl = wv == 2 || wv == 3, f0 = wv == 4 ? 6 : (wv & 1) * 3 + dbl;
#pragma unroll 1
          for (int i = wv ? 0 : kTail; i < 8 << dbl; i++, q.next()) {
            q.acquire();
            mbar_expect_tx(q.bar(), 16384);
            tma2d(q.dst(), &p.hh, ((i >> dbl) * 7 + f0 + (i & dbl)) * 64, row, q.bar());
          }
        }
#pragma unroll 1
        for (int i = 0; i < kTail - 1; i++, q.next()) {
          q.acquire();
          mbar_expect_tx(q.bar(), i < 3 ? 16384 : 8192);
          tma2d(q.dst() + 8192, &p.hhst, i * (7 * 64), row + 64, q.bar());
          if (i == 2) tma2d(q.dst(), &p.hhst, (kTail - 1) * (7 * 64), row + 64, q.bar());
          if (i == rank) tma2d_mc(q.dst(), &p.wd, (c * 2 + rank) * 64, (kTail - 1) * (7 * 64), q.bar());
        }
      }
    } else if (pw == 1) {
      if (elect_one()) {
        const int rp = r >> 1;
#pragma unroll 1
        for (Ring<0> q(sb, 16384); q.j < 32; q.next()) {
          q.acquire();
          mbar_expect_tx(q.bar(), 24576);
          const int col = ((q.j >> 4) * 8 + c) * 64, k0 = g1_block(q.j, c) * 64;
          tma2d_mc(q.dst() + rank * 8192, &p.wqkv, rank * kD + col, k0, q.bar());
          if ((q.j & 1) == rank) tma2d_mc(q.dst() + 16384, &p.wqkv, 2 * kD + col, k0, q.bar());
          if (q.j == max(r, 4))
            for (int a = 0; a < 3; a++) tma_prefetch2d(&p.wqkv, a * kD + (8 + c) * 64, ((r + 12) & 15) * 64);
          if (q.j >> 1 == rp + 8) tma_prefetch2d(&p.wo, (c * 2 + rank) * 64, (q.j & 15) * 64);
        }
        if (r < 6) tma_prefetch2d(rp == 1 ? &p.wu : &p.wg, (c * 7 + 3 + (rp >> 1)) * 64, (c * 2 + rank) * 64);
#pragma unroll 1
        for (Ring<1> q(sb, 16384 + rank * 8192); q.j < 16; q.next()) {
          q.acquire_first();
          mbar_expect_tx(q.bar(), 16384);
          tma2d_mc(q.dst(), &p.wo, (c * 2 + rank) * 64, g2_block(q.j, c) * 64, q.bar());
        }
        const CUtensorMap* mine = rank ? &p.wu : &p.wg;
#pragma unroll 1
        for (Ring<2> q(sb, 16384); q.j < 64; q.next()) {
          const int tile = g3_tile(q.j), f0 = c * 7 + (tile & 1) * 3, fp = f0 + (tile & 2);
          const int k0 = g3_block(q.j, c) * 64;
          q.acquire_first();
          mbar_expect_tx(q.bar(), 24576);
          const uint32_t dst = q.j < 4 ? sb + kRing + (q.j + 1) * 32768 : q.dst();
          tma2d_mc(dst + rank * 8192, mine, fp * 64, k0, q.bar());
          if ((q.j & 1) == rank) tma2d_mc(dst + 16384, tile & 2 ? &p.wu : &p.wg, (f0 + 1) * 64, k0, q.bar());
          const int d = q.j - kPfStep - (c & 1) * 5 - (r >> 2);
          if (d == 0 || d == 11 || d == 22) {
            const int f = c * 7 + (d == 0 ? 2 : d == 11 ? 5 : 6);
            tma_prefetch2d(&p.wg, f * 64, r * 64);
            tma_prefetch2d(&p.wu, f * 64, r * 64);
            if (d != 22) tma_prefetch2d(&p.wu, (f - 1) * 64, r * 64);
            else if (rp < kTail) tma_prefetch2d(&p.wd, (c * 2 + rank) * 64, rp * (7 * 64));
          }
          if (q.j >> 1 == rp + 24) tma_prefetch2d(&p.wd, (c * 2 + rank) * 64, g4_block(q.j & 15) * 64);
        }
        Ring<3> q(sb, 16384 + rank * 8192);
#pragma unroll 1
        for (; q.j < 16; q.next()) {
          q.acquire_first();
          mbar_expect_tx(q.bar(), 16384);
          tma2d_mc(q.dst(), mine, (c * 7 + 6) * 64, ((q.j + 9) & 15) * 64, q.bar());
          if (q.j >> 1 == rp) tma_prefetch2d(&p.wd, (c * 2 + rank) * 64, g4_block(q.j + 16) * 64);
        }
#pragma unroll 1
        for (int wv = 0; wv < 6; wv++) {
          const int dbl = wv == 2 || wv == 3, f0 = wv == 4 ? 6 : wv == 5 ? 0 : (wv & 1) * 3 + dbl;
#pragma unroll 1
          for (int i = wv ? 0 : kTail; i < (wv == 5 ? kTail - 1 : 8 << dbl); i++, q.next()) {
            q.acquire();
            mbar_expect_tx(q.bar(), 16384);
            tma2d_mc(q.dst(), &p.wd, (c * 2 + rank) * 64, ((i >> dbl) * 7 + f0 + (i & dbl)) * 64, q.bar());
            if ((q.j & 15) >> 1 == rp && q.j < 40 + kTail) tma_prefetch2d(&p.wd, (c * 2 + rank) * 64, g4_block(q.j + 16) * 64);
          }
        }
      }
    } else {
      const int cw = pw - 2;
      const uint32_t stg = sb + kStage + cw * 32768, rb = sb + kBars + 8 * kResBar;
      uint32_t land_par = 0;
      if (cw == 0) {
#pragma unroll 1
        for (int i = 0; i < 16; i++) sts128(sb + kFill + i * 512 + (tid & 31) * 16, make_uint4(kPoison, kPoison, kPoison, kPoison));
        __nanosleep(kSampleNs);
        const uint32_t l15 = tid & 15;
        const uint4 os = __ldg(p.wop + ((tid & 31) * 128 + c * 16 + l15));
        const uint4 gs = __ldg((tid & 16 ? p.wup : p.wgp) + (l15 * 451 + c * 56));
        const uint4 ws = __ldg((const uint4*)wqkvp + ((tid & 7) * 385 + (tid & 24) * 16 + (8 + c) * 8));
        sts64(sb + kScale, __float_as_uint(low_peak(os) * kBias3 * low_peak(gs)), __float_as_uint(low_peak(ws) * kBias1) | 1);
        if (tid == 320) TS(93);
      }
#pragma unroll 1
      for (int ev = -1; ev < 4; ev++) {
        const bool quads = cw == 0 && ev == 1;
        if (ev >= cw && !quads) nb_sync(kNbPub + cw, 160);
        if (ev >= cw && elect_one()) {
          if (quads) {
            mbar_wait(sb + kBars + 8 * (kHalfBar + 1), 0);
#pragma unroll 1
            for (int i = 0; i < 2; i++) {
              __nanosleep(i ? kPaceNs : kHoldNs);
              tma_store2d(&p.hst, stg + 16384 + i * 8192, c * 128 + 64, r * 128 + i * 64);
              TS(100 + i);
            }
            bulk_commit();
            bulk_wait_read();
            mbar_arrive(sb + kBars + 8 * kStgBar);
          } else {
            const int it = ev - 2 + cw, f0 = c * 7 + (1 - cw) * 3, fp = it == 2 ? c * 7 + 6 : f0 + 2 * it;
            const bool is_o = ev == 0;
            const CUtensorMap* m = is_o ? &p.ost : &p.hhst;
            const int b0 = is_o ? c : f0 + 1, b1 = fp;
#pragma unroll 1
            for (int i = is_o || it == 1 ? 0 : 2; i < (is_o ? 2 : 4); i++) {
              tma_store2d(m, stg + i * 8192, (i < 2 ? b0 : b1) * 64, r * 128 + (i & 1) * 64);
              if (!is_o) {
                bulk_commit();
                bulk_wait_read();
                __nanosleep(kPaceNs);
              }
            }
            bulk_commit();
            bulk_wait_all();
            mbar_arrive(sb + kBars + 8 * (kStgBar + cw));
            flag_signal(sc->flags + kFlHH + ev * 2 - 3 + cw + r * kFlRow);
            TS(44 + cw * 8 + ev);
            if (ev == 2 && cw) {
              mbar_expect_tx(rb, 32768);
#pragma unroll 1
              for (int i = 0; i < 2; i++) tma2d(stg + i * 16384, &p.h, c * 128 + i * 64, r * 128, rb);
            }
          }
        }
        nb_sync(kNbSelf + cw, 32);
        if (ev >= 2 && ev + cw >= 3 && elect_one()) {
          const int wv = cw == 0 ? 3 : ev == 2 ? 0 : 4;
#pragma unroll 1
          for (int i = wv; i <= max(wv, 2); i++) flag_wait(sc->flags + kFlHH + i + r * kFlRow, ep * 8);
          fence_async();
          mbar_arrive(sb + kBars + 8 * (kWaveBar + (wv >> 1)));
          if (wv == 4) {
            flag_wait(sc->flags + kFlPart + (c >> 1) + (r & 12) * kFlRow, ep);
            fence_async();
            mbar_expect_tx(sb + kBars + 8 * kPartBar, 16384);
#pragma unroll 1
            for (int i = 0; i < 2; i++) {
              asm volatile("cp.async.bulk.shared::cluster.global.mbarrier::complete_tx::bytes [%0], [%1], 8192, [%2];"
                           ::"r"(stg + i * 8192), "l"(sc->part + bid * 1024 + i * 512), "r"(sb + kBars + 8 * kPartBar) : "memory");
              __nanosleep(kPartNs);
            }
            TSK(56);
          }
        }
        nb_sync(kNbSelf + cw, 32);
#pragma unroll 1
        for (int sub = 0; ev < 3 && (ev != 0 || cw == 1); sub++) {
          nb_sync(kNbSelf + cw, 32);
          if (ev == 0) check_blocks(p, sc, sb, r, c, sub, land_par);
          const int u = ev < 0 ? cw : 2 * ev + 1 + cw, lane = fresh_tid() & 31;
          if (u == 1 && !sub) {
            uint3 st[5];
            load_tagged<5, true>(st, sc->stat1 + r * 128 + lane, 32, ep, (r < 2 ? -8 : -264) - (lane & 24));
#pragma unroll
            for (int i = 0; i < 4; i++) sts64(sb + kStat + (i * 32 + lane) * 8, st[i].x, st[i].y);
            sts64(sb + kStat - 64 + (lane & 7) * 8, st[4].x, st[4].y);
            nb_sync(kNbSelf + cw, 32);
            if (lane < 4) mbar_arrive(sb + kBars + 8 * kStatBar);
            if (lane == 0) TS(17);
          }
          if (u == 1) {
            const uint4* gh = sc->halo + ((sub * 16 + r - 2) * 8 + c) * 192 + lane;
            uint4 hv[6] = {};
            nb_sync(kNbHalo, 64);
            uint32_t ns = sub ? kHaloNs : 2 * kBackoffNs;
#pragma unroll 1
            for (int spins = 0; r >= 2; spins++) {
              if (ns) __nanosleep(ns);
              ns = sub ? 0 : kBackoffNs;
              if (spins > 2000000) __trap();
#pragma unroll
              for (int i = 0; i < 6; i++) hv[i] = ld_b128(gh + i * 32);
              uint32_t bad = (hv[5].y ^ ep) | (hv[5].z ^ ep);
#pragma unroll
              for (int i = 0; i < 6; i++) bad |= hv[i].w ^ ep;
              if (!__any_sync(~0u, bad != 0)) break;
            }
            const uint32_t dst = sb + kStage + sub * 32768 + lane * 16;
            sts128(dst, make_uint4(hv[0].x, hv[0].y, hv[0].z, hv[1].x));
            sts128(dst + 512, make_uint4(hv[1].y, hv[1].z, hv[2].x, hv[2].y));
            sts128(dst + 1024, make_uint4(hv[2].z, hv[3].x, hv[3].y, hv[3].z));
            sts128(dst + 1536, make_uint4(hv[4].x, hv[4].y, hv[4].z, hv[5].x));
            nb_arrive(kNbHalo + 1, 64);
            if (lane == 0) TS(123 + sub);
          }
          if (sub) break;
          uint3 v[3];
          load_tagged<3, false>(v, sc->cs + c * 96 + (u * 768 + lane), 32, ep);
          if (u < 2) {
#pragma unroll
            for (int i = 0; i < 3; i++)
#pragma unroll
              for (int k = 0; k < 8; k++)
                sts32(sb + kAug + cw * 4096 + i * 1024 + k * 128 + ((lane * 4) ^ (k * 16)), k == 7 ? 0x3F803F80u : k == 4 || k == 6 ? v[i].z : k & 1 && k != 5 ? v[i].y : v[i].x);
            fence_async_smem();
          } else {
#pragma unroll
            for (int i = 0; i < 3; i++) sts64(sb + kCs + cw * 768 + (i * 32 + lane) * 8, v[i].x, v[i].y);
          }
          nb_sync(kNbSelf + cw, 32);
          if (lane == 0) { mbar_arrive(sb + kBars + 8 * (kAuxBar + cw)); TS(104 + u); }
        }
        nb_sync(kNbSelf + cw, 32);
        if (ev < 0 && cw == 0 && elect_one()) {
#pragma unroll 1
          for (int i = 0; i < 6; i++) {
            __nanosleep(i == 0 ? (c >> 1) * (kFillNs / 4) : kFillNs);
            tma_store2d(i < 2 ? &p.ost : &p.hst, sb + kFill, i < 2 ? (8 + c) * 64 : (c * 2 - 1 + (i >> 1)) * 64, r * 128 + (i & 1) * 64);
            bulk_commit();
          }
          uint32_t peer;
          asm volatile("ld.shared::cluster.b32 %0, [%1];" : "=r"(peer) : "r"(map_cta(sb + kRole, rank ^ 1)) : "memory");
          if (peer != (bid ^ 8)) __trap();
          TS(90);
        }
        nb_sync(kNbSelf + cw, 32);
      }
    }
  } else {
    if (tid == 0) TSS(2);
    cluster_arrive();
    float bias = 0.f;
    float sx = 0.f, mx = 0.f;
    asm volatile("setmaxnreg.inc.sync.aligned.u32 232;");
    if (tid == 0) TSS(4);
    int task;
    asm volatile("mov.u32 %0, %1;" : "=r"(task) : "r"(8 - wg));

#pragma unroll 1
    for (task = __shfl_sync(~0u, task, 0);; task++) {
      if (task == 1 + wg || task == 9 - wg) {
        const int t = fresh_tid();
        uint2 scale;
        do asm volatile("ld.volatile.shared.v2.b32 {%0, %1}, [%2];" : "=r"(scale.x), "=r"(scale.y) : "r"(sb + kScale) : "memory");
        while (scale.y == 0);
        __syncwarp();
        bias = bias_at(low_peak(lds128(sb + (task > 5 ? kRing : kStage + wg * 32768) + (t & 126) * 64 + (t & 14) * 8 + (t & 1) * 8192)) *
                       __uint_as_float(task > 5 ? scale.y : scale.x));
        if (t == 128 && task > 5) TS(95);
      }
      if (wg == 0 && (task == 1 || task == 4)) {
        float acc[2][96];
        const int t = fresh_tid() & 127;
        const uint32_t frag = sb + kOwn + ((t >> 5) * 16 + (t & 15)) * 128, frag_x = ((t >> 4) & 1) ^ (t & 7);
        TSG(2);
        if (task == 4) mbar_wait(sb + kBars + 8 * kResBar, 0);
#pragma unroll
        for (int i = 0; i < 16; i++) {
          uint32_t v[4];
          ldsm4(frag + (i >> 3) * 16384 + (i & 1) * 8192 + ((frag_x ^ (i & 6)) << 4), v);
#pragma unroll
          for (int e = 0; e < 4; e++) {
            float* d = &acc[i & 1][8 * (i >> 1) + 2 * e];
            asm("shl.b32 %0, %1, 16;" : "=f"(d[0]) : "r"(v[e]));
            asm("and.b32 %0, %1, 0xFFFF0000;" : "=f"(d[1]) : "r"(v[e]));
          }
        }
        __syncwarp();
        if ((t & 31) == 0) mbar_arrive(sb + kBars + 8 * kResFreeBar);
        TSG(4);
        if ((tid & 127) == 0) TS(task == 1 ? 6 : 14);
        if (task == 4) {
          mainloop<128, kTail>(sc, acc, sb, 3, 16, 56, -2, true, false, false, 0, -1, &p.out, c * 128, (r >> 1) * 128, warp, outp);
          if ((tid & 127) == 0) TSK(15);
          if (fresh_tid() == 0) {
            if (bid == 0) __stcg(sc->epoch, lds32(sb + kEpoch));
            TSK(19);
          }
          break;
        }
        mainloop<128, -1>(sc, acc, sb, 1, 0, 15, kPauseG2, false, true, false, 0);
        const int t2 = fresh_tid() & 127;
        const uint32_t frag2 = sb + kStage + ((t2 >> 5) * 16 + (t2 & 15)) * 128, frag2_x = ((t2 >> 4) & 1) ^ (t2 & 7);
        const uint32_t empty = map_cta(sb + kBars + 8 * (ring_base(1) + 5), t2 & 1);
        mbar_wait(sb + kBars + 8 * kStgBar, 0);
        mbar_wait(sb + kBars + 8 * ring_base(1), 1);
#pragma unroll
        for (int m = 0; m < 2; m++) {
          const uint32_t a = desc_lo(sb + kRing, 16);
          wg_fence();
#pragma unroll
          for (int k = 0; k < 4; k++) wgmma_n128(acc[m], desc_kept(a, sb) + (m * 512 + k * 2), desc_kept(a, sb) + (kToB + k * 128));
          wg_commit();
          if (m) nb_arrive(kNbOrder + 1, 256);
          wg_wait<1>();
          if (!m) mbar_arrive_cluster_if(empty + 8 * 4, (t2 & 31) < 2);
        }
#pragma unroll
        for (int b = 0; b < 4; b++) {
          if (b == 1) {
            wg_wait<0>();
            if (t2 == 0) TSK(7);
          }
          if (b < 2) {
#pragma unroll
            for (int i = 0; i < 64; i++) asm volatile("" : "+f"(acc[b][i])::"memory");
          }
          stage_quarter(&acc[b & 1][32 * (b >> 1)], frag2, frag2_x, b);
          if (b & 1) {
            fence_async_smem();
            __syncwarp();
            if (elect_one()) {
              mbar_arrive(sb + kBars + 8 * (kHalfBar + (b >> 1)));
#pragma unroll
              for (int m = 0; m < 2; m++)
                if (b == 1) tma_store2d(&p.h16, sb + kStage + m * 8192 + warp * 2048, c * 128, r * 128 + m * 64 + warp * 16);
            }
            __syncwarp();
          }
        }
        if (t2 == 0) TS(8);
        sx = mx = 0.f;
        continue;
      }
      float acc[2][96];
      if (task == 8 + wg) {
        wg_fence();
#pragma unroll
        for (int m = 0; m < 2; m++) wgmma_n192_any(acc[m], desc(64 + m), desc(64 + m));
        wg_commit();
        wg_wait<0>();
#pragma unroll
        for (int i = 0; i < 96; i++) asm volatile("" : "+f"(acc[0][i]), "+f"(acc[1][i])::"memory");
      } else {
        const uint32_t z = fresh_tid() >> 10;
#pragma unroll
        for (int i = 0; i < 96; i++) {
#pragma unroll
          for (int m = 0; m < 2; m++) {
            if ((2 * i + m) % kInitMix == kInitMix - 1) asm("fma.rn.f32 %0, %1, %2, %3;" : "=f"(acc[m][i]) : "f"(__uint_as_float(z)), "f"(2 * i + m + 2.f), "f"(bias));
            else asm("{\n.reg .b32 t;\nlop3.b32 t, %1, %2, %3, 0xEA;\nmov.b32 %0, t;\n}\n" : "=f"(acc[m][i]) : "r"(z), "r"(2 * i + m + 1), "r"(__float_as_uint(bias)));
          }
        }
      }
      if (task > 5) {
      if (wg) {
        if (task == 7) cluster_wait();
        if (tid == 128 && task == 7) { TSS(5); TSK(69); }
        const int t = fresh_tid() & 127, lr = c * 16 + (t >> 3);
        uint32_t pf = t < 64 ? (bid * 16 + (t >> 2)) * kD + (t & 3) * 64 : (r * 48 + t - 64) * kD + c * 64;
        const uint32_t src = sb + kRing + lr * 128 + (((t ^ lr) & 7) << 4), empty = map_cta(sb + kBars + 8 * 4, t & 1), zero = fresh_tid() >> 10;
#pragma unroll 1
        for (int j = task == 7 ? 0 : kSplit; j < (task == 7 ? kSplit : 16); j++) {
          mbar_wait(sb + kBars + 8 * (j & 3), (j >> 2) & 1);
          if (j < 2 && t == 0) TS(102 + j);
          const uint4 v = lds128(src + (j >> 1 == c ? kOwn + (j & 1) * 16384 : (j & 3) * 40960));
          __syncwarp();
          mbar_arrive_cluster_if(empty + 8 * (j & 3) + (v.x & zero), (t & 31) < 2);
          if ((j == 0 || j == 3 || j == 6) && t < 112) { pf += t < 64 ? 256 : 256 * 3 * kD; prefetch_l2((t < 64 ? xp : wqkvp) + pf); }
          const uint32_t u[4] = {v.x, v.y, v.z, v.w};
#pragma unroll
          for (int e = 0; e < 4; e++) {
            const float d0 = bf_lo(u[e]), d1 = bf_hi(u[e]);
            sx += d0 + d1;
            mx = fmaf(d1, d1, fmaf(d0, d0, mx));
          }
        }
        if (task == 7) {
          if (t == 0) TS(96);
          continue;
        }
#pragma unroll
        for (int o = 4; o > 0; o >>= 1) { sx += __shfl_xor_sync(~0u, sx, o); mx += __shfl_xor_sync(~0u, mx, o); }
        const float mean = sx * (1.f / kD);
        float rstd;
        asm("rsqrt.approx.ftz.f32 %0, %1;" : "=f"(rstd) : "f"(fmaxf(mx * (1.f / kD) - mean * mean, 0.f) + 1e-5f));
        const uint32_t ep = lds32(sb + kEpoch);
        const int t2 = fresh_tid();
        if ((t2 & 7) == 0) st_b128(sc->stat1 + (bid * 16 + (t2 >> 3 & 15)), __float_as_uint(rstd), __float_as_uint(-mean), ep, ep);
        if (t == 0) TS(16);
      }
      if (tid == 0) TSS(6);
      mainloop<192, -1>(sc, acc, sb, 0, wg * 16, wg ? 16 - kAhead : 16, wg ? kPauseG1 : -2, false, wg == 0, false, wg,
                        wg ? min((c + 2) & 7, 6) : c);
      const int t = fresh_tid() & 127, w = warp & 3, lane = t & 31, g = lane >> 2, q = lane & 3;
      const uint32_t stg = sb + kStage + wg * 32768;
      auto tail = [&](int m, int k0, int k1) {
        wg_fence();
#pragma unroll
        for (int k = k0; k < k1; k++) {
          const uint64_t a = desc_kept(desc_lo(sb + kRing, 16), sb) + (4 - kAhead + (k >> 2)) * (40960 >> 4);
          wgmma_n192(acc[m], a + (m * 512 + (k & 3) * 2), a + (kToB + (k & 3) * 128));
        }
      };
      auto release = [&](int j, bool cond) { mbar_arrive_cluster_if(map_cta(sb + kBars + 8 * (4 + (j & 3)), lane & 1), cond); };
      if (wg) {
#pragma unroll
        for (int j = 32 - kAhead; j < 32; j++) {
          TST(2 * (j & 1));
          mbar_wait(sb + kBars + 8 * (j & 3), 1);
          TST(2 * (j & 1) + 1);
          tail(1, 4 * (j - 32 + kAhead), 4 * (j - 31 + kAhead));
          wg_commit();
          if (j == 32 - kAhead) {
            wg_wait<1>();
            release(j - 1, lane < 4);
            mbar_wait(sb + kBars + 8 * kResFreeBar, 0);
          }
        }
      } else {
        nb_arrive(kNbOrder + 1, 256);
        wg_wait<0>();
        release(15, lane < 2);
        if (t == 0) TSK(1);
      }
      TST(4);
      mbar_wait(sb + kBars + 8 * (kAuxBar + wg), 0);
      mbar_wait(sb + kBars + 8 * kStatBar, 0);
      {
        uint32_t am[4];
#pragma unroll
        for (int i = 0; i < 4; i++) {
          const float m1 = __uint_as_float(lds32(sb + kStat + (w * 16 + g) * 8 + 4 + (i >> 1) * 512 + (i & 1) * 64));
          const float m2 = bf_rest(m1), lo = q & 1 ? m2 : m1;
          am[i] = bf_upper(lo, q == 3 ? -bias : q == 2 ? bf_rest(m2) : lo);
        }
        const uint64_t db = (uint64_t)desc_lo(sb + kAug + wg * 4096, 1024) | (0x40000000ull << 32);
        TST(5);
        wg_fence();
        wgmma_n192_rs(acc[1], am[2], am[3], 0u, db);
        wg_commit();
        TST(6);
        if (wg) {
          wg_fence();
          wgmma_n192_rs(acc[0], am[0], am[1], 0u, db);
          tail(0, 0, 4 * kAhead);
          wg_commit();
        } else {
          wg_fence();
          wgmma_n192_rs(acc[0], am[0], am[1], 0u, db);
          wg_commit();
          asm volatile("" ::: "memory");
        }
        TST(7);
        wg_wait<1>();
        TST(8);
#pragma unroll
        for (int i = 0; i < 96; i++) asm volatile("" : "+f"(acc[1][i])::"memory");
      }
      const uint32_t ep = lds32(sb + kEpoch);
      uint32_t pk[2][48];
      auto fold = [&](int pp, int jn, int hf) {
        const uint32_t v = pack_bf16(acc[pp][4 * jn + 2 * hf], acc[pp][4 * jn + 2 * hf + 1]);
        pk[pp][2 * jn + hf] = jn >= 16 ? movm(v) : v;
      };
      if (t == 96) TS(115 + wg);
#pragma unroll
      for (int jn = 8; jn < 24; jn++) fold(1, jn, 1);
      if (w < 3) {
#pragma unroll
        for (int i = 0; i < 4; i++)
          sts128(stg + (w + 5) * 2048 + i * 512 + lane * 16, make_uint4(pk[1][17 + 8 * i], pk[1][19 + 8 * i], pk[1][21 + 8 * i], pk[1][23 + 8 * i]));
      } else if (r < 14) {
        uint4* gh = sc->halo + ((wg * 16 + r) * 8 + c) * 192 + lane;
#pragma unroll
        for (int i = 0; i < 6; i++) st_b128(gh + i * 32, pk[1][17 + 6 * i], i < 5 ? pk[1][(19 + 6 * i) % 48] : ep, i < 5 ? pk[1][(21 + 6 * i) % 48] : ep, ep);
        if (wg == 0) {
#pragma unroll 1
          for (int i = 0; i < 6; i++, gh += 32) st_b128(gh + 128 * 192, 0, 0, 0, ep - 1);
        }
      }
      if (w == 3) nb_arrive(kNbHalo, 64);
      if (wg) nb_arrive(kNbOrder, 256);
      TST(9);
      if (t == 96) TS(111 + wg);
#pragma unroll
      for (int jn = 23; jn >= 0; jn--) {
        fold(1, jn, 0);
        if (jn < 8) fold(1, jn, 1);
      }
      const bool sel0 = 2 * q > g, sel1 = 2 * q + 1 > g, no_prev = (r < 2 && w == 0);
      const uint4 ones = lds128(sb + kOnes);
      const uint32_t lowmask = (sel0 ? 0x0000FFFFu : 0u) | (sel1 ? 0xFFFF0000u : 0u) | ones.y;
      float rs[4][2], rk[4][2];
#pragma unroll
      for (int i = 0; i < 4; i++) {
        const uint32_t a = sb + kStat + w * 128 + (i >> 1) * 512 + (i & 1) * 64;
        const float rq = __uint_as_float(lds32(a + g * 8)) * (0.17677669529663687f * 1.4426950408889634f);
        rk[i][0] = __uint_as_float(lds32(a + q * 16 - (sel0 ? 64 : 0)));
        rk[i][1] = __uint_as_float(lds32(a + q * 16 + 8 - (sel1 ? 64 : 0)));
        rs[i][0] = rk[i][0] * rq;
        rs[i][1] = rk[i][1] * rq;
      }
      {
        uint32_t all = ~0u;
#pragma unroll
        for (int i = 0; i < 48; i++) if (i < 16 || !(i & 1)) all &= pk[1][i];
        if (all == kPoison) sts32(sb + kZero + 8, 0);
      }
      TST(10);
      wg_wait<0>();
      TST(11);
#pragma unroll
      for (int j = 32 - kAhead; j < 32; j++) release(j, lane < 4 * wg && (w != 0 || j < 31));
#pragma unroll
      for (int i = 0; i < 96; i++) asm volatile("" : "+f"(acc[0][i])::"memory");
      if (t == 0 && wg) TSK(21);
#pragma unroll
      for (int jn = 8; jn < 24; jn++) fold(0, jn, 1);
#pragma unroll
      for (int i = 0; i < 4; i++)
        sts128(stg + (w + 1) * 2048 + i * 512 + lane * 16, make_uint4(pk[0][17 + 8 * i], pk[0][19 + 8 * i], pk[0][21 + 8 * i], pk[0][23 + 8 * i]));
#pragma unroll
      for (int jn = 23; jn >= 0; jn--) {
        fold(0, jn, 0);
        if (jn < 8) fold(0, jn, 1);
      }
      if (t == 0) TS(113 + wg);
      nb_sync(kNbWg + wg, 128);
      uint32_t hal[2][16];
      auto load_halo = [&](int m) {
#pragma unroll
        for (int i = 0; i < 4; i++) {
          const uint4 v = lds128(stg + w * 2048 + m * 8192 + i * 512 + lane * 16);
          uint32_t* h = &hal[m][i * 4];
          h[0] = v.x; h[1] = v.y; h[2] = v.z; h[3] = v.w;
        }
      };
      load_halo(1);
      if (w == 0) {
        nb_sync(kNbHalo + 1, 64);
        release(31, lane < 4 * wg);
      }
      load_halo(0);
      __syncwarp();
      if (t == 0) TS(2 + wg * 20);
      {
        uint32_t all = lowmask;
#pragma unroll
        for (int i = 0; i < 32; i++) if (i < 16 || !(i & 1)) all &= pk[0][i];
#pragma unroll
        for (int i = 0; i < 8; i++) all &= __float_as_uint(rs[i >> 1][i & 1]);
        if (all == kPoison) sts32(sb + kZero + 8, 0);
      }
      nb_sync(kNbWin, 256);
      if (t == 0) TS(9 + wg * 20);
      const uint32_t zero = lds32(sb + kZero);
      float s0[4][4], s1[4][4], s2[4][4];
#pragma unroll
      for (int k = 0; k < 4; k++) {
        pk[k >> 1][8 * (k & 1)] |= zero;
#pragma unroll
        for (int e = 0; e < 4; e++) s0[k][e] = s1[k][e] = s2[k][e] = 0.f;
      }
#pragma unroll
      for (int ks = 0; ks < 2; ks++)
#pragma unroll
        for (int k = 0; k < 4; k++) {
          const uint32_t* qf = &pk[k >> 1][8 * (k & 1) + 4 * ks];
          const uint32_t* kf = &pk[k >> 1][16 + 8 * (k & 1) + 4 * ks];
          const uint32_t* hf = &hal[k >> 1][4 * (k & 1) + 2 * ks];
          mma16816(s0[k], qf[0], qf[1], qf[2], qf[3], hf[0], hf[1]);
          mma16816(s1[k], qf[0], qf[1], qf[2], qf[3], kf[0], kf[2]);
          mma16816(s2[k], qf[0], qf[1], qf[2], qf[3], kf[1], kf[3]);
        }
      float ea[4][2], eb[4][2], ma[4], mb[4];
#pragma unroll
      for (int k = 0; k < 4; k++) {
        const float *ra = rs[k & 2], *rb = rs[(k & 2) + 1];
        if (no_prev && k < 2) s0[k][0] = s0[k][1] = -INFINITY;
        ea[k][0] = (sel0 ? s0[k][0] : s1[k][0]) * ra[0]; ea[k][1] = (sel1 ? s0[k][1] : s1[k][1]) * ra[1];
        eb[k][0] = (sel0 ? s1[k][2] : s2[k][2]) * rb[0]; eb[k][1] = (sel1 ? s1[k][3] : s2[k][3]) * rb[1];
        ma[k] = fmaxf(ea[k][0], ea[k][1]); mb[k] = fmaxf(eb[k][0], eb[k][1]);
      }
#pragma unroll
      for (int o = 1; o < 4; o <<= 1)
#pragma unroll
        for (int k = 0; k < 4; k++) {
          ma[k] = fmaxf(ma[k], __shfl_xor_sync(~0u, ma[k], o));
          mb[k] = fmaxf(mb[k], __shfl_xor_sync(~0u, mb[k], o));
        }
      float ov[4][4][4], ls[4][4];
      uint32_t all = 0;
#pragma unroll
      for (int k = 0; k < 4; k++) {
        const float *ra = rk[k & 2], *rb = rk[(k & 2) + 1];
        ea[k][0] = ex2(ea[k][0] - ma[k]); ea[k][1] = ex2(ea[k][1] - ma[k]);
        eb[k][0] = ex2(eb[k][0] - mb[k]); eb[k][1] = ex2(eb[k][1] - mb[k]);
        const uint32_t pa = pack_bf16(ea[k][0] * ra[0], ea[k][1] * ra[1]), pb = pack_bf16(eb[k][0] * rb[0], eb[k][1] * rb[1]);
        const uint32_t* vf = &pk[k >> 1][32 + 8 * (k & 1)];
        const uint32_t* hf = &hal[k >> 1][8 + 4 * (k & 1)];
#pragma unroll
        for (int d2 = 0; d2 < 2; d2++) {
#pragma unroll
          for (int e = 0; e < 4; e++) ov[k][d2][e] = ov[k][2 + d2][e] = 0.f;
          mma1688(ov[k][d2], hf[2 * d2], hf[2 * d2 + 1], pa & lowmask);
          mma1688(ov[k][2 + d2], vf[4 * d2], vf[4 * d2 + 2], pb & lowmask);
        }
#pragma unroll
        for (int d2 = 0; d2 < 2; d2++) {
          mma1688(ov[k][d2], vf[4 * d2], vf[4 * d2 + 2], pa & ~lowmask);
          mma1688(ov[k][2 + d2], vf[4 * d2 + 1], vf[4 * d2 + 3], pb & ~lowmask);
        }
        ls[k][0] = ls[k][1] = ls[k][2] = ls[k][3] = 0.f;
        mma16816(ls[k], ones.x, ones.y, ones.z, ones.w, pack_bf16(ea[k][0], ea[k][1]), pack_bf16(eb[k][0], eb[k][1]));
        if (k >= kDone) all |= pa & pb;
      }
#pragma unroll
      for (int k = 0; k < 4; k++) {
        if (k == kDone) {
          if (all == 0xFFFFFFFFu) sts32(sb + kZero + 8, 0);
          nb_arrive(kNbWin + 1, 256);
          all = 0;
        }
        all |= (__float_as_uint(ov[k][0][0]) & __float_as_uint(ov[k][1][0]) & __float_as_uint(ov[k][2][0])) &
               (__float_as_uint(ov[k][3][0]) & __float_as_uint(ls[k][0]));
      }
      const uint32_t nil = lds32(sb + kZero);
      const uint32_t frag = stg + (w * 16 + (lane & 15)) * 128, frag_x = (lane >> 4) ^ (lane & 7);
      uint32_t after = all;
#pragma unroll
      for (int k = 0; k < 4; k++) {
        uint32_t h[2][4];
#pragma unroll
        for (int hf = 0; hf < 2; hf++) {
          const float i0 = rcp(__uint_as_float(__float_as_uint(ls[k][2 * hf]) | (after & nil)));
          const float i1 = rcp(__uint_as_float(__float_as_uint(ls[k][2 * hf + 1]) | (after & nil)));
#pragma unroll
          for (int e = 0; e < 4; e++) h[e >> 1][2 * (e & 1) + hf] = pack_bf16(ov[k][2 * hf + (e >> 1)][2 * (e & 1)] * i0, ov[k][2 * hf + (e >> 1)][2 * (e & 1) + 1] * i1);
          after = h[0][hf];
        }
#pragma unroll
        for (int d2 = 0; d2 < 2; d2++) stsm4_t(frag + (k >> 1) * 8192 + ((frag_x ^ ((k & 1) * 4 + d2 * 2)) << 4), h[d2][0], h[d2][1], h[d2][2], h[d2][3]);
      }
      fence_async_smem();
      if (wg) {
        __syncwarp();
        if (elect_one()) {
          tma_store2d(&p.o16, stg + w * 2048, (8 + c) * 64, r * 128 + w * 16);
          tma_store2d(&p.o16, stg + 8192 + w * 2048, (8 + c) * 64, r * 128 + 64 + w * 16);
          bulk_commit();
          bulk_wait_read();
          mbar_arrive(sb + kBars + 8 * kSentBar);
        }
        __syncwarp();
      } else {
        nb_arrive(kNbPub, 160);
      }
      if (t == 0) TS(3 + wg * 20);
      task = wg;
      sx = mx = 0.f;
      continue;
      }

      {
#pragma unroll 1
        for (int part = task != 2; part < 2; part++) {
          if ((tid & 127) == 0) TS(6 + 2 * task + wg * 20);
          if (task + part == 5) {
            mainloop<128, 0>(sc, acc, sb, 3, 0, 16, -2, false, true, false, 1);
            continue;
          }
          const int j0 = task == 3 ? 48 - wg * 16 : part == 0 ? 2 - 2 * wg : 18 - 14 * wg;
          mainloop<192, 0>(sc, acc, sb, 2, j0, task != 2 ? 16 : part == 0 ? 2 : 14, -2, false, true, part == 0, wg);
          if (part == 0 && wg == 0) {
            const int t = fresh_tid() & 127;
            const uint32_t ep = lds32(sb + kEpoch);
            {
              float s = 0.f, ss = 0.f;
#pragma unroll 1
              for (int i = 0; i < 16; i++) {
                const uint4 v = lds128(sb + kStage + t * 128 + (i >> 3) * 16384 + (((i ^ t) & 7) << 4));
                const uint32_t u[4] = {v.x, v.y, v.z, v.w};
#pragma unroll
                for (int e = 0; e < 4; e++) {
                  const float d0 = bf_lo(u[e]), d1 = bf_hi(u[e]);
                  s = (s + d0) + d1;
                  ss = fmaf(d1, d1, fmaf(d0, d0, ss));
                }
              }
              st_b128(sc->stat2 + c * kS + r * 128 + t, __float_as_uint(s), __float_as_uint(ss), ep, ep);
            }
            __nanosleep(kStatNs);
            float2 sum = make_float2(0.f, 0.f);
#pragma unroll 1
            for (int i = 0; i < 2; i++) {
              uint3 a[4];
              load_tagged<4, true>(a, sc->stat2 + i * 4 * kS + r * 128 + t, kS, ep);
              sum.x += (__uint_as_float(a[0].x) + __uint_as_float(a[1].x)) + (__uint_as_float(a[2].x) + __uint_as_float(a[3].x));
              sum.y += (__uint_as_float(a[0].y) + __uint_as_float(a[1].y)) + (__uint_as_float(a[2].y) + __uint_as_float(a[3].y));
            }
            const float mean = sum.x * (1.f / kD);
            sts64f(sb + kStat + t * 8, make_float2(fmaxf(sum.y * (1.f / kD) - mean * mean, 0.f) + 1e-5f, -mean));
            __syncwarp();
            if (elect_one()) {
              bulk_commit();
              bulk_wait_read();
              mbar_arrive(sb + kBars + 8 * kStatBar);
            }
            __syncwarp();
            if (t == 0) TS(37);
          }
        }
      }
      const int t = fresh_tid() & 127, w = warp & 3, lane = t & 31, g = lane >> 2, q = lane & 3;
      const uint32_t stg = sb + kStage + wg * 32768;
      uint32_t csv = sb + kCs + wg * 768 + q * 8;
      uint32_t statv = sb + kStat + (w * 16 + g) * 8;
      const uint32_t frag = stg + (w * 16 + (lane & 15)) * 128;
      const uint32_t frag_x = (lane >> 4) ^ (lane & 7);
      const uint32_t priv = stg + w * 2048 + lane * 16;
      if (t == 0) TSK(7 + 2 * task + wg * 20);

      if (task == 4) {
        mbar_wait(sb + kBars + 8 * (kAuxBar + 1), 1);
        mbar_wait(sb + kBars + 8 * kResFreeBar, 1);
        mbar_wait(sb + kBars + 8 * (kStgBar + 1), 0);
      }
      asm volatile("" : "+r"(csv), "+r"(statv)::"memory");

      {
#pragma unroll
        for (int i = 0; i < 96; i++) asm volatile("sub.f32 %0, %0, %1;" : "+f"(acc[0][i]) : "f"(bias));
#define NEXT(i) asm volatile("sub.f32 %0, %1, %2;" : "=f"(acc[0][i]) : "f"(acc[1][i]), "f"(bias))
#pragma unroll 1
        for (int pp = 0; pp < 2; pp++) {
          TSG(pp);
          RowConst rc[2];
#pragma unroll
          for (int hf = 0; hf < 2; hf++) {
            const float2 st = lds64f_const(statv + pp * 512 + hf * 64);
            float rstd;
            asm("rsqrt.approx.ftz.f32 %0, %1;" : "=f"(rstd) : "f"(st.x));
            rc[hf] = {st.y, 0.7978845608f * rstd, 0.0356774081f * rstd * rstd * rstd, 0.5f * rstd * rstd};
          }
#pragma unroll
          for (int j2 = 0; j2 < 4; j2++) {
            uint32_t hv[4];
#pragma unroll
            for (int jj = 0; jj < 2; jj++) {
              const int jn = 2 * j2 + jj;
              const float2 cg = lds64f_const(csv + jn * 32), cu = lds64f_const(csv + 256 + jn * 32);
#pragma unroll
              for (int hf = 0; hf < 2; hf++) {
                const float nm = rc[hf].nmean;
                const float g0 = fmaf(nm, cg.x, acc[0][4 * jn + 2 * hf]), g1 = fmaf(nm, cg.y, acc[0][4 * jn + 2 * hf + 1]);
                const float u0 = fmaf(nm, cu.x, acc[0][32 + 4 * jn + 2 * hf]), u1 = fmaf(nm, cu.y, acc[0][33 + 4 * jn + 2 * hf]);
                hv[2 * jj + hf] = pack_bf16(g0 * u0 * gate_scale(g0, rc[hf]), g1 * u1 * gate_scale(g1, rc[hf]));
              }
            }
            stsm4(frag + 16384 + pp * 8192 + ((frag_x ^ (j2 * 2)) << 4), hv[0], hv[1], hv[2], hv[3]);
          }
          if (task < 4) {
            if (task == 2) {
#pragma unroll
              for (int j2 = 0; j2 < 4; j2++) {
                uint32_t hv[4];
#pragma unroll
                for (int jj = 0; jj < 2; jj++) {
                  const int jn = 16 + 2 * j2 + jj;
                  const float2 cs = lds64f_const(csv + jn * 32);
#pragma unroll
                  for (int hf = 0; hf < 2; hf++) {
                    const float nm = rc[hf].nmean;
                    const float t0 = fmaf(nm, cs.x, acc[0][4 * jn + 2 * hf]), t1 = fmaf(nm, cs.y, acc[0][4 * jn + 2 * hf + 1]);
                    hv[2 * jj + hf] = pack_bf16(t0 * gate_scale(t0, rc[hf]), t1 * gate_scale(t1, rc[hf]));
                  }
                }
                sts128(priv + pp * 8192 + j2 * 512, make_uint4(hv[0], hv[1], hv[2], hv[3]));
              }
            } else {
              uint4 park[4];
#pragma unroll
              for (int j2 = 0; j2 < 4; j2++) park[j2] = lds128(priv + pp * 8192 + j2 * 512);
              __syncwarp();
#pragma unroll
              for (int j2 = 0; j2 < 4; j2++) {
                const uint32_t pv[4] = {park[j2].x, park[j2].y, park[j2].z, park[j2].w};
                uint32_t hv[4];
#pragma unroll
                for (int jj = 0; jj < 2; jj++) {
                  const int jn = 16 + 2 * j2 + jj;
                  const float2 cs = lds64f_const(csv + jn * 32);
#pragma unroll
                  for (int hf = 0; hf < 2; hf++) {
                    const float nm = rc[hf].nmean;
                    const float t0 = fmaf(nm, cs.x, acc[0][4 * jn + 2 * hf]), t1 = fmaf(nm, cs.y, acc[0][4 * jn + 2 * hf + 1]);
                    asm("mul.rn.bf16x2 %0, %1, %2;" : "=r"(hv[2 * jj + hf]) : "r"(pack_bf16(t0, t1)), "r"(pv[2 * jj + hf]));
                  }
                }
                stsm4(frag + pp * 8192 + ((frag_x ^ (j2 * 2)) << 4), hv[0], hv[1], hv[2], hv[3]);
              }
            }
            if (pp == 1) break;
#pragma unroll
            for (int i = 64; i < 96; i++) NEXT(i);
          }
          if (pp == 1) break;
#pragma unroll
          for (int i = 0; i < 64; i++) NEXT(i);
        }
      }
      fence_async_smem();
      nb_arrive(kNbPub + wg, 160);
      if (t == 0) TS(task == 4 ? 57 : 56 + task + wg * 2);
      if (task == 4) break;
      sx = mx = 0.f;
    }
  }
}

typedef CUresult (*EncodeTiledFn)(CUtensorMap*, CUtensorMapDataType, cuuint32_t, void*, const cuuint64_t*, const cuuint64_t*,
                                  const cuuint32_t*, const cuuint32_t*, CUtensorMapInterleave, CUtensorMapSwizzle,
                                  CUtensorMapL2promotion, CUtensorMapFloatOOBfill);

void encode(EncodeTiledFn fn, CUtensorMap* m, const void* base, int rank, cuuint64_t d0, cuuint64_t d1, cuuint64_t d2,
            cuuint64_t s1, cuuint64_t s2, cuuint32_t b2, cuuint32_t b1 = 64) {
  const cuuint64_t dims[3] = {d0, d1, d2}, strides[2] = {s1, s2};
  const cuuint32_t box[3] = {64, b1, b2}, es[3] = {1, 1, 1};
  fn(m, CU_TENSOR_MAP_DATA_TYPE_BFLOAT16, rank, const_cast<void*>(base), dims, strides, box, es, CU_TENSOR_MAP_INTERLEAVE_NONE,
     CU_TENSOR_MAP_SWIZZLE_128B, CU_TENSOR_MAP_L2_PROMOTION_L2_128B, CU_TENSOR_MAP_FLOAT_OOB_FILL_NONE);
}

}

extern "C" void kernel_launch(void* const* d_in, const int* in_sizes, int n_in, void* d_out, int out_size) {
  void* fnp = nullptr;
  cudaDriverEntryPointQueryResult qr;
  cudaGetDriverEntryPoint("cuTensorMapEncodeTiled", &fnp, cudaEnableDefault, &qr);
  EncodeTiledFn fn = (EncodeTiledFn)fnp;
  void *o, *h, *hh;
  cudaGetSymbolAddress(&o, g_o);
  cudaGetSymbolAddress(&h, g_h);
  cudaGetSymbolAddress(&hh, g_hh);

  Params p;
  Scratch* sc;
  cudaGetSymbolAddress((void**)&sc, g_scratch);
  encode(fn, &p.x, d_in[0], 3, kD, kS / 2, 2, 4 * kD, 2 * kD, 1, 128);
  encode(fn, &p.out, d_out, 3, kD, kS / 2, 2, 4 * kD, 2 * kD, 1, 16);
  encode(fn, &p.wqkv, d_in[1], 2, 3 * kD, kD, 1, 6 * kD, 0, 1);
  encode(fn, &p.wo, d_in[2], 2, kD, kD, 1, 2 * kD, 0, 1);
  encode(fn, &p.wd, d_in[6], 2, kD, kF, 1, 2 * kD, 0, 1);
  encode(fn, &p.wg, d_in[4], 2, kF, kD, 1, 2 * kF, 0, 1);
  encode(fn, &p.wu, d_in[5], 2, kF, kD, 1, 2 * kF, 0, 1);
  encode(fn, &p.o, o, 2, kD, kS, 1, 2 * kD, 0, 1, 128);
  encode(fn, &p.h, h, 2, kD, kS, 1, 2 * kD, 0, 1, 128);
  encode(fn, &p.hh, hh, 2, kF, kS, 1, 2 * kF, 0, 1, 128);
  encode(fn, &p.ost, o, 2, kD, kS, 1, 2 * kD, 0, 1);
  encode(fn, &p.o16, o, 2, kD, kS, 1, 2 * kD, 0, 1, 16);
  encode(fn, &p.h16, h, 2, kD, kS, 1, 2 * kD, 0, 1, 16);
  encode(fn, &p.hst, h, 2, kD, kS, 1, 2 * kD, 0, 1);
  encode(fn, &p.hhst, hh, 2, kF, kS, 1, 2 * kF, 0, 1);
  p.wop = (const uint4*)d_in[2];
  p.wgp = (const uint4*)d_in[4];
  p.wup = (const uint4*)d_in[5];

  int dev = 0, sms = 0;
  cudaGetDevice(&dev);
  cudaDeviceGetAttribute(&sms, cudaDevAttrMultiProcessorCount, dev);
  auto* kernel = sms == 132 ? fused_block_kernel<true> : fused_block_kernel<false>;
  cudaFuncSetAttribute(kernel, cudaFuncAttributeMaxDynamicSharedMemorySize, kSmemBytes);
  kernel<<<132, kThreads, kSmemBytes, cudaStreamPerThread>>>(sc, (const __nv_bfloat16*)d_in[0], (const __nv_bfloat16*)d_in[1],
                                                                  (__nv_bfloat16*)d_out, p);
}
```

```cpp
#include <cuda_runtime.h>
#include <cuda_bf16.h>
#include <cuda.h>
#include <stdint.h>

namespace {

constexpr int kS = 2048, kD = 1024, kF = 3584;
constexpr int kThreads = 384;

constexpr int kRing = 0;
constexpr int kStage = 163840;
constexpr int kAug = kStage + 16384;
constexpr int kOwn = kStage + 32768;
constexpr int kFill = kStage + 24576;
constexpr int kCs = kStage + 65536;
constexpr int kStat = kCs + 1536;
constexpr int kBars = kStat + 1024;
constexpr int kSmemBytes = kBars + 512;
constexpr int kResBar = 36;
constexpr int kAuxBar = 37;
constexpr int kStgBar = 39;
constexpr int kResFreeBar = 41;
constexpr int kStatBar = 42;
constexpr int kPartBar = 43;
constexpr int kWaveBar = 45;
constexpr int kHalfBar = 49;
constexpr int kSentBar = 51;
constexpr int kLandBar = 52;
constexpr int kNumBars = 58;
static_assert(kNumBars == 4 + 3 * 18, "barrier initialisation is split 4 + 3 x 18");
__host__ __device__ constexpr int bar_count(int i) {
  const int ph = i < 8 ? 0 : i < 18 ? 1 : i < 26 ? 2 : 3, base = ph * 9 - (ph & 1);
  return i < 36 ? (i - base < 4 + (ph & 1) ? 2 : ph == 0 ? 16 : 8) : i == kResFreeBar || i == kStatBar || (i >= kHalfBar && i < kLandBar) ? 4 : 1;
}
__host__ __device__ constexpr uint64_t bar_shifts(int first) {
  uint64_t m = 0;
  for (int i = 17; i >= 0; i--) {
    const int n = bar_count(first + i);
    m = m << 3 | (n == 16 ? 4 : n == 8 ? 3 : n >> 1);
  }
  return m;
}
constexpr int kScale = kBars + 464;
constexpr int kOnes = kBars + 480;
constexpr int kZero = kBars + 496;
constexpr int kRole = kBars + 508;
constexpr int kEpoch = kBars + 500;
__device__ __forceinline__ int ring_base(int ph) { return ph * 9 - (ph & 1); }
constexpr int kNbOrder = 1;
constexpr int kNbWg = 3;
constexpr int kNbPub = 5;
constexpr int kNbWin = 7;
constexpr int kNbSelf = 13;
constexpr int kNbHalo = 9;

constexpr int kFlO = 0;
constexpr int kFlPace = 1;
constexpr int kFlHH = 3;
constexpr int kFlPart = 8;
constexpr int kFlRow = 32;
constexpr int kNumFlags = 16 * kFlRow;

constexpr int kPauseG1 = 7;
constexpr int kPauseG2 = 1;
constexpr int kAhead = 2;
constexpr int kTail = 5;
constexpr int kDone = 3;
constexpr int kQuietAt = 48;
constexpr int kPfStep = 8;
constexpr int kBackoffNs = 200;
constexpr int kPaceNs = 300;
constexpr int kPartNs = 150;
constexpr int kFillNs = 500;
constexpr int kHaloNs = 150;
constexpr int kGateONs = 150;
constexpr int kGateHNs = 150;
constexpr int kHoldNs = 1200;
constexpr float kBias1 = 512.f, kBias3 = 32768.f;
constexpr int kInitMix = 1000;
constexpr int kSplit = 13;
constexpr int kSampleNs = 1000;
constexpr int kStatNs = 1500;

struct Scratch {
  uint32_t flags[kNumFlags];
  uint32_t epoch[32];
  uint4 stat1[kS];
  uint4 stat2[8 * kS];
  uint4 cs[7 * 8 * 96];
  uint4 halo[2 * 16 * 8 * 6 * 32];
  uint4 part[128 * 8 * 128];
};
struct Params {
  CUtensorMap x, wqkv, o, wo, h, wg, wu, hh, wd, out;
  CUtensorMap ost, hst, hhst;
  CUtensorMap o16, h16;
  const uint4 *wop, *wgp, *wup;
};

__device__ __align__(256) __nv_bfloat16 g_o[kS * kD];
__device__ __align__(256) __nv_bfloat16 g_h[kS * kD];
__device__ __align__(256) __nv_bfloat16 g_hh[kS * kF];
__device__ __align__(256) Scratch g_scratch;

template <bool BY_SM>
__device__ __forceinline__ int role_id() {
  uint32_t sm;
  asm("mov.u32 %0, %%smid;" : "=r"(sm));
  const int tpc = (BY_SM ? sm : blockIdx.x) >> 1, rank = blockIdx.x & 1;
  if ((tpc | 1) == 61) return 8 + 2 * tpc + rank;
  const int u = tpc - 32, s7 = (u * 37) >> 8;
  const int g = tpc < 32 ? tpc & 7 : tpc < 60 ? 1 + u - 7 * s7 : 0, s = tpc < 32 ? tpc >> 3 : tpc < 60 ? 4 + s7 : tpc - 58;
  return (g * 2 + rank) * 8 + s;
}
#define TS(i) do { } while (0)
#define TSK(i) do { } while (0)
#define TSS(i) do { } while (0)
#define TST(i)
#define TSG(i)

__device__ __forceinline__ uint32_t smem_u32(const void* p) { return (uint32_t)__cvta_generic_to_shared(p); }
__device__ __forceinline__ void mbar_init(uint32_t bar, uint32_t cnt) {
  asm volatile("mbarrier.init.shared::cta.b64 [%0], %1;" ::"r"(bar), "r"(cnt));
}
__device__ __forceinline__ void mbar_expect_tx(uint32_t bar, uint32_t bytes) {
  asm volatile("mbarrier.arrive.expect_tx.shared::cta.b64 _, [%0], %1;" ::"r"(bar), "r"(bytes) : "memory");
}
__device__ __forceinline__ uint32_t map_cta(uint32_t addr, uint32_t cta) {
  uint32_t r;
  asm("mapa.shared::cluster.u32 %0, %1, %2;" : "=r"(r) : "r"(addr), "r"(cta));
  return r;
}
__device__ __forceinline__ void mbar_arrive_cluster_if(uint32_t bar, bool cond) {
  asm volatile("{\n.reg .pred p;\nsetp.ne.u32 p, %1, 0;\n@p mbarrier.arrive.shared::cluster.b64 _, [%0];\n}\n"
               ::"r"(bar), "r"((uint32_t)cond) : "memory");
}
__device__ __forceinline__ void mbar_wait(uint32_t bar, uint32_t parity) {
  asm volatile("{\n.reg .pred p;\nLAB_WAIT:\nmbarrier.try_wait.parity.shared::cta.b64 p, [%0], %1;\n@!p bra LAB_WAIT;\n}\n"
               ::"r"(bar), "r"(parity) : "memory");
  return;
  asm volatile("{\n.reg .pred p;\n.reg .u32 c;\nmov.u32 c, 0;\n"
               "LAB_WAIT:\nmbarrier.try_wait.parity.shared::cta.b64 p, [%0], %1;\n@p bra LAB_DONE;\n"
               "add.u32 c, c, 1;\nsetp.lt.u32 p, c, 2000000;\n@p bra LAB_WAIT;\ntrap;\nLAB_DONE:\n}\n"
               ::"r"(bar), "r"(parity) : "memory");
}
__device__ __forceinline__ void mbar_arrive(uint32_t bar) {
  asm volatile("mbarrier.arrive.shared::cta.b64 _, [%0];" ::"r"(bar) : "memory");
}
__device__ __forceinline__ void flag_signal(uint32_t* flag) {
  asm volatile("red.release.gpu.global.add.u32 [%0], 1;" ::"l"(flag) : "memory");
}
__device__ __forceinline__ void st_b128(uint4* p, uint32_t a, uint32_t b, uint32_t c, uint32_t d) {
  asm volatile("{\n.reg .b128 t;\n.reg .b64 lo, hi;\nmov.b64 lo, {%1,%2};\nmov.b64 hi, {%3,%4};\nmov.b128 t, {lo, hi};\n"
               "st.relaxed.gpu.global.b128 [%0], t;\n}\n" ::"l"(p), "r"(a), "r"(b), "r"(c), "r"(d) : "memory");
}
__device__ __forceinline__ uint4 ld_b128(const uint4* p) {
  uint4 v;
  asm volatile("{\n.reg .b128 t;\n.reg .b64 lo, hi;\nld.relaxed.gpu.global.b128 t, [%4];\nmov.b128 {lo, hi}, t;\n"
               "mov.b64 {%0,%1}, lo;\nmov.b64 {%2,%3}, hi;\n}\n" : "=r"(v.x), "=r"(v.y), "=r"(v.z), "=r"(v.w) : "l"(p) : "memory");
  return v;
}
__device__ __forceinline__ uint32_t ld_epoch(Scratch* sc) {
  uint32_t v;
  asm volatile("ld.relaxed.gpu.global.u32 %0, [%1];" : "=r"(v) : "l"(sc->epoch) : "memory");
  return v + 1;
}
__device__ __forceinline__ void flag_wait(uint32_t* flag, uint32_t target) {
  asm volatile("{\n.reg .pred p;\n.reg .u32 c, v;\nmov.u32 c, 0;\n"
               "LAB_WAIT:\nld.relaxed.gpu.global.u32 v, [%0];\nsub.u32 v, v, %1;\nsetp.ge.s32 p, v, 0;\n@p bra LAB_DONE;\n"
               "add.u32 c, c, 1;\nsetp.lt.u32 p, c, 4000000;\n@p bra LAB_WAIT;\ntrap;\nLAB_DONE:\n}\n"
               ::"l"(flag), "r"(target) : "memory");
}
__device__ __forceinline__ int fresh_tid() {
  int v;
  asm volatile("mov.u32 %0, %%tid.x;" : "=r"(v));
  return v;
}
constexpr uint32_t kPoison = 0xFFFFFFFFu;
__device__ __forceinline__ bool elect_one() {
  uint32_t p;
  asm volatile("{\n.reg .pred P;\nelect.sync _|P, 0xffffffff;\nselp.u32 %0, 1, 0, P;\n}\n" : "=r"(p));
  return p != 0;
}
__device__ __forceinline__ void fence_async() { asm volatile("fence.acquire.gpu;\nfence.proxy.async.global;" ::: "memory"); }
__device__ __forceinline__ void fence_async_smem() { asm volatile("fence.proxy.async.shared::cta;" ::: "memory"); }
__device__ __forceinline__ void nb_sync(int id, int n) { asm volatile("bar.sync %0, %1;" ::"r"(id), "r"(n) : "memory"); }
__device__ __forceinline__ void nb_arrive(int id, int n) { asm volatile("bar.arrive %0, %1;" ::"r"(id), "r"(n) : "memory"); }

__device__ __forceinline__ void tma2d(uint32_t dst, const CUtensorMap* m, int c0, int c1, uint32_t bar) {
  asm volatile("cp.async.bulk.tensor.2d.shared::cluster.global.mbarrier::complete_tx::bytes [%0], [%1, {%3, %4}], [%2];"
               ::"r"(dst), "l"(m), "r"(bar), "r"(c0), "r"(c1) : "memory");
}
__device__ __forceinline__ void tma2d_mc(uint32_t dst, const CUtensorMap* m, int c0, int c1, uint32_t bar) {
  asm volatile("cp.async.bulk.tensor.2d.shared::cluster.global.mbarrier::complete_tx::bytes.multicast::cluster"
               " [%0], [%1, {%3, %4}], [%2], %5;"
               ::"r"(dst), "l"(m), "r"(bar), "r"(c0), "r"(c1), "h"((uint16_t)3) : "memory");
}
__device__ __forceinline__ void tma3d(uint32_t dst, const CUtensorMap* m, int c0, int c1, int c2, uint32_t bar) {
  asm volatile("cp.async.bulk.tensor.3d.shared::cluster.global.mbarrier::complete_tx::bytes [%0], [%1, {%3, %4, %5}], [%2];"
               ::"r"(dst), "l"(m), "r"(bar), "r"(c0), "r"(c1), "r"(c2) : "memory");
}
__device__ __forceinline__ void tma_store2d(const CUtensorMap* m, uint32_t src, int c0, int c1) {
  asm volatile("cp.async.bulk.tensor.2d.global.shared::cta.bulk_group [%0, {%2, %3}], [%1];"
               ::"l"(m), "r"(src), "r"(c0), "r"(c1) : "memory");
}
__device__ __forceinline__ void tma_store3d(const CUtensorMap* m, uint32_t src, int c0, int c1, int c2) {
  asm volatile("cp.async.bulk.tensor.3d.global.shared::cta.bulk_group [%0, {%2, %3, %4}], [%1];"
               ::"l"(m), "r"(src), "r"(c0), "r"(c1), "r"(c2) : "memory");
}
__device__ __forceinline__ void tma_prefetch2d(const CUtensorMap* m, int c0, int c1) {
  asm volatile("cp.async.bulk.prefetch.tensor.2d.L2.global [%0, {%1, %2}];" ::"l"(m), "r"(c0), "r"(c1) : "memory");
}
__device__ __forceinline__ void prefetch_map(const CUtensorMap* m) { asm volatile("prefetch.tensormap [%0];" ::"l"(m) : "memory"); }
__device__ __forceinline__ void bulk_commit() { asm volatile("cp.async.bulk.commit_group;" ::: "memory"); }
__device__ __forceinline__ void bulk_wait_all() { asm volatile("cp.async.bulk.wait_group 0;" ::: "memory"); }
__device__ __forceinline__ void bulk_wait_read() { asm volatile("cp.async.bulk.wait_group.read 0;" ::: "memory"); }
__device__ __forceinline__ void prefetch_l2(const void* p) { asm volatile("prefetch.global.L2 [%0];" ::"l"(p)); }
__device__ __forceinline__ void cluster_arrive() { asm volatile("barrier.cluster.arrive.relaxed.aligned;" ::: "memory"); }
__device__ __forceinline__ void cluster_wait() { asm volatile("barrier.cluster.wait.aligned;" ::: "memory"); }

__device__ __forceinline__ void wg_fence() { asm volatile("wgmma.fence.sync.aligned;" ::: "memory"); }
__device__ __forceinline__ void wg_commit() { asm volatile("wgmma.commit_group.sync.aligned;" ::: "memory"); }
template <int N> __device__ __forceinline__ void wg_wait() { asm volatile("wgmma.wait_group.sync.aligned %0;" ::"n"(N) : "memory"); }
__device__ __forceinline__ uint32_t desc_lo(uint32_t addr, uint32_t lbo) { return ((addr & 0x3FFFF) >> 4) | ((lbo >> 4) << 16); }
__device__ __forceinline__ uint64_t desc(uint32_t lo) { return (uint64_t)lo | (0x40000040ull << 32); }
__device__ __forceinline__ uint64_t desc_kept(uint32_t lo, uint32_t sb) { return (uint64_t)lo | (uint64_t)(0x40000040u | sb >> 31) << 32; }
constexpr int kToB = (16384 >> 4) + ((8192 - 16) >> 4 << 16);

__device__ __forceinline__ void wgmma_n128(float (&d)[96], uint64_t da, uint64_t db) {
  asm volatile(
      "wgmma.mma_async.sync.aligned.m64n128k16.f32.bf16.bf16 {"
      "%0, %1, %2, %3, %4, %5, %6, %7, %8, %9, %10, %11, %12, %13, %14, %15, "
      "%16, %17, %18, %19, %20, %21, %22, %23, %24, %25, %26, %27, %28, %29, %30, %31, "
      "%32, %33, %34, %35, %36, %37, %38, %39, %40, %41, %42, %43, %44, %45, %46, %47, "
      "%48, %49, %50, %51, %52, %53, %54, %55, %56, %57, %58, %59, %60, %61, %62, %63}, "
      "%64, %65, 1, 1, 1, 0, 1;\n"
      :
        "+f"(d[0]), "+f"(d[1]), "+f"(d[2]), "+f"(d[3]), "+f"(d[4]), "+f"(d[5]), "+f"(d[6]), "+f"(d[7]),
        "+f"(d[8]), "+f"(d[9]), "+f"(d[10]), "+f"(d[11]), "+f"(d[12]), "+f"(d[13]), "+f"(d[14]), "+f"(d[15]),
        "+f"(d[16]), "+f"(d[17]), "+f"(d[18]), "+f"(d[19]), "+f"(d[20]), "+f"(d[21]), "+f"(d[22]), "+f"(d[23]),
        "+f"(d[24]), "+f"(d[25]), "+f"(d[26]), "+f"(d[27]), "+f"(d[28]), "+f"(d[29]), "+f"(d[30]), "+f"(d[31]),
        "+f"(d[32]), "+f"(d[33]), "+f"(d[34]), "+f"(d[35]), "+f"(d[36]), "+f"(d[37]), "+f"(d[38]), "+f"(d[39]),
        "+f"(d[40]), "+f"(d[41]), "+f"(d[42]), "+f"(d[43]), "+f"(d[44]), "+f"(d[45]), "+f"(d[46]), "+f"(d[47]),
        "+f"(d[48]), "+f"(d[49]), "+f"(d[50]), "+f"(d[51]), "+f"(d[52]), "+f"(d[53]), "+f"(d[54]), "+f"(d[55]),
        "+f"(d[56]), "+f"(d[57]), "+f"(d[58]), "+f"(d[59]), "+f"(d[60]), "+f"(d[61]), "+f"(d[62]), "+f"(d[63])
      : "l"(da), "l"(db));
}

__device__ __forceinline__ void wgmma_n256(float (&d)[128], uint64_t da, uint64_t db, int add) {
  asm volatile(
      "{\n.reg .pred p;\nsetp.ne.b32 p, %130, 0;\n"
      "wgmma.mma_async.sync.aligned.m64n256k16.f32.bf16.bf16 {"
      "%0, %1, %2, %3, %4, %5, %6, %7, %8, %9, %10, %11, %12, %13, %14, %15, "
      "%16, %17, %18, %19, %20, %21, %22, %23, %24, %25, %26, %27, %28, %29, %30, %31, "
      "%32, %33, %34, %35, %36, %37, %38, %39, %40, %41, %42, %43, %44, %45, %46, %47, "
      "%48, %49, %50, %51, %52, %53, %54, %55, %56, %57, %58, %59, %60, %61, %62, %63, "
      "%64, %65, %66, %67, %68, %69, %70, %71, %72, %73, %74, %75, %76, %77, %78, %79, "
      "%80, %81, %82, %83, %84, %85, %86, %87, %88, %89, %90, %91, %92, %93, %94, %95, "
      "%96, %97, %98, %99, %100, %101, %102, %103, %104, %105, %106, %107, %108, %109, %110, %111, "
      "%112, %113, %114, %115, %116, %117, %118, %119, %120, %121, %122, %123, %124, %125, %126, %127}, "
      "%128, %129, p, 1, 1, 0, 1;\n}\n"
      :
        "+f"(d[0]), "+f"(d[1]), "+f"(d[2]), "+f"(d[3]), "+f"(d[4]), "+f"(d[5]), "+f"(d[6]), "+f"(d[7]),
        "+f"(d[8]), "+f"(d[9]), "+f"(d[10]), "+f"(d[11]), "+f"(d[12]), "+f"(d[13]), "+f"(d[14]), "+f"(d[15]),
        "+f"(d[16]), "+f"(d[17]), "+f"(d[18]), "+f"(d[19]), "+f"(d[20]), "+f"(d[21]), "+f"(d[22]), "+f"(d[23]),
        "+f"(d[24]), "+f"(d[25]), "+f"(d[26]), "+f"(d[27]), "+f"(d[28]), "+f"(d[29]), "+f"(d[30]), "+f"(d[31]),
        "+f"(d[32]), "+f"(d[33]), "+f"(d[34]), "+f"(d[35]), "+f"(d[36]), "+f"(d[37]), "+f"(d[38]), "+f"(d[39]),
        "+f"(d[40]), "+f"(d[41]), "+f"(d[42]), "+f"(d[43]), "+f"(d[44]), "+f"(d[45]), "+f"(d[46]), "+f"(d[47]),
        "+f"(d[48]), "+f"(d[49]), "+f"(d[50]), "+f"(d[51]), "+f"(d[52]), "+f"(d[53]), "+f"(d[54]), "+f"(d[55]),
        "+f"(d[56]), "+f"(d[57]), "+f"(d[58]), "+f"(d[59]), "+f"(d[60]), "+f"(d[61]), "+f"(d[62]), "+f"(d[63]),
        "+f"(d[64]), "+f"(d[65]), "+f"(d[66]), "+f"(d[67]), "+f"(d[68]), "+f"(d[69]), "+f"(d[70]), "+f"(d[71]),
        "+f"(d[72]), "+f"(d[73]), "+f"(d[74]), "+f"(d[75]), "+f"(d[76]), "+f"(d[77]), "+f"(d[78]), "+f"(d[79]),
        "+f"(d[80]), "+f"(d[81]), "+f"(d[82]), "+f"(d[83]), "+f"(d[84]), "+f"(d[85]), "+f"(d[86]), "+f"(d[87]),
        "+f"(d[88]), "+f"(d[89]), "+f"(d[90]), "+f"(d[91]), "+f"(d[92]), "+f"(d[93]), "+f"(d[94]), "+f"(d[95]),
        "+f"(d[96]), "+f"(d[97]), "+f"(d[98]), "+f"(d[99]), "+f"(d[100]), "+f"(d[101]), "+f"(d[102]), "+f"(d[103]),
        "+f"(d[104]), "+f"(d[105]), "+f"(d[106]), "+f"(d[107]), "+f"(d[108]), "+f"(d[109]), "+f"(d[110]), "+f"(d[111]),
        "+f"(d[112]), "+f"(d[113]), "+f"(d[114]), "+f"(d[115]), "+f"(d[116]), "+f"(d[117]), "+f"(d[118]), "+f"(d[119]),
        "+f"(d[120]), "+f"(d[121]), "+f"(d[122]), "+f"(d[123]), "+f"(d[124]), "+f"(d[125]), "+f"(d[126]), "+f"(d[127])
      : "l"(da), "l"(db), "r"(add));
}

__device__ __forceinline__ void wgmma_n192(float (&d)[96], uint64_t da, uint64_t db, int add = 1) {
  asm volatile(
      "{\n.reg .pred p;\nsetp.ne.b32 p, %98, 0;\n"
      "wgmma.mma_async.sync.aligned.m64n192k16.f32.bf16.bf16 {"
      "%0, %1, %2, %3, %4, %5, %6, %7, %8, %9, %10, %11, %12, %13, %14, %15, "
      "%16, %17, %18, %19, %20, %21, %22, %23, %24, %25, %26, %27, %28, %29, %30, %31, "
      "%32, %33, %34, %35, %36, %37, %38, %39, %40, %41, %42, %43, %44, %45, %46, %47, "
      "%48, %49, %50, %51, %52, %53, %54, %55, %56, %57, %58, %59, %60, %61, %62, %63, "
      "%64, %65, %66, %67, %68, %69, %70, %71, %72, %73, %74, %75, %76, %77, %78, %79, "
      "%80, %81, %82, %83, %84, %85, %86, %87, %88, %89, %90, %91, %92, %93, %94, %95}, "
      "%96, %97, p, 1, 1, 0, 1;\n}\n"
      :
        "+f"(d[0]), "+f"(d[1]), "+f"(d[2]), "+f"(d[3]), "+f"(d[4]), "+f"(d[5]), "+f"(d[6]), "+f"(d[7]),
        "+f"(d[8]), "+f"(d[9]), "+f"(d[10]), "+f"(d[11]), "+f"(d[12]), "+f"(d[13]), "+f"(d[14]), "+f"(d[15]),
        "+f"(d[16]), "+f"(d[17]), "+f"(d[18]), "+f"(d[19]), "+f"(d[20]), "+f"(d[21]), "+f"(d[22]), "+f"(d[23]),
        "+f"(d[24]), "+f"(d[25]), "+f"(d[26]), "+f"(d[27]), "+f"(d[28]), "+f"(d[29]), "+f"(d[30]), "+f"(d[31]),
        "+f"(d[32]), "+f"(d[33]), "+f"(d[34]), "+f"(d[35]), "+f"(d[36]), "+f"(d[37]), "+f"(d[38]), "+f"(d[39]),
        "+f"(d[40]), "+f"(d[41]), "+f"(d[42]), "+f"(d[43]), "+f"(d[44]), "+f"(d[45]), "+f"(d[46]), "+f"(d[47]),
        "+f"(d[48]), "+f"(d[49]), "+f"(d[50]), "+f"(d[51]), "+f"(d[52]), "+f"(d[53]), "+f"(d[54]), "+f"(d[55]),
        "+f"(d[56]), "+f"(d[57]), "+f"(d[58]), "+f"(d[59]), "+f"(d[60]), "+f"(d[61]), "+f"(d[62]), "+f"(d[63]),
        "+f"(d[64]), "+f"(d[65]), "+f"(d[66]), "+f"(d[67]), "+f"(d[68]), "+f"(d[69]), "+f"(d[70]), "+f"(d[71]),
        "+f"(d[72]), "+f"(d[73]), "+f"(d[74]), "+f"(d[75]), "+f"(d[76]), "+f"(d[77]), "+f"(d[78]), "+f"(d[79]),
        "+f"(d[80]), "+f"(d[81]), "+f"(d[82]), "+f"(d[83]), "+f"(d[84]), "+f"(d[85]), "+f"(d[86]), "+f"(d[87]),
        "+f"(d[88]), "+f"(d[89]), "+f"(d[90]), "+f"(d[91]), "+f"(d[92]), "+f"(d[93]), "+f"(d[94]), "+f"(d[95])
      : "l"(da), "l"(db), "r"(add));
}

__device__ __forceinline__ void wgmma_n192_any(float (&d)[96], uint64_t da, uint64_t db) {
  asm volatile(
      "wgmma.mma_async.sync.aligned.m64n192k16.f32.bf16.bf16 {"
      "%0, %1, %2, %3, %4, %5, %6, %7, %8, %9, %10, %11, %12, %13, %14, %15, "
      "%16, %17, %18, %19, %20, %21, %22, %23, %24, %25, %26, %27, %28, %29, %30, %31, "
      "%32, %33, %34, %35, %36, %37, %38, %39, %40, %41, %42, %43, %44, %45, %46, %47, "
      "%48, %49, %50, %51, %52, %53, %54, %55, %56, %57, %58, %59, %60, %61, %62, %63, "
      "%64, %65, %66, %67, %68, %69, %70, %71, %72, %73, %74, %75, %76, %77, %78, %79, "
      "%80, %81, %82, %83, %84, %85, %86, %87, %88, %89, %90, %91, %92, %93, %94, %95}, "
      "%96, %97, 0, 1, 1, 0, 1;\n"
      :
        "=f"(d[0]), "=f"(d[1]), "=f"(d[2]), "=f"(d[3]), "=f"(d[4]), "=f"(d[5]), "=f"(d[6]), "=f"(d[7]),
        "=f"(d[8]), "=f"(d[9]), "=f"(d[10]), "=f"(d[11]), "=f"(d[12]), "=f"(d[13]), "=f"(d[14]), "=f"(d[15]),
        "=f"(d[16]), "=f"(d[17]), "=f"(d[18]), "=f"(d[19]), "=f"(d[20]), "=f"(d[21]), "=f"(d[22]), "=f"(d[23]),
        "=f"(d[24]), "=f"(d[25]), "=f"(d[26]), "=f"(d[27]), "=f"(d[28]), "=f"(d[29]), "=f"(d[30]), "=f"(d[31]),
        "=f"(d[32]), "=f"(d[33]), "=f"(d[34]), "=f"(d[35]), "=f"(d[36]), "=f"(d[37]), "=f"(d[38]), "=f"(d[39]),
        "=f"(d[40]), "=f"(d[41]), "=f"(d[42]), "=f"(d[43]), "=f"(d[44]), "=f"(d[45]), "=f"(d[46]), "=f"(d[47]),
        "=f"(d[48]), "=f"(d[49]), "=f"(d[50]), "=f"(d[51]), "=f"(d[52]), "=f"(d[53]), "=f"(d[54]), "=f"(d[55]),
        "=f"(d[56]), "=f"(d[57]), "=f"(d[58]), "=f"(d[59]), "=f"(d[60]), "=f"(d[61]), "=f"(d[62]), "=f"(d[63]),
        "=f"(d[64]), "=f"(d[65]), "=f"(d[66]), "=f"(d[67]), "=f"(d[68]), "=f"(d[69]), "=f"(d[70]), "=f"(d[71]),
        "=f"(d[72]), "=f"(d[73]), "=f"(d[74]), "=f"(d[75]), "=f"(d[76]), "=f"(d[77]), "=f"(d[78]), "=f"(d[79]),
        "=f"(d[80]), "=f"(d[81]), "=f"(d[82]), "=f"(d[83]), "=f"(d[84]), "=f"(d[85]), "=f"(d[86]), "=f"(d[87]),
        "=f"(d[88]), "=f"(d[89]), "=f"(d[90]), "=f"(d[91]), "=f"(d[92]), "=f"(d[93]), "=f"(d[94]), "=f"(d[95])
      : "l"(da), "l"(db));
}

__device__ __forceinline__ void wgmma_n192_rs(float (&d)[96], uint32_t a0, uint32_t a1, uint32_t a23, uint64_t db) {
  asm volatile(
      "wgmma.mma_async.sync.aligned.m64n192k16.f32.bf16.bf16 {"
      "%0, %1, %2, %3, %4, %5, %6, %7, %8, %9, %10, %11, %12, %13, %14, %15, "
      "%16, %17, %18, %19, %20, %21, %22, %23, %24, %25, %26, %27, %28, %29, %30, %31, "
      "%32, %33, %34, %35, %36, %37, %38, %39, %40, %41, %42, %43, %44, %45, %46, %47, "
      "%48, %49, %50, %51, %52, %53, %54, %55, %56, %57, %58, %59, %60, %61, %62, %63, "
      "%64, %65, %66, %67, %68, %69, %70, %71, %72, %73, %74, %75, %76, %77, %78, %79, "
      "%80, %81, %82, %83, %84, %85, %86, %87, %88, %89, %90, %91, %92, %93, %94, %95}, "
      "{%96, %97, %98, %98}, %99, 1, 1, 1, 1;\n"
      :
        "+f"(d[0]), "+f"(d[1]), "+f"(d[2]), "+f"(d[3]), "+f"(d[4]), "+f"(d[5]), "+f"(d[6]), "+f"(d[7]),
        "+f"(d[8]), "+f"(d[9]), "+f"(d[10]), "+f"(d[11]), "+f"(d[12]), "+f"(d[13]), "+f"(d[14]), "+f"(d[15]),
        "+f"(d[16]), "+f"(d[17]), "+f"(d[18]), "+f"(d[19]), "+f"(d[20]), "+f"(d[21]), "+f"(d[22]), "+f"(d[23]),
        "+f"(d[24]), "+f"(d[25]), "+f"(d[26]), "+f"(d[27]), "+f"(d[28]), "+f"(d[29]), "+f"(d[30]), "+f"(d[31]),
        "+f"(d[32]), "+f"(d[33]), "+f"(d[34]), "+f"(d[35]), "+f"(d[36]), "+f"(d[37]), "+f"(d[38]), "+f"(d[39]),
        "+f"(d[40]), "+f"(d[41]), "+f"(d[42]), "+f"(d[43]), "+f"(d[44]), "+f"(d[45]), "+f"(d[46]), "+f"(d[47]),
        "+f"(d[48]), "+f"(d[49]), "+f"(d[50]), "+f"(d[51]), "+f"(d[52]), "+f"(d[53]), "+f"(d[54]), "+f"(d[55]),
        "+f"(d[56]), "+f"(d[57]), "+f"(d[58]), "+f"(d[59]), "+f"(d[60]), "+f"(d[61]), "+f"(d[62]), "+f"(d[63]),
        "+f"(d[64]), "+f"(d[65]), "+f"(d[66]), "+f"(d[67]), "+f"(d[68]), "+f"(d[69]), "+f"(d[70]), "+f"(d[71]),
        "+f"(d[72]), "+f"(d[73]), "+f"(d[74]), "+f"(d[75]), "+f"(d[76]), "+f"(d[77]), "+f"(d[78]), "+f"(d[79]),
        "+f"(d[80]), "+f"(d[81]), "+f"(d[82]), "+f"(d[83]), "+f"(d[84]), "+f"(d[85]), "+f"(d[86]), "+f"(d[87]),
        "+f"(d[88]), "+f"(d[89]), "+f"(d[90]), "+f"(d[91]), "+f"(d[92]), "+f"(d[93]), "+f"(d[94]), "+f"(d[95])
      : "r"(a0), "r"(a1), "r"(a23), "l"(db));
}

__device__ __forceinline__ uint32_t pack_bf16(float lo, float hi) {
  uint32_t r;
  asm("cvt.rn.bf16x2.f32 %0, %1, %2;" : "=r"(r) : "f"(hi), "f"(lo));
  return r;
}
__device__ __forceinline__ float bf_lo(uint32_t v) { return __uint_as_float(v << 16); }
__device__ __forceinline__ float bf_hi(uint32_t v) { return __uint_as_float(v & 0xFFFF0000u); }
__device__ __forceinline__ float ex2(float x) { float r; asm("ex2.approx.ftz.f32 %0, %1;" : "=f"(r) : "f"(x)); return r; }
__device__ __forceinline__ float rcp(float x) { float r; asm("rcp.approx.ftz.f32 %0, %1;" : "=f"(r) : "f"(x)); return r; }
__device__ __forceinline__ uint32_t movm(uint32_t a) {
  uint32_t d;
  asm volatile("movmatrix.sync.aligned.m8n8.trans.b16 %0, %1;" : "=r"(d) : "r"(a));
  return d;
}
__device__ __forceinline__ void mma16816(float (&c)[4], uint32_t a0, uint32_t a1, uint32_t a2, uint32_t a3, uint32_t b0, uint32_t b1) {
  asm volatile("mma.sync.aligned.m16n8k16.row.col.f32.bf16.bf16.f32 {%0,%1,%2,%3}, {%4,%5,%6,%7}, {%8,%9}, {%0,%1,%2,%3};"
               : "+f"(c[0]), "+f"(c[1]), "+f"(c[2]), "+f"(c[3]) : "r"(a0), "r"(a1), "r"(a2), "r"(a3), "r"(b0), "r"(b1));
}
__device__ __forceinline__ void mma1688(float (&c)[4], uint32_t a0, uint32_t a1, uint32_t b0) {
  asm volatile("mma.sync.aligned.m16n8k8.row.col.f32.bf16.bf16.f32 {%0,%1,%2,%3}, {%4,%5}, {%6}, {%0,%1,%2,%3};"
               : "+f"(c[0]), "+f"(c[1]), "+f"(c[2]), "+f"(c[3]) : "r"(a0), "r"(a1), "r"(b0));
}
__device__ __forceinline__ void stsm4(uint32_t addr, uint32_t a, uint32_t b, uint32_t c, uint32_t d) {
  asm volatile("stmatrix.sync.aligned.m8n8.x4.shared.b16 [%0], {%1,%2,%3,%4};" ::"r"(addr), "r"(a), "r"(b), "r"(c), "r"(d) : "memory");
}
__device__ __forceinline__ void stsm4_t(uint32_t addr, uint32_t a, uint32_t b, uint32_t c, uint32_t d) {
  asm volatile("stmatrix.sync.aligned.m8n8.x4.trans.shared.b16 [%0], {%1,%2,%3,%4};" ::"r"(addr), "r"(a), "r"(b), "r"(c), "r"(d) : "memory");
}
__device__ __forceinline__ void ldsm4(uint32_t addr, uint32_t (&v)[4]) {
  asm volatile("ldmatrix.sync.aligned.m8n8.x4.shared.b16 {%0,%1,%2,%3}, [%4];"
               : "=r"(v[0]), "=r"(v[1]), "=r"(v[2]), "=r"(v[3]) : "r"(addr) : "memory");
}
__device__ __forceinline__ void sts128(uint32_t addr, uint4 v) {
  asm volatile("st.shared.v4.b32 [%0], {%1,%2,%3,%4};" ::"r"(addr), "r"(v.x), "r"(v.y), "r"(v.z), "r"(v.w) : "memory");
}
__device__ __forceinline__ uint4 lds128(uint32_t addr) {
  uint4 v;
  asm volatile("ld.shared.v4.b32 {%0,%1,%2,%3}, [%4];" : "=r"(v.x), "=r"(v.y), "=r"(v.z), "=r"(v.w) : "r"(addr) : "memory");
  return v;
}
__device__ __forceinline__ void sts64(uint32_t addr, uint32_t a, uint32_t b) {
  asm volatile("st.shared.v2.b32 [%0], {%1,%2};" ::"r"(addr), "r"(a), "r"(b) : "memory");
}
__device__ __forceinline__ void sts32(uint32_t addr, uint32_t a) { asm volatile("st.shared.b32 [%0], %1;" ::"r"(addr), "r"(a) : "memory"); }
__device__ __forceinline__ uint32_t lds32(uint32_t addr) {
  uint32_t v;
  asm volatile("ld.shared.b32 %0, [%1];" : "=r"(v) : "r"(addr) : "memory");
  return v;
}
__device__ __forceinline__ float2 lds64f_const(uint32_t addr) {
  float2 v;
  asm("ld.shared.v2.f32 {%0,%1}, [%2];" : "=f"(v.x), "=f"(v.y) : "r"(addr));
  return v;
}
template <int N, bool PAIR>
__device__ __forceinline__ void load_tagged(uint3 (&out)[N], const uint4* src, int stride, uint32_t tag, int last = 0) {
  uint32_t bad;
  int spins = 0;
  do {
    if (spins != 0) __nanosleep(kBackoffNs);
    if (++spins > 2000000) __trap();
    bad = 0;
#pragma unroll
    for (int i = 0; i < N; i++) {
      const uint4 v = ld_b128(src + i * stride + (i == N - 1 ? last : 0));
      out[i] = make_uint3(v.x, v.y, v.z);
      bad |= (v.w ^ tag) | (PAIR ? v.z ^ tag : 0);
    }
  } while (bad != 0);
}
__device__ __forceinline__ void sts64f(uint32_t addr, float2 v) { sts64(addr, __float_as_uint(v.x), __float_as_uint(v.y)); }
__device__ __forceinline__ float bf_rest(float v) { return v - __uint_as_float(__float_as_uint(v) & 0xFFFF0000u); }
__device__ __forceinline__ uint32_t bf_upper(float lo, float hi) { return __byte_perm(__float_as_uint(lo), __float_as_uint(hi), 0x7632); }
__device__ __forceinline__ float low_peak(uint4 v) {
  asm("max.xorsign.abs.bf16x2 %0, %0, %1;" : "+r"(v.x) : "r"(v.y));
  asm("max.xorsign.abs.bf16x2 %0, %0, %1;" : "+r"(v.z) : "r"(v.w));
  asm("max.xorsign.abs.bf16x2 %0, %0, %1;" : "+r"(v.x) : "r"(v.z));
  asm("max.xorsign.abs.bf16x2 %0, %0, %1;" : "+r"(v.x) : "r"(v.x << 16));
  return __uint_as_float(__reduce_min_sync(~0u, v.x & 0x7FFF0000u));
}
__device__ __forceinline__ float bias_at(float v) { return __uint_as_float((__float_as_uint(fminf(v, 1e37f)) & 0x7F800000u) | 0x00400000u); }
struct RowConst {
  float nmean, k0, k1, half;
};
__device__ __forceinline__ float gate_scale(float t, const RowConst& k) {
  float th;
  asm("tanh.approx.f32 %0, %1;" : "=f"(th) : "f"(t * fmaf(t * t, k.k1, k.k0)));
  return fmaf(th, k.half, k.half);
}

template <int N>
__device__ __forceinline__ void mma_k16(float (&acc)[2][96], uint32_t a, uint32_t b, int kk, int add = 1) {
#pragma unroll
  for (int m = 0; m < 2; m++) {
    const uint64_t da = desc(a) + (m * 512 + kk * 2), db = desc(b) + kk * 128;
    if (N == 128) wgmma_n128(acc[m], da, db); else wgmma_n192(acc[m], da, db, add);
  }
}

__device__ __forceinline__ void stage_quarter(const float* acc, uint32_t frag, uint32_t frag_x, int b, const uint4* add = nullptr) {
#pragma unroll
  for (int j = 0; j < 4; j++) {
    const float* v = acc + 8 * j;
    uint32_t h[4] = {pack_bf16(v[0], v[1]), pack_bf16(v[2], v[3]), pack_bf16(v[4], v[5]), pack_bf16(v[6], v[7])};
    if (add) {
      const uint32_t a[4] = {add[j].x, add[j].y, add[j].z, add[j].w};
#pragma unroll
      for (int e = 0; e < 4; e++) asm("add.rn.bf16x2 %0, %0, %1;" : "+r"(h[e]) : "r"(a[e]));
    }
    stsm4(frag + b * 8192 + ((frag_x ^ (j * 2)) << 4), h[0], h[1], h[2], h[3]);
  }
}

__device__ __forceinline__ int g1_block(int j, int c) { return j < 16 ? j : ((j + 12) & 15) ^ (c == 5 && j >= 28 ? 2 : 0); }
__device__ __forceinline__ int g2_block(int j, int c) { return j < 8 ? j : j == 8 ? 8 + c : j - (j - 9 < c); }
__device__ __forceinline__ int g3_tile(int j) { return j < 4 ? j >> 1 : j < 18 ? 0 : j >> 4; }
__device__ __forceinline__ int g3_block(int j, int c) {
  const int i = j < 32 ? (j < 16 ? 0xDCBA976543218080ull : 0x7654321BA9FEDCFEull) >> 4 * (j & 15) : j + (~j >> 2 & 4), o = i & 7;
  return 2 * (j < 32 && (o == c || o == 0) ? c - o : o) + (i >> 3 & 1);
}
__device__ __forceinline__ bool g3_is_up(int tile, int a) { return a == 1 || (a == 2 && tile >= 2); }
__device__ __forceinline__ int g3_atom(int tile, int a, int c) { return c * 7 + (tile & 1) * 3 + (a == 2 ? 1 : tile == 4 ? 6 : tile & 2); }
__device__ __forceinline__ int g4_block(int i) {
  return i < 16 ? 7 * (i & 7) + 3 * (i >> 3) : i < 48 ? 7 * ((i & 15) >> 1) + 3 * (i >> 5) + 1 + (i & 1) : 7 * (i & 7) + (i < 56 ? 6 : 0);
}

template <int N, int TAIL>
__device__ __forceinline__ void mainloop(Scratch* sc, float (&acc)[2][96], uint32_t sb, int ph, int j0, int nsteps, int pause_at, bool last,
                                         bool hand_over, bool local, int wg, int own = -1, const CUtensorMap* out = nullptr, int out_col = 0,
                                         int out_row = 0, int warp = 0, __nv_bfloat16* outp = nullptr) {
  constexpr int NSLOT = N == 128 ? 5 : 4, SLOT = N == 128 ? 32768 : 40960;
  const int lane = fresh_tid() & 31;
  const uint32_t full = sb + kBars + 8 * ring_base(ph);
  const uint32_t empty = map_cta(full + 8 * NSLOT, lane & 1);
  const uint32_t ring = desc_lo(sb + kRing, 16);
  int bi = j0 % NSLOT, par = (j0 / NSLOT) & 1;
  const int release_end = lane < (N == 192 && !hand_over ? 4 : 2) ? (last ? nsteps - 1 - NSLOT : nsteps) : 0;
  uint32_t rel = empty;
  const uint32_t special = ph == 0 && wg == 0 ? 3 : pause_at < 0 ? 1 : 1 | 2 << pause_at;
#pragma unroll 1
  for (int i = 0; i < nsteps - (TAIL > 0 ? TAIL + 1 : 0); i++) {
    uint32_t a = ring + bi * (SLOT >> 4), b = a + kToB;
    if (TAIL > 0 && i == 0) TSG(5);
    if (special >> i & 1) {
      if (i == 0) nb_sync(kNbOrder + wg, ph == 0 && wg == 0 ? 160 : 256);
      else if (ph == 0 && wg == 0) cluster_wait();
      else if (ph < 2) nb_sync(kNbWin + 1, 256);
    }
    if (N == 192 && local) {
      a = ring + ((kStage + i * 16384) >> 4);
      b = ring + bi * (32768 >> 4) + desc_lo(32768, 8192) - desc_lo(0, 16);
    }
    if (ph == 0 && i >> 1 == own) a = ring + ((kOwn + (i & 1) * 16384) >> 4);
    if (ph == 1 && i == 8) a = ring + ((kStage + 32768) >> 4);
    if (TAIL > 0 && i == 0) TSG(6);
    mbar_wait(full + 8 * bi, par);
    if (N == 192 && local) mbar_wait(sb + kBars + 8 * (kHalfBar + i), 0);
    if (TAIL > 0 && i == 0) TSG(7);
    wg_fence();
    mma_k16<N>(acc, a, b, 0, ph == 0 ? i | wg : 1);
    mma_k16<N>(acc, a, b, 1);
    wg_commit();
    const bool release = (uint32_t)(i - 1) < (uint32_t)release_end;
    wg_wait<1>();
    mbar_arrive_cluster_if(rel, release);
    wg_fence();
    mma_k16<N>(acc, a, b, 2);
    mma_k16<N>(acc, a, b, 3);
    wg_commit();
    rel = empty + 8 * bi;
    if (++bi == NSLOT) { bi = 0; par ^= 1; }
    if (i == pause_at) nb_arrive(kNbWin, 256);
  }
  if (TAIL < 0) return;
  if (TAIL > 0) {
    uint32_t at[TAIL + 2];
    const int t = fresh_tid() & 127;
    uint32_t frag = sb + kStage + ((t >> 5) * 16 + (t & 15)) * 128, frag_x = ((t >> 4) & 1) ^ (t & 7);
    const uint32_t back = sb + kStage + (t >> 5) * 2048 + ((t >> 3) & 3) * 128, back_x = ((t ^ (t >> 3 & 3)) & 7) << 4;
    outp += (2 * (out_row + (t >> 5) * 16 + ((t >> 3) & 3)) + (blockIdx.x & 1)) * kD + out_col + (t & 7) * 8;
    static_assert(kTail == 5, "");
    uint4 part[8];
    mbar_wait(full + 8 * bi, par);
#pragma unroll
    for (int hf = 0; hf < 2; hf++) {
      const uint32_t a = ring + bi * (SLOT >> 4), b = a + kToB;
      wg_fence();
      mma_k16<N>(acc, a, b, 2 * hf);
      mma_k16<N>(acc, a, b, 2 * hf + 1);
      wg_commit();
      if (hf == 0) {
        wg_wait<1>();
        mbar_arrive_cluster_if(rel, (t & 31) < 2);
      }
      mbar_wait(sb + kBars + 8 * (hf ? kStgBar : kPartBar), hf);
#pragma unroll
      for (int k = 4 * hf; k < 4 * hf + 4; k++) part[k] = lds128(sb + kStage + 32768 + (t >> 5) * 4096 + (t & 31) * 16 + k * 512);
    }
    if (++bi == NSLOT) { bi = 0; par ^= 1; }
    auto last_rows = [&](int i0, int i1) {
#pragma unroll
      for (int i = i0; i < i1; i++) {
        if (i == 3) continue;
        at[i] = bi * (SLOT >> 4);
        mbar_wait(full + 8 * bi, par);
        if (++bi == NSLOT) { bi = 0; par ^= 1; }
      }
      wg_fence();
#pragma unroll
      for (int i = 4 * i0; i < 4 * i1; i++)
        wgmma_n128(acc[1], desc_kept(ring, sb) + ((i >> 2 != 3 ? at[i >> 2] + 512 : at[2]) + (i & 3) * 2),
                   desc_kept(ring, sb) + ((i >> 2 != 3 ? at[i >> 2] + kToB : at[0] + ((SLOT - 16) >> 4 << 16)) + (i & 3) * 128));
      wg_commit();
    };
    last_rows(0, 2);
#pragma unroll
    for (int b = 0; b < 4; b++) {
      if (b == 0) wg_wait<1>();
      if (b == 1) last_rows(3, 4);
      if (b == 2) wg_wait<0>();
      if (!(b & 1)) {
#pragma unroll
        for (int i = 0; i < 64; i++) asm volatile("" : "+f"(acc[b >> 1][i])::"memory");
        if (t == 0) TSS(b);
      }
      stage_quarter(&acc[b >> 1][32 * (b & 1)], frag, frag_x, b, b < 2 ? &part[4 * b] : nullptr);
      if (b == 3) {
        __syncwarp();
        uint4 v[4];
#pragma unroll
        for (int i = 0; i < 4; i++) v[i] = lds128(back + b * 8192 + i * 512 + ((i & 1) ? back_x ^ 64 : back_x));
#pragma unroll
        for (int i = 0; i < 4; i++) __stcs((uint4*)(outp + ((b >> 1) * 128 + i * 8) * kD + (b & 1) * 64), v[i]);
        if (t == 0) TSS(4 + b);
        continue;
      }
      if (b < 2) last_rows(2 + 2 * b, 3 + 2 * b);
      fence_async_smem();
      __syncwarp();
      if (elect_one()) tma_store3d(out, sb + kStage + b * 8192 + warp * 2048, out_col + (b & 1) * 64, out_row + (b >> 1) * 64 + warp * 16, blockIdx.x & 1);
      __syncwarp();
      if (t == 0) TSS(4 + b);
    }
    if (elect_one()) {
      bulk_commit();
      bulk_wait_read();
    }
    if (t == 0) TSS(1);
    return;
  }
  if (hand_over) nb_arrive(kNbOrder + (wg ^ 1), 256);
  if (N == 192 && !local) {
    mbar_wait(sb + kBars + 8 * (kAuxBar + wg), j0 < 32);
    if (j0 < 32) mbar_wait(sb + kBars + 8 * kStatBar, 1);
    mbar_wait(sb + kBars + 8 * (kStgBar + wg), ((j0 >> 5) ^ wg ^ 1) & 1);
  }
  wg_wait<0>();
  mbar_arrive_cluster_if(rel, release_end == nsteps);
#pragma unroll
  for (int i = 0; i < N / 2; i++) asm volatile("" : "+f"(acc[0][i]), "+f"(acc[1][i])::"memory");
}

template <int PH>
struct Ring {
  static constexpr int NSLOT = 4 + (PH & 1), SLOT = PH & 1 ? 32768 : 40960;
  uint32_t full, dst0;
  int j = PH == 0 ? 4 : 0, bi = 0, par = PH == 0 ? 0 : 1;
  __device__ __forceinline__ Ring(uint32_t sb, uint32_t ofs) : full(sb + kBars + 8 * (PH * 9 - (PH & 1))), dst0(sb + kRing + ofs) {}
  __device__ __forceinline__ uint32_t bar() const { return full + 8 * bi; }
  __device__ __forceinline__ uint32_t dst() const { return dst0 + bi * SLOT; }
  __device__ __forceinline__ void acquire_first() const {
    const bool first = j < NSLOT;
    mbar_wait(full + (first ? 8 * min(j, 3) - 32 : 8 * (NSLOT + bi)), PH == 2 && first ? 0 : par);
  }
  __device__ __forceinline__ void acquire() const { mbar_wait(full + 8 * (NSLOT + bi), par); }
  __device__ __forceinline__ void next() {
    j++;
    if (++bi == NSLOT) { bi = 0; par ^= 1; }
  }
};

__device__ __forceinline__ void check_blocks(const Params& p, Scratch* sc, uint32_t sb, int r, int c, bool g3, uint32_t& par) {
  const int lane = fresh_tid() & 31, nslot = g3 ? 4 : 5, slot_bytes = g3 ? 40960 : 32768;
  const uint32_t mine = (lane >> 2) * 132 + (lane & 3) * 32, ring_end = sb + kRing + kStage + mine;
  const uint32_t to_full = 8 * (kLandBar - (g3 ? ring_base(2) : ring_base(1)));
  uint32_t src = sb + kRing + mine + (g3 ? 0 : 4 * 32768);
  int bi = g3 ? 0 : 4, spins = 0;
#pragma unroll 1
  for (int i = g3 ? 2 : 9; i < 16;) {
    const uint32_t land = sb + kBars + 8 * (kLandBar + bi);
    mbar_wait(land, (par >> bi) & 1);
    uint32_t v[16];
#pragma unroll
    for (int k = 0; k < 16; k++) v[k] = lds32(src + k * 1024);
#pragma unroll
    for (int k = 0; k < 5; k++) v[k] = max(max(v[3 * k + 1], v[3 * k + 2]), k ? v[3 * k] : max(v[0], v[15]));
    const bool again = __any_sync(~0u, max(max(max(v[0], v[1]), v[2]), max(v[3], v[4])) == kPoison);
    asm volatile("{\n.reg .pred p;\nsetp.eq.u32 p, %1, 0;\n@p mbarrier.arrive.shared::cta.b64 _, [%0];\n}\n"
                 ::"r"(land - to_full), "r"(lane + again) : "memory");
    par ^= 1u << bi;
    if (again) {
      if (++spins > 100000) __trap();
      if (elect_one()) {
        mbar_expect_tx(land, 16384);
        tma2d(src - mine, g3 ? &p.h : &p.o, (g3 ? g3_block(i + 2, c) : g2_block(i, c)) * 64, r * 128, land);
      }
      nb_sync(kNbSelf + 1, 32);
      continue;
    }
    if (lane == 0 && (i == 2 || i == 3 || (!g3 && (i == 9 || i == 12)))) TS(i < 4 ? 88 + 2 * i : i == 9 ? 120 : 122);
    i++;
    if (++bi == nslot) bi = 0;
    src += slot_bytes;
    if (src == ring_end) src -= kStage;
  }
}

__device__ __forceinline__ void colsum_cta(const Params& p, Scratch* sc, uint32_t sb, int warp, int bid) {
  constexpr int kSlots = 4, kSlot = 49152;
  constexpr int kRows = kTail * 32768;
  static_assert(kRows + 65536 <= kCs, "");
  const int lane = threadIdx.x & 31, c0 = (bid - 128) * 2;
  const uint32_t full = sb + kBars, empty = full + 8 * kSlots;
  const uint32_t event = full + 64, stored = full + 96, rfull = full + 128, rempty = full + 192;
  if (threadIdx.x == 0) {
#pragma unroll 1
    for (int i = 0; i < 32; i++) mbar_init(full + 8 * i, i & (i < 16 ? 4 : 8) ? 8 : 1);
    asm volatile("fence.mbarrier_init.release.cluster;" ::: "memory");
  }
  __syncthreads();
  const uint32_t ep = ld_epoch(sc);
  if (warp == 8) {
    if (elect_one()) {
#pragma unroll 1
      for (int n = 0; n < 112 + kSlots; n++) {
        const int u = n >> 4, c = c0 + ((n >> 3) & 1), k0 = (n & 7) * 128, slot = n & (kSlots - 1);
        if (n == kQuietAt) flag_wait(sc->flags + kFlPace, ep);
        const uint32_t bar = full + 8 * slot;
        mbar_wait(empty + 8 * slot, ((n / kSlots) & 1) ^ 1);
        if (n == 108) mbar_arrive(event);
        if (u == 7) continue;
        mbar_expect_tx(bar, u == 6 ? 32768 : 49152);
#pragma unroll
        for (int a = 0; a < 3; a++) {
          if (a == 2 && u == 6) break;
          const CUtensorMap* m = u < 2 ? &p.wqkv : g3_is_up(u - 2, a) ? &p.wu : &p.wg;
          const int col = (u < 2 ? a * 16 + u * 8 + c : g3_atom(u - 2, a, c)) * 64;
          tma2d(sb + slot * kSlot + a * 8192, m, col, k0, bar);
          tma2d(sb + slot * kSlot + a * 8192 + 24576, m, col, k0 + 64, bar);
        }
      }
      mbar_wait(event + 8, 0);
      fence_async();
#pragma unroll 1
      for (int n = 0, r = 0, i = 0; r < 16; n++) {
        const uint32_t bar = rfull + 8 * (n & 7);
        mbar_wait(bar + 64, ~n >> 3 & 1);
        mbar_expect_tx(bar, r ? 8192 : 40960);
        tma2d(sb + kRows + (n & 7) * 8192, &p.hhst, i * (7 * 64), r * 128, bar);
#pragma unroll 1
        for (int a = r ? 4 : 0; a < 4; a++) tma2d(sb + i * 32768 + a * 8192, &p.wd, (c0 * 2 + a) * 64, i * (7 * 64), bar);
        if (++i == kTail) { i = 0; r++; }
      }
    }
  } else if (warp < 8) {
    uint32_t src[3];
#pragma unroll
    for (int j = 0; j < 3; j++) src[j] = sb + ((warp * 3 + j) >> 3) * 8192 + lane * 128 + ((((warp * 3 + j) & 7) ^ (lane & 7)) << 4);
    const uint32_t ones = 0x3F803F80u;
#pragma unroll 1
    for (int s = 0; s < 112; s++) {
      float a[3][2][4] = {};
#pragma unroll 1
      for (;; s++) {
      const int slot = s & (kSlots - 1);
      mbar_wait(full + 8 * slot, (s / kSlots) & 1);
      uint32_t b[3][4][4];
#pragma unroll
      for (int j = 0; j < 3; j++)
#pragma unroll
        for (int k = 0; k < 4; k++)
          asm volatile("ldmatrix.sync.aligned.m8n8.x4.trans.shared.b16 {%0,%1,%2,%3}, [%4];"
                       : "=r"(b[j][k][0]), "=r"(b[j][k][1]), "=r"(b[j][k][2]), "=r"(b[j][k][3])
                       : "r"(src[j] + slot * kSlot + (k >> 1) * 24576 + (k & 1) * 4096) : "memory");
      __syncwarp();
      if (lane == 0) mbar_arrive(empty + 8 * slot);
#pragma unroll
      for (int k = 0; k < 4; k++)
#pragma unroll
        for (int j = 0; j < 3; j++) {
          mma16816(a[j][0], ones, ones, ones, ones, b[j][k][0], b[j][k][1]);
          mma16816(a[j][1], ones, ones, ones, ones, b[j][k][2], b[j][k][3]);
        }
      if ((s & 7) == 7) break;
      }
      {
        if (lane < 12) {
          const int j = lane >> 2;
          const float x = j == 0 ? a[0][0][0] + a[0][1][0] : j == 1 ? a[1][0][0] + a[1][1][0] : a[2][0][0] + a[2][1][0];
          const float y = j == 0 ? a[0][0][1] + a[0][1][1] : j == 1 ? a[1][0][1] + a[1][1][1] : a[2][0][1] + a[2][1][1];
          const float x1 = bf_rest(x), y1 = bf_rest(y);
          const bool split = s < 32;
          st_b128(sc->cs + ((s >> 4) * 8 + c0 + ((s >> 3) & 1)) * 96 + warp * 12 + lane, split ? bf_upper(x, y) : __float_as_uint(x),
                  split ? bf_upper(x1, y1) : __float_as_uint(y), bf_upper(bf_rest(x1), bf_rest(y1)), ep);
        }
        if (threadIdx.x == 0 && (s & 8)) TSK(s >> 4);
      }
    }
    const int wg = warp >> 2;
#pragma unroll 1
    for (int r = wg; r < 16; r += 2) {
      float acc[128];
#pragma unroll
      for (int i = 0; i < 128; i++) asm volatile("" : "=f"(acc[i]));
      const uint32_t da = desc_lo(sb + kRows, 16);
      uint32_t db = desc_lo(sb, 8192);
      int n = r * kTail - 1;
      if (r) nb_sync(kNbOrder + wg, 256);
#pragma unroll 1
      for (int i = 0; i < kTail; i++, db += 2048) {
        const uint32_t done = rempty + 8 * (n & 7);
        n++;
        mbar_wait(rfull + 8 * (n & 7), n >> 3 & 1);
        wg_fence();
#pragma unroll
        for (int k = 0; k < 4; k++) wgmma_n256(acc, desc(da + (n & 7) * 512) + k * 2, desc(db) + k * 128, k | i);
        wg_commit();
        wg_wait<1>();
        if (lane < 2 && i) mbar_arrive(done);
      }
      if (r < 15) nb_arrive(kNbOrder + (wg ^ 1), 256);
      wg_wait<0>();
#pragma unroll
      for (int i = 0; i < 128; i++) asm volatile("" : "+f"(acc[i])::"memory");
      if (lane < 2) mbar_arrive(rempty + 8 * (n & 7));
#pragma unroll
      for (int i = 0; i < 16; i++) {
        const float* v = &acc[8 * i];
        __stcg(sc->part + (r * 8 + c0) * 1024 + (warp & 3) * 256 + lane + (i >> 3) * 1024 + (i & 7) * 32,
               make_uint4(pack_bf16(v[0], v[1]), pack_bf16(v[2], v[3]), pack_bf16(v[4], v[5]), pack_bf16(v[6], v[7])));
      }
      __syncwarp();
      if ((r & 2) && lane == 0) mbar_arrive(stored + 8 * (r >> 2));
    }
  } else if (warp == 10) {
    mbar_wait(event, 0);
    flag_wait(sc->flags + kFlHH + (lane & 15) * kFlRow, ep * 8);
    fence_async();
    __syncwarp();
    if (lane == 0) mbar_arrive(event + 8);
  } else if (threadIdx.x == 352) {
#pragma unroll 1
    for (int r = 0; r < 16; r += 4) {
      mbar_wait(stored + 2 * r, 0);
      flag_signal(sc->flags + kFlPart + (c0 >> 1) + r * kFlRow);
    }
    TSK(7);
  }
}

#define PROF_BEGIN
template <bool BY_SM>
__global__ void __cluster_dims__(2, 1, 1) __launch_bounds__(kThreads, 1) fused_block_kernel(Scratch* sc, const __nv_bfloat16* xp, const __nv_bfloat16* wqkvp, __nv_bfloat16* outp,
                                                                   const __grid_constant__ Params p) {
  extern __shared__ __align__(1024) uint8_t smem_raw[];
  if (threadIdx.x < 56) {
    const int l = threadIdx.x & 31, b = blockIdx.x & 127;
    if (threadIdx.x < 32) prefetch_l2(xp + (b * 16 + (l & 15)) * kD + (l >> 4) * 64);
    else prefetch_l2(wqkvp + b * (3 * kD) + (l >> 3) * kD + (l & 7) * 64);
  }
  const uint32_t sb = smem_u32(smem_raw);
  const int bid = role_id<BY_SM>();
  const int r = bid >> 3, c = bid & 7, rank = blockIdx.x & 1;
  auto first_fill = [&](int j) {
    const uint32_t fb = sb + kBars + 8 * j, dst = sb + kRing + j * 40960;
    mbar_expect_tx(fb, 40960);
    tma3d(j >> 1 == c ? sb + kOwn + (j & 1) * 16384 : dst, &p.x, j * 64, (r >> 1) * 128, rank, fb);
#pragma unroll
    for (int a = 0; a < 3; a++) tma2d(dst + 16384 + a * 8192, &p.wqkv, a * kD + c * 64, j * 64, fb);
    mbar_arrive(fb);
  };
  const int tid = threadIdx.x, warp = __shfl_sync(~0u, tid >> 5, 0), wg = warp >> 2;
  if (bid >= 128) {
    if (tid == 0) PROF_BEGIN;
    colsum_cta(p, sc, sb, warp, bid);
    return;
  }
  if (wg == 2) {
    if (warp == 8 && elect_one()) {
#pragma unroll
      for (int j = 0; j < 4; j++) mbar_init(sb + kBars + 8 * j, 2);
      asm volatile("fence.mbarrier_init.release.cluster;" ::: "memory");
      first_fill(0);
      TSS(0);
    }
    __syncwarp();
    if (warp == 8) nb_arrive(kNbOrder, 160);
    asm volatile("setmaxnreg.dec.sync.aligned.u32 40;");
    if (warp == 8) {
      cluster_arrive();
      if (elect_one()) {
#pragma unroll 1
        for (int j = 1; j < 4; j++) first_fill(j);
        TSS(1);
      }
      __syncwarp();
    } else {
      if (elect_one()) {
        uint64_t shifts = warp == 9 ? bar_shifts(4) : warp == 10 ? bar_shifts(22) : bar_shifts(40);
#pragma unroll 1
        for (int i = 0; i < 18; i++, shifts >>= 3) mbar_init(sb + kBars + 8 * (18 * warp - 158 + i), 1u << (shifts & 7));
        sts32(sb + kZero, 0);
        sts32(sb + kScale + 4, 0);
        sts32(sb + kRole, bid);
        sts128(sb + kOnes, make_uint4(0x3F803F80u, 0, 0, 0x3F803F80u));
        asm volatile("fence.mbarrier_init.release.cluster;" ::: "memory");
      }
      __syncwarp();
      cluster_arrive();
    }
    cluster_wait();
    const uint32_t ep = ld_epoch(sc);
    if (tid == 320) sts32(sb + kEpoch, ep);
    if (tid == 320) PROF_BEGIN;
    const int pw = warp & 3;
    if (pw == 0) {
      if (elect_one()) {
        const int row = r * 128;
        const uint32_t land = sb + kBars + 8 * kLandBar;
#pragma unroll 1
        for (Ring<0> q(sb, 0); q.j < 32; q.next()) {
          q.acquire();
          const int kb = g1_block(q.j, c);
          if (q.j >= 16 && (q.j < 20 || kb >> 1 == c)) { mbar_arrive(q.bar()); continue; }
          mbar_expect_tx(q.bar(), 16384);
          tma3d(kb >> 1 == c ? sb + kOwn + (kb & 1) * 16384 : q.dst(), &p.x, kb * 64, (r >> 1) * 128, rank, q.bar());
        }
        prefetch_map(&p.o);
        prefetch_map(&p.o16);
        flag_wait(sc->flags + kFlO + r * kFlRow, ep * 8);
        fence_async();
        TS(40);
#pragma unroll 1
        for (Ring<1> q(sb, 0); q.j < 16; q.next()) {
          q.acquire_first();
          if (q.j == 8) {
            prefetch_map(&p.wg);
            prefetch_map(&p.wu);
            prefetch_map(&p.h);
            prefetch_map(&p.h16);
            mbar_wait(sb + kBars + 8 * kSentBar, 0);
            mbar_arrive(q.bar());
            mbar_arrive(sb + kBars + 8 * (kStgBar + 1));
            if (bid == 0) __stcg(sc->flags + kFlPace, ep);
            __nanosleep(kGateONs);
            continue;
          }
          const uint32_t bar = q.j < 8 ? q.bar() : land + 8 * q.bi;
          if (q.j == 9) TS(41);
          mbar_expect_tx(bar, 16384);
          tma2d(q.dst(), &p.o, g2_block(q.j, c) * 64, row, bar);
        }
#pragma unroll 1
        for (Ring<2> q(sb, 0); q.j < 64; q.next()) {
          q.acquire_first();
          if ((0x000F000F003C000Full >> q.j & 1) && q.j != 28 + c) { mbar_arrive(q.bar()); continue; }
          if (q.j == 4) { __nanosleep(kGateHNs); TS(42); }
          const uint32_t bar = q.j < 18 ? land + 8 * q.bi : q.bar();
          mbar_expect_tx(bar, 16384);
          tma2d(q.dst(), &p.h, g3_block(q.j, c) * 64, row, bar);
        }
        prefetch_map(&p.hh);
        prefetch_map(&p.out);
        Ring<3> q(sb, 0);
#pragma unroll 1
        for (; q.j < 16; q.next()) {
          q.acquire_first();
          if (q.j == 0) { mbar_arrive(q.bar()); continue; }
          mbar_expect_tx(q.bar(), 16384);
          tma2d(q.dst(), &p.h, ((q.j + 9) & 15) * 64, row, q.bar());
        }
#pragma unroll 1
        for (int wv = 0; wv < 5; wv++) {
          if (wv == 3 && c < kTail) tma_prefetch2d(&p.hhst, c * (7 * 64), row + 64);
          if (wv == 0 || wv >= 3) {
            mbar_wait(sb + kBars + 8 * (kWaveBar + (wv >> 1)), 0);
            fence_async();
          }
          const int dbl = wv == 2 || wv == 3, f0 = wv == 4 ? 6 : (wv & 1) * 3 + dbl;
#pragma unroll 1
          for (int i = wv ? 0 : kTail; i < 8 << dbl; i++, q.next()) {
            q.acquire();
            mbar_expect_tx(q.bar(), 16384);
            tma2d(q.dst(), &p.hh, ((i >> dbl) * 7 + f0 + (i & dbl)) * 64, row, q.bar());
          }
        }
#pragma unroll 1
        for (int i = 0; i < kTail - 1; i++, q.next()) {
          q.acquire();
          mbar_expect_tx(q.bar(), i < 3 ? 16384 : 8192);
          tma2d(q.dst() + 8192, &p.hhst, i * (7 * 64), row + 64, q.bar());
          if (i == 2) tma2d(q.dst(), &p.hhst, (kTail - 1) * (7 * 64), row + 64, q.bar());
          if (i == rank) tma2d_mc(q.dst(), &p.wd, (c * 2 + rank) * 64, (kTail - 1) * (7 * 64), q.bar());
        }
      }
    } else if (pw == 1) {
      if (elect_one()) {
        const int rp = r >> 1;
#pragma unroll 1
        for (Ring<0> q(sb, 16384); q.j < 32; q.next()) {
          q.acquire();
          mbar_expect_tx(q.bar(), 24576);
          const int col = ((q.j >> 4) * 8 + c) * 64, k0 = g1_block(q.j, c) * 64;
          tma2d_mc(q.dst() + rank * 8192, &p.wqkv, rank * kD + col, k0, q.bar());
          if ((q.j & 1) == rank) tma2d_mc(q.dst() + 16384, &p.wqkv, 2 * kD + col, k0, q.bar());
          if (q.j == max(r, 4))
            for (int a = 0; a < 3; a++) tma_prefetch2d(&p.wqkv, a * kD + (8 + c) * 64, ((r + 12) & 15) * 64);
          if (q.j >> 1 == rp + 8) tma_prefetch2d(&p.wo, (c * 2 + rank) * 64, (q.j & 15) * 64);
        }
        if (r < 6) tma_prefetch2d(rp == 1 ? &p.wu : &p.wg, (c * 7 + 3 + (rp >> 1)) * 64, (c * 2 + rank) * 64);
#pragma unroll 1
        for (Ring<1> q(sb, 16384 + rank * 8192); q.j < 16; q.next()) {
          q.acquire_first();
          mbar_expect_tx(q.bar(), 16384);
          tma2d_mc(q.dst(), &p.wo, (c * 2 + rank) * 64, g2_block(q.j, c) * 64, q.bar());
        }
        const CUtensorMap* mine = rank ? &p.wu : &p.wg;
#pragma unroll 1
        for (Ring<2> q(sb, 16384); q.j < 64; q.next()) {
          const int tile = g3_tile(q.j), f0 = c * 7 + (tile & 1) * 3, fp = f0 + (tile & 2);
          const int k0 = g3_block(q.j, c) * 64;
          q.acquire_first();
          mbar_expect_tx(q.bar(), 24576);
          const uint32_t dst = q.j < 4 ? sb + kRing + (q.j + 1) * 32768 : q.dst();
          tma2d_mc(dst + rank * 8192, mine, fp * 64, k0, q.bar());
          if ((q.j & 1) == rank) tma2d_mc(dst + 16384, tile & 2 ? &p.wu : &p.wg, (f0 + 1) * 64, k0, q.bar());
          const int d = q.j - kPfStep - (c & 1) * 5 - (r >> 2);
          if (d == 0 || d == 11 || d == 22) {
            const int f = c * 7 + (d == 0 ? 2 : d == 11 ? 5 : 6);
            tma_prefetch2d(&p.wg, f * 64, r * 64);
            tma_prefetch2d(&p.wu, f * 64, r * 64);
            if (d != 22) tma_prefetch2d(&p.wu, (f - 1) * 64, r * 64);
            else if (rp < kTail) tma_prefetch2d(&p.wd, (c * 2 + rank) * 64, rp * (7 * 64));
          }
          if (q.j >> 1 == rp + 24) tma_prefetch2d(&p.wd, (c * 2 + rank) * 64, g4_block(q.j & 15) * 64);
        }
        Ring<3> q(sb, 16384 + rank * 8192);
#pragma unroll 1
        for (; q.j < 16; q.next()) {
          q.acquire_first();
          mbar_expect_tx(q.bar(), 16384);
          tma2d_mc(q.dst(), mine, (c * 7 + 6) * 64, ((q.j + 9) & 15) * 64, q.bar());
          if (q.j >> 1 == rp) tma_prefetch2d(&p.wd, (c * 2 + rank) * 64, g4_block(q.j + 16) * 64);
        }
#pragma unroll 1
        for (int wv = 0; wv < 6; wv++) {
          const int dbl = wv == 2 || wv == 3, f0 = wv == 4 ? 6 : wv == 5 ? 0 : (wv & 1) * 3 + dbl;
#pragma unroll 1
          for (int i = wv ? 0 : kTail; i < (wv == 5 ? kTail - 1 : 8 << dbl); i++, q.next()) {
            q.acquire();
            mbar_expect_tx(q.bar(), 16384);
            tma2d_mc(q.dst(), &p.wd, (c * 2 + rank) * 64, ((i >> dbl) * 7 + f0 + (i & dbl)) * 64, q.bar());
            if ((q.j & 15) >> 1 == rp && q.j < 40 + kTail) tma_prefetch2d(&p.wd, (c * 2 + rank) * 64, g4_block(q.j + 16) * 64);
          }
        }
      }
    } else {
      const int cw = pw - 2;
      const uint32_t stg = sb + kStage + cw * 32768, rb = sb + kBars + 8 * kResBar;
      uint32_t land_par = 0;
      if (cw == 0) {
#pragma unroll 1
        for (int i = 0; i < 16; i++) sts128(sb + kFill + i * 512 + (tid & 31) * 16, make_uint4(kPoison, kPoison, kPoison, kPoison));
        __nanosleep(kSampleNs);
        const uint32_t l15 = tid & 15;
        const uint4 os = __ldg(p.wop + ((tid & 31) * 128 + c * 16 + l15));
        const uint4 gs = __ldg((tid & 16 ? p.wup : p.wgp) + (l15 * 451 + c * 56));
        const uint4 ws = __ldg((const uint4*)wqkvp + ((tid & 7) * 385 + (tid & 24) * 16 + (8 + c) * 8));
        sts64(sb + kScale, __float_as_uint(low_peak(os) * kBias3 * low_peak(gs)), __float_as_uint(low_peak(ws) * kBias1) | 1);
        if (tid == 320) TS(93);
      }
#pragma unroll 1
      for (int ev = -1; ev < 4; ev++) {
        const bool quads = cw == 0 && ev == 1;
        if (ev >= cw && !quads) nb_sync(kNbPub + cw, 160);
        if (ev >= cw && elect_one()) {
          if (quads) {
            mbar_wait(sb + kBars + 8 * (kHalfBar + 1), 0);
#pragma unroll 1
            for (int i = 0; i < 2; i++) {
              __nanosleep(i ? kPaceNs : kHoldNs);
              tma_store2d(&p.hst, stg + 16384 + i * 8192, c * 128 + 64, r * 128 + i * 64);
              TS(100 + i);
            }
            bulk_commit();
            bulk_wait_read();
            mbar_arrive(sb + kBars + 8 * kStgBar);
          } else {
            const int it = ev - 2 + cw, f0 = c * 7 + (1 - cw) * 3, fp = it == 2 ? c * 7 + 6 : f0 + 2 * it;
            const bool is_o = ev == 0;
            const CUtensorMap* m = is_o ? &p.ost : &p.hhst;
            const int b0 = is_o ? c : f0 + 1, b1 = fp;
#pragma unroll 1
            for (int i = is_o || it == 1 ? 0 : 2; i < (is_o ? 2 : 4); i++) {
              tma_store2d(m, stg + i * 8192, (i < 2 ? b0 : b1) * 64, r * 128 + (i & 1) * 64);
              if (!is_o) {
                bulk_commit();
                bulk_wait_read();
                __nanosleep(kPaceNs);
              }
            }
            bulk_commit();
            bulk_wait_all();
            mbar_arrive(sb + kBars + 8 * (kStgBar + cw));
            flag_signal(sc->flags + kFlHH + ev * 2 - 3 + cw + r * kFlRow);
            TS(44 + cw * 8 + ev);
            if (ev == 2 && cw) {
              mbar_expect_tx(rb, 32768);
#pragma unroll 1
              for (int i = 0; i < 2; i++) tma2d(stg + i * 16384, &p.h, c * 128 + i * 64, r * 128, rb);
            }
          }
        }
        nb_sync(kNbSelf + cw, 32);
        if (ev >= 2 && ev + cw >= 3 && elect_one()) {
          const int wv = cw == 0 ? 3 : ev == 2 ? 0 : 4;
#pragma unroll 1
          for (int i = wv; i <= max(wv, 2); i++) flag_wait(sc->flags + kFlHH + i + r * kFlRow, ep * 8);
          fence_async();
          mbar_arrive(sb + kBars + 8 * (kWaveBar + (wv >> 1)));
          if (wv == 4) {
            flag_wait(sc->flags + kFlPart + (c >> 1) + (r & 12) * kFlRow, ep);
            fence_async();
            mbar_expect_tx(sb + kBars + 8 * kPartBar, 16384);
#pragma unroll 1
            for (int i = 0; i < 2; i++) {
              asm volatile("cp.async.bulk.shared::cluster.global.mbarrier::complete_tx::bytes [%0], [%1], 8192, [%2];"
                           ::"r"(stg + i * 8192), "l"(sc->part + bid * 1024 + i * 512), "r"(sb + kBars + 8 * kPartBar) : "memory");
              __nanosleep(kPartNs);
            }
            TSK(56);
          }
        }
        nb_sync(kNbSelf + cw, 32);
#pragma unroll 1
        for (int sub = 0; ev < 3 && (ev != 0 || cw == 1); sub++) {
          nb_sync(kNbSelf + cw, 32);
          if (ev == 0) check_blocks(p, sc, sb, r, c, sub, land_par);
          const int u = ev < 0 ? cw : 2 * ev + 1 + cw, lane = fresh_tid() & 31;
          if (u == 1 && !sub) {
            uint3 st[5];
            load_tagged<5, true>(st, sc->stat1 + r * 128 + lane, 32, ep, (r < 2 ? -8 : -264) - (lane & 24));
#pragma unroll
            for (int i = 0; i < 4; i++) sts64(sb + kStat + (i * 32 + lane) * 8, st[i].x, st[i].y);
            sts64(sb + kStat - 64 + (lane & 7) * 8, st[4].x, st[4].y);
            nb_sync(kNbSelf + cw, 32);
            if (lane < 4) mbar_arrive(sb + kBars + 8 * kStatBar);
            if (lane == 0) TS(17);
          }
          if (u == 1) {
            const uint4* gh = sc->halo + ((sub * 16 + r - 2) * 8 + c) * 192 + lane;
            uint4 hv[6] = {};
            nb_sync(kNbHalo, 64);
            uint32_t ns = sub ? kHaloNs : 2 * kBackoffNs;
#pragma unroll 1
            for (int spins = 0; r >= 2; spins++) {
              if (ns) __nanosleep(ns);
              ns = sub ? 0 : kBackoffNs;
              if (spins > 2000000) __trap();
#pragma unroll
              for (int i = 0; i < 6; i++) hv[i] = ld_b128(gh + i * 32);
              uint32_t bad = (hv[5].y ^ ep) | (hv[5].z ^ ep);
#pragma unroll
              for (int i = 0; i < 6; i++) bad |= hv[i].w ^ ep;
              if (!__any_sync(~0u, bad != 0)) break;
            }
            const uint32_t dst = sb + kStage + sub * 32768 + lane * 16;
            sts128(dst, make_uint4(hv[0].x, hv[0].y, hv[0].z, hv[1].x));
            sts128(dst + 512, make_uint4(hv[1].y, hv[1].z, hv[2].x, hv[2].y));
            sts128(dst + 1024, make_uint4(hv[2].z, hv[3].x, hv[3].y, hv[3].z));
            sts128(dst + 1536, make_uint4(hv[4].x, hv[4].y, hv[4].z, hv[5].x));
            nb_arrive(kNbHalo + 1, 64);
            if (lane == 0) TS(123 + sub);
          }
          if (sub) break;
          uint3 v[3];
          load_tagged<3, false>(v, sc->cs + c * 96 + (u * 768 + lane), 32, ep);
          if (u < 2) {
#pragma unroll
            for (int i = 0; i < 3; i++)
#pragma unroll
              for (int k = 0; k < 8; k++)
                sts32(sb + kAug + cw * 4096 + i * 1024 + k * 128 + ((lane * 4) ^ (k * 16)), k == 7 ? 0x3F803F80u : k == 4 || k == 6 ? v[i].z : k & 1 && k != 5 ? v[i].y : v[i].x);
            fence_async_smem();
          } else {
#pragma unroll
            for (int i = 0; i < 3; i++) sts64(sb + kCs + cw * 768 + (i * 32 + lane) * 8, v[i].x, v[i].y);
          }
          nb_sync(kNbSelf + cw, 32);
          if (lane == 0) { mbar_arrive(sb + kBars + 8 * (kAuxBar + cw)); TS(104 + u); }
        }
        nb_sync(kNbSelf + cw, 32);
        if (ev < 0 && cw == 0 && elect_one()) {
#pragma unroll 1
          for (int i = 0; i < 6; i++) {
            __nanosleep(i == 0 ? (c >> 1) * (kFillNs / 4) : kFillNs);
            tma_store2d(i < 2 ? &p.ost : &p.hst, sb + kFill, i < 2 ? (8 + c) * 64 : (c * 2 - 1 + (i >> 1)) * 64, r * 128 + (i & 1) * 64);
            bulk_commit();
          }
          uint32_t peer;
          asm volatile("ld.shared::cluster.b32 %0, [%1];" : "=r"(peer) : "r"(map_cta(sb + kRole, rank ^ 1)) : "memory");
          if (peer != (bid ^ 8)) __trap();
          TS(90);
        }
        nb_sync(kNbSelf + cw, 32);
      }
    }
  } else {
    if (tid == 0) TSS(2);
    cluster_arrive();
    float bias = 0.f;
    float sx = 0.f, mx = 0.f;
    asm volatile("setmaxnreg.inc.sync.aligned.u32 232;");
    if (tid == 0) TSS(4);
    int task;
    asm volatile("mov.u32 %0, %1;" : "=r"(task) : "r"(8 - wg));

#pragma unroll 1
    for (task = __shfl_sync(~0u, task, 0);; task++) {
      if (task == 1 + wg || task == 9 - wg) {
        const int t = fresh_tid();
        uint2 scale;
        do asm volatile("ld.volatile.shared.v2.b32 {%0, %1}, [%2];" : "=r"(scale.x), "=r"(scale.y) : "r"(sb + kScale) : "memory");
        while (scale.y == 0);
        __syncwarp();
        bias = bias_at(low_peak(lds128(sb + (task > 5 ? kRing : kStage + wg * 32768) + (t & 126) * 64 + (t & 14) * 8 + (t & 1) * 8192)) *
                       __uint_as_float(task > 5 ? scale.y : scale.x));
        if (t == 128 && task > 5) TS(95);
      }
      if (wg == 0 && (task == 1 || task == 4)) {
        float acc[2][96];
        const int t = fresh_tid() & 127;
        const uint32_t frag = sb + kOwn + ((t >> 5) * 16 + (t & 15)) * 128, frag_x = ((t >> 4) & 1) ^ (t & 7);
        TSG(2);
        if (task == 4) mbar_wait(sb + kBars + 8 * kResBar, 0);
#pragma unroll
        for (int i = 0; i < 16; i++) {
          uint32_t v[4];
          ldsm4(frag + (i >> 3) * 16384 + (i & 1) * 8192 + ((frag_x ^ (i & 6)) << 4), v);
#pragma unroll
          for (int e = 0; e < 4; e++) {
            float* d = &acc[i & 1][8 * (i >> 1) + 2 * e];
            asm("shl.b32 %0, %1, 16;" : "=f"(d[0]) : "r"(v[e]));
            asm("and.b32 %0, %1, 0xFFFF0000;" : "=f"(d[1]) : "r"(v[e]));
          }
        }
        __syncwarp();
        if ((t & 31) == 0) mbar_arrive(sb + kBars + 8 * kResFreeBar);
        TSG(4);
        if ((tid & 127) == 0) TS(task == 1 ? 6 : 14);
        if (task == 4) {
          mainloop<128, kTail>(sc, acc, sb, 3, 16, 56, -2, true, false, false, 0, -1, &p.out, c * 128, (r >> 1) * 128, warp, outp);
          if ((tid & 127) == 0) TSK(15);
          if (fresh_tid() == 0) {
            if (bid == 0) __stcg(sc->epoch, lds32(sb + kEpoch));
            TSK(19);
          }
          break;
        }
        mainloop<128, -1>(sc, acc, sb, 1, 0, 15, kPauseG2, false, true, false, 0);
        const int t2 = fresh_tid() & 127;
        const uint32_t frag2 = sb + kStage + ((t2 >> 5) * 16 + (t2 & 15)) * 128, frag2_x = ((t2 >> 4) & 1) ^ (t2 & 7);
        const uint32_t empty = map_cta(sb + kBars + 8 * (ring_base(1) + 5), t2 & 1);
        mbar_wait(sb + kBars + 8 * kStgBar, 0);
        mbar_wait(sb + kBars + 8 * ring_base(1), 1);
#pragma unroll
        for (int m = 0; m < 2; m++) {
          const uint32_t a = desc_lo(sb + kRing, 16);
          wg_fence();
#pragma unroll
          for (int k = 0; k < 4; k++) wgmma_n128(acc[m], desc_kept(a, sb) + (m * 512 + k * 2), desc_kept(a, sb) + (kToB + k * 128));
          wg_commit();
          if (m) nb_arrive(kNbOrder + 1, 256);
          wg_wait<1>();
          if (!m) mbar_arrive_cluster_if(empty + 8 * 4, (t2 & 31) < 2);
        }
#pragma unroll
        for (int b = 0; b < 4; b++) {
          if (b == 1) {
            wg_wait<0>();
            if (t2 == 0) TSK(7);
          }
          if (b < 2) {
#pragma unroll
            for (int i = 0; i < 64; i++) asm volatile("" : "+f"(acc[b][i])::"memory");
          }
          stage_quarter(&acc[b & 1][32 * (b >> 1)], frag2, frag2_x, b);
          if (b & 1) {
            fence_async_smem();
            __syncwarp();
            if (elect_one()) {
              mbar_arrive(sb + kBars + 8 * (kHalfBar + (b >> 1)));
#pragma unroll
              for (int m = 0; m < 2; m++)
                if (b == 1) tma_store2d(&p.h16, sb + kStage + m * 8192 + warp * 2048, c * 128, r * 128 + m * 64 + warp * 16);
            }
            __syncwarp();
          }
        }
        if (t2 == 0) TS(8);
        sx = mx = 0.f;
        continue;
      }
      float acc[2][96];
      if (task == 8 + wg) {
        wg_fence();
#pragma unroll
        for (int m = 0; m < 2; m++) wgmma_n192_any(acc[m], desc(64 + m), desc(64 + m));
        wg_commit();
        wg_wait<0>();
#pragma unroll
        for (int i = 0; i < 96; i++) asm volatile("" : "+f"(acc[0][i]), "+f"(acc[1][i])::"memory");
      } else {
        const uint32_t z = fresh_tid() >> 10;
#pragma unroll
        for (int i = 0; i < 96; i++) {
#pragma unroll
          for (int m = 0; m < 2; m++) {
            if ((2 * i + m) % kInitMix == kInitMix - 1) asm("fma.rn.f32 %0, %1, %2, %3;" : "=f"(acc[m][i]) : "f"(__uint_as_float(z)), "f"(2 * i + m + 2.f), "f"(bias));
            else asm("{\n.reg .b32 t;\nlop3.b32 t, %1, %2, %3, 0xEA;\nmov.b32 %0, t;\n}\n" : "=f"(acc[m][i]) : "r"(z), "r"(2 * i + m + 1), "r"(__float_as_uint(bias)));
          }
        }
      }
      if (task > 5) {
      if (wg) {
        if (task == 7) cluster_wait();
        if (tid == 128 && task == 7) { TSS(5); TSK(69); }
        const int t = fresh_tid() & 127, lr = c * 16 + (t >> 3);
        uint32_t pf = t < 64 ? (bid * 16 + (t >> 2)) * kD + (t & 3) * 64 : (r * 48 + t - 64) * kD + c * 64;
        const uint32_t src = sb + kRing + lr * 128 + (((t ^ lr) & 7) << 4), empty = map_cta(sb + kBars + 8 * 4, t & 1), zero = fresh_tid() >> 10;
#pragma unroll 1
        for (int j = task == 7 ? 0 : kSplit; j < (task == 7 ? kSplit : 16); j++) {
          mbar_wait(sb + kBars + 8 * (j & 3), (j >> 2) & 1);
          if (j < 2 && t == 0) TS(102 + j);
          const uint4 v = lds128(src + (j >> 1 == c ? kOwn + (j & 1) * 16384 : (j & 3) * 40960));
          __syncwarp();
          mbar_arrive_cluster_if(empty + 8 * (j & 3) + (v.x & zero), (t & 31) < 2);
          if ((j == 0 || j == 3 || j == 6) && t < 112) { pf += t < 64 ? 256 : 256 * 3 * kD; prefetch_l2((t < 64 ? xp : wqkvp) + pf); }
          const uint32_t u[4] = {v.x, v.y, v.z, v.w};
#pragma unroll
          for (int e = 0; e < 4; e++) {
            const float d0 = bf_lo(u[e]), d1 = bf_hi(u[e]);
            sx += d0 + d1;
            mx = fmaf(d1, d1, fmaf(d0, d0, mx));
          }
        }
        if (task == 7) {
          if (t == 0) TS(96);
          continue;
        }
#pragma unroll
        for (int o = 4; o > 0; o >>= 1) { sx += __shfl_xor_sync(~0u, sx, o); mx += __shfl_xor_sync(~0u, mx, o); }
        const float mean = sx * (1.f / kD);
        float rstd;
        asm("rsqrt.approx.ftz.f32 %0, %1;" : "=f"(rstd) : "f"(fmaxf(mx * (1.f / kD) - mean * mean, 0.f) + 1e-5f));
        const uint32_t ep = lds32(sb + kEpoch);
        const int t2 = fresh_tid();
        if ((t2 & 7) == 0) st_b128(sc->stat1 + (bid * 16 + (t2 >> 3 & 15)), __float_as_uint(rstd), __float_as_uint(-mean), ep, ep);
        if (t == 0) TS(16);
      }
      if (tid == 0) TSS(6);
      mainloop<192, -1>(sc, acc, sb, 0, wg * 16, wg ? 16 - kAhead : 16, wg ? kPauseG1 : -2, false, wg == 0, false, wg,
                        wg ? min((c + 2) & 7, 6) : c);
      const int t = fresh_tid() & 127, w = warp & 3, lane = t & 31, g = lane >> 2, q = lane & 3;
      const uint32_t stg = sb + kStage + wg * 32768;
      auto tail = [&](int m, int k0, int k1) {
        wg_fence();
#pragma unroll
        for (int k = k0; k < k1; k++) {
          const uint64_t a = desc_kept(desc_lo(sb + kRing, 16), sb) + (4 - kAhead + (k >> 2)) * (40960 >> 4);
          wgmma_n192(acc[m], a + (m * 512 + (k & 3) * 2), a + (kToB + (k & 3) * 128));
        }
      };
      auto release = [&](int j, bool cond) { mbar_arrive_cluster_if(map_cta(sb + kBars + 8 * (4 + (j & 3)), lane & 1), cond); };
      if (wg) {
#pragma unroll
        for (int j = 32 - kAhead; j < 32; j++) {
          TST(2 * (j & 1));
          mbar_wait(sb + kBars + 8 * (j & 3), 1);
          TST(2 * (j & 1) + 1);
          tail(1, 4 * (j - 32 + kAhead), 4 * (j - 31 + kAhead));
          wg_commit();
          if (j == 32 - kAhead) {
            wg_wait<1>();
            release(j - 1, lane < 4);
            mbar_wait(sb + kBars + 8 * kResFreeBar, 0);
          }
        }
      } else {
        nb_arrive(kNbOrder + 1, 256);
        wg_wait<0>();
        release(15, lane < 2);
        if (t == 0) TSK(1);
      }
      TST(4);
      mbar_wait(sb + kBars + 8 * (kAuxBar + wg), 0);
      mbar_wait(sb + kBars + 8 * kStatBar, 0);
      {
        uint32_t am[4];
#pragma unroll
        for (int i = 0; i < 4; i++) {
          const float m1 = __uint_as_float(lds32(sb + kStat + (w * 16 + g) * 8 + 4 + (i >> 1) * 512 + (i & 1) * 64));
          const float m2 = bf_rest(m1), lo = q & 1 ? m2 : m1;
          am[i] = bf_upper(lo, q == 3 ? -bias : q == 2 ? bf_rest(m2) : lo);
        }
        const uint64_t db = (uint64_t)desc_lo(sb + kAug + wg * 4096, 1024) | (0x40000000ull << 32);
        TST(5);
        wg_fence();
        wgmma_n192_rs(acc[1], am[2], am[3], 0u, db);
        wg_commit();
        TST(6);
        wg_fence();
        wgmma_n192_rs(acc[0], am[0], am[1], 0u, db);
        wg_commit();
        if (wg) {
          tail(0, 0, 4 * kAhead);
          wg_commit();
          wg_wait<2>();
        } else {
          wg_wait<1>();
        }
        TST(8);
#pragma unroll
        for (int i = 0; i < 96; i++) asm volatile("" : "+f"(acc[1][i])::"memory");
      }
      const uint32_t ep = lds32(sb + kEpoch);
      uint32_t pk[2][48];
      auto fold = [&](int pp, int jn, int hf) {
        const uint32_t v = pack_bf16(acc[pp][4 * jn + 2 * hf], acc[pp][4 * jn + 2 * hf + 1]);
        pk[pp][2 * jn + hf] = jn >= 16 ? movm(v) : v;
      };
      if (t == 96) TS(115 + wg);
#pragma unroll
      for (int jn = 8; jn < 24; jn++) fold(1, jn, 1);
      if (w < 3) {
#pragma unroll
        for (int i = 0; i < 4; i++)
          sts128(stg + (w + 5) * 2048 + i * 512 + lane * 16, make_uint4(pk[1][17 + 8 * i], pk[1][19 + 8 * i], pk[1][21 + 8 * i], pk[1][23 + 8 * i]));
      } else if (r < 14) {
        uint4* gh = sc->halo + ((wg * 16 + r) * 8 + c) * 192 + lane;
#pragma unroll
        for (int i = 0; i < 6; i++) st_b128(gh + i * 32, pk[1][17 + 6 * i], i < 5 ? pk[1][(19 + 6 * i) % 48] : ep, i < 5 ? pk[1][(21 + 6 * i) % 48] : ep, ep);
        if (wg == 0) {
#pragma unroll 1
          for (int i = 0; i < 6; i++, gh += 32) st_b128(gh + 128 * 192, 0, 0, 0, ep - 1);
        }
      }
      if (w == 3) nb_arrive(kNbHalo, 64);
      if (wg) nb_arrive(kNbOrder, 256);
      TST(9);
      if (t == 96) TS(111 + wg);
#pragma unroll
      for (int jn = 23; jn >= 0; jn--) {
        fold(1, jn, 0);
        if (jn < 8) fold(1, jn, 1);
      }
      const bool sel0 = 2 * q > g, sel1 = 2 * q + 1 > g, no_prev = (r < 2 && w == 0);
      const uint4 ones = lds128(sb + kOnes);
      const uint32_t lowmask = (sel0 ? 0x0000FFFFu : 0u) | (sel1 ? 0xFFFF0000u : 0u) | ones.y;
      float rs[4][2], rk[4][2];
#pragma unroll
      for (int i = 0; i < 4; i++) {
        const uint32_t a = sb + kStat + w * 128 + (i >> 1) * 512 + (i & 1) * 64;
        const float rq = __uint_as_float(lds32(a + g * 8)) * (0.17677669529663687f * 1.4426950408889634f);
        rk[i][0] = __uint_as_float(lds32(a + q * 16 - (sel0 ? 64 : 0)));
        rk[i][1] = __uint_as_float(lds32(a + q * 16 + 8 - (sel1 ? 64 : 0)));
        rs[i][0] = rk[i][0] * rq;
        rs[i][1] = rk[i][1] * rq;
      }
      {
        uint32_t all = ~0u;
#pragma unroll
        for (int i = 0; i < 48; i++) if (i < 16 || !(i & 1)) all &= pk[1][i];
        if (all == kPoison) sts32(sb + kZero + 8, 0);
      }
      TST(10);
      wg_wait<0>();
      TST(11);
#pragma unroll
      for (int j = 32 - kAhead; j < 32; j++) release(j, lane < 4 * wg && (w != 0 || j < 31));
#pragma unroll
      for (int i = 0; i < 96; i++) asm volatile("" : "+f"(acc[0][i])::"memory");
      if (t == 0 && wg) TSK(21);
#pragma unroll
      for (int jn = 8; jn < 24; jn++) fold(0, jn, 1);
#pragma unroll
      for (int i = 0; i < 4; i++)
        sts128(stg + (w + 1) * 2048 + i * 512 + lane * 16, make_uint4(pk[0][17 + 8 * i], pk[0][19 + 8 * i], pk[0][21 + 8 * i], pk[0][23 + 8 * i]));
#pragma unroll
      for (int jn = 23; jn >= 0; jn--) {
        fold(0, jn, 0);
        if (jn < 8) fold(0, jn, 1);
      }
      if (t == 0) TS(113 + wg);
      nb_sync(kNbWg + wg, 128);
      uint32_t hal[2][16];
      auto load_halo = [&](int m) {
#pragma unroll
        for (int i = 0; i < 4; i++) {
          const uint4 v = lds128(stg + w * 2048 + m * 8192 + i * 512 + lane * 16);
          uint32_t* h = &hal[m][i * 4];
          h[0] = v.x; h[1] = v.y; h[2] = v.z; h[3] = v.w;
        }
      };
      load_halo(1);
      if (w == 0) {
        nb_sync(kNbHalo + 1, 64);
        release(31, lane < 4 * wg);
      }
      load_halo(0);
      __syncwarp();
      if (t == 0) TS(2 + wg * 20);
      {
        uint32_t all = lowmask;
#pragma unroll
        for (int i = 0; i < 32; i++) if (i < 16 || !(i & 1)) all &= pk[0][i];
#pragma unroll
        for (int i = 0; i < 8; i++) all &= __float_as_uint(rs[i >> 1][i & 1]);
        if (all == kPoison) sts32(sb + kZero + 8, 0);
      }
      nb_sync(kNbWin, 256);
      if (t == 0) TS(9 + wg * 20);
      const uint32_t zero = lds32(sb + kZero);
      float s0[4][4], s1[4][4], s2[4][4];
#pragma unroll
      for (int k = 0; k < 4; k++) {
        pk[k >> 1][8 * (k & 1)] |= zero;
#pragma unroll
        for (int e = 0; e < 4; e++) s0[k][e] = s1[k][e] = s2[k][e] = 0.f;
      }
#pragma unroll
      for (int ks = 0; ks < 2; ks++)
#pragma unroll
        for (int k = 0; k < 4; k++) {
          const uint32_t* qf = &pk[k >> 1][8 * (k & 1) + 4 * ks];
          const uint32_t* kf = &pk[k >> 1][16 + 8 * (k & 1) + 4 * ks];
          const uint32_t* hf = &hal[k >> 1][4 * (k & 1) + 2 * ks];
          mma16816(s0[k], qf[0], qf[1], qf[2], qf[3], hf[0], hf[1]);
          mma16816(s1[k], qf[0], qf[1], qf[2], qf[3], kf[0], kf[2]);
          mma16816(s2[k], qf[0], qf[1], qf[2], qf[3], kf[1], kf[3]);
        }
      float ea[4][2], eb[4][2], ma[4], mb[4];
#pragma unroll
      for (int k = 0; k < 4; k++) {
        const float *ra = rs[k & 2], *rb = rs[(k & 2) + 1];
        if (no_prev && k < 2) s0[k][0] = s0[k][1] = -INFINITY;
        ea[k][0] = (sel0 ? s0[k][0] : s1[k][0]) * ra[0]; ea[k][1] = (sel1 ? s0[k][1] : s1[k][1]) * ra[1];
        eb[k][0] = (sel0 ? s1[k][2] : s2[k][2]) * rb[0]; eb[k][1] = (sel1 ? s1[k][3] : s2[k][3]) * rb[1];
        ma[k] = fmaxf(ea[k][0], ea[k][1]); mb[k] = fmaxf(eb[k][0], eb[k][1]);
      }
#pragma unroll
      for (int o = 1; o < 4; o <<= 1)
#pragma unroll
        for (int k = 0; k < 4; k++) {
          ma[k] = fmaxf(ma[k], __shfl_xor_sync(~0u, ma[k], o));
          mb[k] = fmaxf(mb[k], __shfl_xor_sync(~0u, mb[k], o));
        }
      float ov[4][4][4], ls[4][4];
      uint32_t all = 0;
#pragma unroll
      for (int k = 0; k < 4; k++) {
        const float *ra = rk[k & 2], *rb = rk[(k & 2) + 1];
        ea[k][0] = ex2(ea[k][0] - ma[k]); ea[k][1] = ex2(ea[k][1] - ma[k]);
        eb[k][0] = ex2(eb[k][0] - mb[k]); eb[k][1] = ex2(eb[k][1] - mb[k]);
        const uint32_t pa = pack_bf16(ea[k][0] * ra[0], ea[k][1] * ra[1]), pb = pack_bf16(eb[k][0] * rb[0], eb[k][1] * rb[1]);
        const uint32_t* vf = &pk[k >> 1][32 + 8 * (k & 1)];
        const uint32_t* hf = &hal[k >> 1][8 + 4 * (k & 1)];
#pragma unroll
        for (int d2 = 0; d2 < 2; d2++) {
#pragma unroll
          for (int e = 0; e < 4; e++) ov[k][d2][e] = ov[k][2 + d2][e] = 0.f;
          mma1688(ov[k][d2], hf[2 * d2], hf[2 * d2 + 1], pa & lowmask);
          mma1688(ov[k][2 + d2], vf[4 * d2], vf[4 * d2 + 2], pb & lowmask);
        }
#pragma unroll
        for (int d2 = 0; d2 < 2; d2++) {
          mma1688(ov[k][d2], vf[4 * d2], vf[4 * d2 + 2], pa & ~lowmask);
          mma1688(ov[k][2 + d2], vf[4 * d2 + 1], vf[4 * d2 + 3], pb & ~lowmask);
        }
        ls[k][0] = ls[k][1] = ls[k][2] = ls[k][3] = 0.f;
        mma16816(ls[k], ones.x, ones.y, ones.z, ones.w, pack_bf16(ea[k][0], ea[k][1]), pack_bf16(eb[k][0], eb[k][1]));
        if (k >= kDone) all |= pa & pb;
      }
#pragma unroll
      for (int k = 0; k < 4; k++) {
        if (k == kDone) {
          if (all == 0xFFFFFFFFu) sts32(sb + kZero + 8, 0);
          nb_arrive(kNbWin + 1, 256);
          all = 0;
        }
        all |= (__float_as_uint(ov[k][0][0]) & __float_as_uint(ov[k][1][0]) & __float_as_uint(ov[k][2][0])) &
               (__float_as_uint(ov[k][3][0]) & __float_as_uint(ls[k][0]));
      }
      const uint32_t nil = lds32(sb + kZero);
      const uint32_t frag = stg + (w * 16 + (lane & 15)) * 128, frag_x = (lane >> 4) ^ (lane & 7);
      uint32_t after = all;
#pragma unroll
      for (int k = 0; k < 4; k++) {
        uint32_t h[2][4];
#pragma unroll
        for (int hf = 0; hf < 2; hf++) {
          const float i0 = rcp(__uint_as_float(__float_as_uint(ls[k][2 * hf]) | (after & nil)));
          const float i1 = rcp(__uint_as_float(__float_as_uint(ls[k][2 * hf + 1]) | (after & nil)));
#pragma unroll
          for (int e = 0; e < 4; e++) h[e >> 1][2 * (e & 1) + hf] = pack_bf16(ov[k][2 * hf + (e >> 1)][2 * (e & 1)] * i0, ov[k][2 * hf + (e >> 1)][2 * (e & 1) + 1] * i1);
          after = h[0][hf];
        }
#pragma unroll
        for (int d2 = 0; d2 < 2; d2++) stsm4_t(frag + (k >> 1) * 8192 + ((frag_x ^ ((k & 1) * 4 + d2 * 2)) << 4), h[d2][0], h[d2][1], h[d2][2], h[d2][3]);
      }
      fence_async_smem();
      if (wg) {
        __syncwarp();
        if (elect_one()) {
          tma_store2d(&p.o16, stg + w * 2048, (8 + c) * 64, r * 128 + w * 16);
          tma_store2d(&p.o16, stg + 8192 + w * 2048, (8 + c) * 64, r * 128 + 64 + w * 16);
          bulk_commit();
          bulk_wait_read();
          mbar_arrive(sb + kBars + 8 * kSentBar);
        }
        __syncwarp();
      } else {
        nb_arrive(kNbPub, 160);
      }
      if (t == 0) TS(3 + wg * 20);
      task = wg;
      sx = mx = bias = 0.f;
      continue;
      }

      {
#pragma unroll 1
        for (int part = task != 2; part < 2; part++) {
          if ((tid & 127) == 0) TS(6 + 2 * task + wg * 20);
          if (task + part == 5) {
            mainloop<128, 0>(sc, acc, sb, 3, 0, 16, -2, false, true, false, 1);
            continue;
          }
          const int j0 = task == 3 ? 48 - wg * 16 : part == 0 ? 2 - 2 * wg : 18 - 14 * wg;
          mainloop<192, 0>(sc, acc, sb, 2, j0, task != 2 ? 16 : part == 0 ? 2 : 14, -2, false, true, part == 0, wg);
          if (part == 0 && wg == 0) {
            const int t = fresh_tid() & 127;
            const uint32_t ep = lds32(sb + kEpoch);
            {
              float s = 0.f, ss = 0.f;
#pragma unroll 1
              for (int i = 0; i < 16; i++) {
                const uint4 v = lds128(sb + kStage + t * 128 + (i >> 3) * 16384 + (((i ^ t) & 7) << 4));
                const uint32_t u[4] = {v.x, v.y, v.z, v.w};
#pragma unroll
                for (int e = 0; e < 4; e++) {
                  const float d0 = bf_lo(u[e]), d1 = bf_hi(u[e]);
                  s = (s + d0) + d1;
                  ss = fmaf(d1, d1, fmaf(d0, d0, ss));
                }
              }
              st_b128(sc->stat2 + c * kS + r * 128 + t, __float_as_uint(s), __float_as_uint(ss), ep, ep);
            }
            __nanosleep(kStatNs);
            float2 sum = make_float2(0.f, 0.f);
#pragma unroll 1
            for (int i = 0; i < 2; i++) {
              uint3 a[4];
              load_tagged<4, true>(a, sc->stat2 + i * 4 * kS + r * 128 + t, kS, ep);
              sum.x += (__uint_as_float(a[0].x) + __uint_as_float(a[1].x)) + (__uint_as_float(a[2].x) + __uint_as_float(a[3].x));
              sum.y += (__uint_as_float(a[0].y) + __uint_as_float(a[1].y)) + (__uint_as_float(a[2].y) + __uint_as_float(a[3].y));
            }
            const float mean = sum.x * (1.f / kD);
            sts64f(sb + kStat + t * 8, make_float2(fmaxf(sum.y * (1.f / kD) - mean * mean, 0.f) + 1e-5f, -mean));
            __syncwarp();
            if (elect_one()) {
              bulk_commit();
              bulk_wait_read();
              mbar_arrive(sb + kBars + 8 * kStatBar);
            }
            __syncwarp();
            if (t == 0) TS(37);
          }
        }
      }
      const int t = fresh_tid() & 127, w = warp & 3, lane = t & 31, g = lane >> 2, q = lane & 3;
      const uint32_t stg = sb + kStage + wg * 32768;
      uint32_t csv = sb + kCs + wg * 768 + q * 8;
      uint32_t statv = sb + kStat + (w * 16 + g) * 8;
      const uint32_t frag = stg + (w * 16 + (lane & 15)) * 128;
      const uint32_t frag_x = (lane >> 4) ^ (lane & 7);
      const uint32_t priv = stg + w * 2048 + lane * 16;
      if (t == 0) TSK(7 + 2 * task + wg * 20);

      if (task == 4) {
        mbar_wait(sb + kBars + 8 * (kAuxBar + 1), 1);
        mbar_wait(sb + kBars + 8 * kResFreeBar, 1);
        mbar_wait(sb + kBars + 8 * (kStgBar + 1), 0);
      }
      asm volatile("" : "+r"(csv), "+r"(statv)::"memory");

      {
#pragma unroll
        for (int i = 0; i < 96; i++) asm volatile("sub.f32 %0, %0, %1;" : "+f"(acc[0][i]) : "f"(bias));
#define NEXT(i) asm volatile("sub.f32 %0, %1, %2;" : "=f"(acc[0][i]) : "f"(acc[1][i]), "f"(bias))
#pragma unroll 1
        for (int pp = 0; pp < 2; pp++) {
          TSG(pp);
          RowConst rc[2];
#pragma unroll
          for (int hf = 0; hf < 2; hf++) {
            const float2 st = lds64f_const(statv + pp * 512 + hf * 64);
            float rstd;
            asm("rsqrt.approx.ftz.f32 %0, %1;" : "=f"(rstd) : "f"(st.x));
            rc[hf] = {st.y, 0.7978845608f * rstd, 0.0356774081f * rstd * rstd * rstd, 0.5f * rstd * rstd};
          }
#pragma unroll
          for (int j2 = 0; j2 < 4; j2++) {
            uint32_t hv[4];
#pragma unroll
            for (int jj = 0; jj < 2; jj++) {
              const int jn = 2 * j2 + jj;
              const float2 cg = lds64f_const(csv + jn * 32), cu = lds64f_const(csv + 256 + jn * 32);
#pragma unroll
              for (int hf = 0; hf < 2; hf++) {
                const float nm = rc[hf].nmean;
                const float g0 = fmaf(nm, cg.x, acc[0][4 * jn + 2 * hf]), g1 = fmaf(nm, cg.y, acc[0][4 * jn + 2 * hf + 1]);
                const float u0 = fmaf(nm, cu.x, acc[0][32 + 4 * jn + 2 * hf]), u1 = fmaf(nm, cu.y, acc[0][33 + 4 * jn + 2 * hf]);
                hv[2 * jj + hf] = pack_bf16(g0 * u0 * gate_scale(g0, rc[hf]), g1 * u1 * gate_scale(g1, rc[hf]));
              }
            }
            stsm4(frag + 16384 + pp * 8192 + ((frag_x ^ (j2 * 2)) << 4), hv[0], hv[1], hv[2], hv[3]);
          }
          if (task < 4) {
            if (task == 2) {
#pragma unroll
              for (int j2 = 0; j2 < 4; j2++) {
                uint32_t hv[4];
#pragma unroll
                for (int jj = 0; jj < 2; jj++) {
                  const int jn = 16 + 2 * j2 + jj;
                  const float2 cs = lds64f_const(csv + jn * 32);
#pragma unroll
                  for (int hf = 0; hf < 2; hf++) {
                    const float nm = rc[hf].nmean;
                    const float t0 = fmaf(nm, cs.x, acc[0][4 * jn + 2 * hf]), t1 = fmaf(nm, cs.y, acc[0][4 * jn + 2 * hf + 1]);
                    hv[2 * jj + hf] = pack_bf16(t0 * gate_scale(t0, rc[hf]), t1 * gate_scale(t1, rc[hf]));
                  }
                }
                sts128(priv + pp * 8192 + j2 * 512, make_uint4(hv[0], hv[1], hv[2], hv[3]));
              }
            } else {
              uint4 park[4];
#pragma unroll
              for (int j2 = 0; j2 < 4; j2++) park[j2] = lds128(priv + pp * 8192 + j2 * 512);
              __syncwarp();
#pragma unroll
              for (int j2 = 0; j2 < 4; j2++) {
                const uint32_t pv[4] = {park[j2].x, park[j2].y, park[j2].z, park[j2].w};
                uint32_t hv[4];
#pragma unroll
                for (int jj = 0; jj < 2; jj++) {
                  const int jn = 16 + 2 * j2 + jj;
                  const float2 cs = lds64f_const(csv + jn * 32);
#pragma unroll
                  for (int hf = 0; hf < 2; hf++) {
                    const float nm = rc[hf].nmean;
                    const float t0 = fmaf(nm, cs.x, acc[0][4 * jn + 2 * hf]), t1 = fmaf(nm, cs.y, acc[0][4 * jn + 2 * hf + 1]);
                    asm("mul.rn.bf16x2 %0, %1, %2;" : "=r"(hv[2 * jj + hf]) : "r"(pack_bf16(t0, t1)), "r"(pv[2 * jj + hf]));
                  }
                }
                stsm4(frag + pp * 8192 + ((frag_x ^ (j2 * 2)) << 4), hv[0], hv[1], hv[2], hv[3]);
              }
            }
            if (pp == 1) break;
#pragma unroll
            for (int i = 64; i < 96; i++) NEXT(i);
          }
          if (pp == 1) break;
#pragma unroll
          for (int i = 0; i < 64; i++) NEXT(i);
        }
      }
      fence_async_smem();
      nb_arrive(kNbPub + wg, 160);
      if (t == 0) TS(task == 4 ? 57 : 56 + task + wg * 2);
      if (task == 4) break;
      sx = mx = 0.f;
    }
  }
}

typedef CUresult (*EncodeTiledFn)(CUtensorMap*, CUtensorMapDataType, cuuint32_t, void*, const cuuint64_t*, const cuuint64_t*,
                                  const cuuint32_t*, const cuuint32_t*, CUtensorMapInterleave, CUtensorMapSwizzle,
                                  CUtensorMapL2promotion, CUtensorMapFloatOOBfill);

void encode(EncodeTiledFn fn, CUtensorMap* m, const void* base, int rank, cuuint64_t d0, cuuint64_t d1, cuuint64_t d2,
            cuuint64_t s1, cuuint64_t s2, cuuint32_t b2, cuuint32_t b1 = 64) {
  const cuuint64_t dims[3] = {d0, d1, d2}, strides[2] = {s1, s2};
  const cuuint32_t box[3] = {64, b1, b2}, es[3] = {1, 1, 1};
  fn(m, CU_TENSOR_MAP_DATA_TYPE_BFLOAT16, rank, const_cast<void*>(base), dims, strides, box, es, CU_TENSOR_MAP_INTERLEAVE_NONE,
     CU_TENSOR_MAP_SWIZZLE_128B, CU_TENSOR_MAP_L2_PROMOTION_L2_128B, CU_TENSOR_MAP_FLOAT_OOB_FILL_NONE);
}

}

extern "C" void kernel_launch(void* const* d_in, const int* in_sizes, int n_in, void* d_out, int out_size) {
  void* fnp = nullptr;
  cudaDriverEntryPointQueryResult qr;
  cudaGetDriverEntryPoint("cuTensorMapEncodeTiled", &fnp, cudaEnableDefault, &qr);
  EncodeTiledFn fn = (EncodeTiledFn)fnp;
  void *o, *h, *hh;
  cudaGetSymbolAddress(&o, g_o);
  cudaGetSymbolAddress(&h, g_h);
  cudaGetSymbolAddress(&hh, g_hh);

  Params p;
  Scratch* sc;
  cudaGetSymbolAddress((void**)&sc, g_scratch);
  encode(fn, &p.x, d_in[0], 3, kD, kS / 2, 2, 4 * kD, 2 * kD, 1, 128);
  encode(fn, &p.out, d_out, 3, kD, kS / 2, 2, 4 * kD, 2 * kD, 1, 16);
  encode(fn, &p.wqkv, d_in[1], 2, 3 * kD, kD, 1, 6 * kD, 0, 1);
  encode(fn, &p.wo, d_in[2], 2, kD, kD, 1, 2 * kD, 0, 1);
  encode(fn, &p.wd, d_in[6], 2, kD, kF, 1, 2 * kD, 0, 1);
  encode(fn, &p.wg, d_in[4], 2, kF, kD, 1, 2 * kF, 0, 1);
  encode(fn, &p.wu, d_in[5], 2, kF, kD, 1, 2 * kF, 0, 1);
  encode(fn, &p.o, o, 2, kD, kS, 1, 2 * kD, 0, 1, 128);
  encode(fn, &p.h, h, 2, kD, kS, 1, 2 * kD, 0, 1, 128);
  encode(fn, &p.hh, hh, 2, kF, kS, 1, 2 * kF, 0, 1, 128);
  encode(fn, &p.ost, o, 2, kD, kS, 1, 2 * kD, 0, 1);
  encode(fn, &p.o16, o, 2, kD, kS, 1, 2 * kD, 0, 1, 16);
  encode(fn, &p.h16, h, 2, kD, kS, 1, 2 * kD, 0, 1, 16);
  encode(fn, &p.hst, h, 2, kD, kS, 1, 2 * kD, 0, 1);
  encode(fn, &p.hhst, hh, 2, kF, kS, 1, 2 * kF, 0, 1);
  p.wop = (const uint4*)d_in[2];
  p.wgp = (const uint4*)d_in[4];
  p.wup = (const uint4*)d_in[5];

  int dev = 0, sms = 0;
  cudaGetDevice(&dev);
  cudaDeviceGetAttribute(&sms, cudaDevAttrMultiProcessorCount, dev);
  auto* kernel = sms == 132 ? fused_block_kernel<true> : fused_block_kernel<false>;
  cudaFuncSetAttribute(kernel, cudaFuncAttributeMaxDynamicSharedMemorySize, kSmemBytes);
  kernel<<<132, kThreads, kSmemBytes, cudaStreamPerThread>>>(sc, (const __nv_bfloat16*)d_in[0], (const __nv_bfloat16*)d_in[1],
                                                                  (__nv_bfloat16*)d_out, p);
}
```

```cpp
#include <cuda_runtime.h>
#include <cuda_bf16.h>
#include <cuda.h>
#include <stdint.h>

namespace {

constexpr int kS = 2048, kD = 1024, kF = 3584;
constexpr int kThreads = 384;

constexpr int kRing = 0;
constexpr int kStage = 163840;
constexpr int kAug = kStage + 16384;
constexpr int kOwn = kStage + 32768;
constexpr int kFill = kStage + 24576;
constexpr int kCs = kStage + 65536;
constexpr int kStat = kCs + 1536;
constexpr int kBars = kStat + 1024;
constexpr int kSmemBytes = kBars + 512;
constexpr int kResBar = 36;
constexpr int kAuxBar = 37;
constexpr int kStgBar = 39;
constexpr int kResFreeBar = 41;
constexpr int kStatBar = 42;
constexpr int kPartBar = 43;
constexpr int kWaveBar = 45;
constexpr int kHalfBar = 49;
constexpr int kSentBar = 51;
constexpr int kLandBar = 52;
constexpr int kNumBars = 58;
static_assert(kNumBars == 4 + 3 * 18, "barrier initialisation is split 4 + 3 x 18");
__host__ __device__ constexpr int bar_count(int i) {
  const int ph = i < 8 ? 0 : i < 18 ? 1 : i < 26 ? 2 : 3, base = ph * 9 - (ph & 1);
  return i < 36 ? (i - base < 4 + (ph & 1) ? 2 : ph == 0 ? 16 : 8) : i == kResFreeBar || i == kStatBar || (i >= kHalfBar && i < kLandBar) ? 4 : 1;
}
__host__ __device__ constexpr uint64_t bar_shifts(int first) {
  uint64_t m = 0;
  for (int i = 17; i >= 0; i--) {
    const int n = bar_count(first + i);
    m = m << 3 | (n == 16 ? 4 : n == 8 ? 3 : n >> 1);
  }
  return m;
}
constexpr int kScale = kBars + 464;
constexpr int kOnes = kBars + 480;
constexpr int kZero = kBars + 496;
constexpr int kRole = kBars + 508;
constexpr int kEpoch = kBars + 500;
__device__ __forceinline__ int ring_base(int ph) { return ph * 9 - (ph & 1); }
constexpr int kNbOrder = 1;
constexpr int kNbWg = 3;
constexpr int kNbPub = 5;
constexpr int kNbWin = 7;
constexpr int kNbSelf = 13;
constexpr int kNbPart = 11;
constexpr int kNbHalo = 9;

constexpr int kFlO = 0;
constexpr int kFlPace = 1;
constexpr int kFlHH = 3;
constexpr int kFlPart = 8;
constexpr int kFlRow = 32;
constexpr int kNumFlags = 16 * kFlRow;

constexpr int kPauseG1 = 7;
constexpr int kPauseG2 = 1;
constexpr int kAhead = 2;
constexpr int kTail = 5;
constexpr int kDone = 3;
constexpr int kQuietAt = 48;
constexpr int kPfStep = 8;
constexpr int kBackoffNs = 200;
constexpr int kPaceNs = 300;
constexpr int kPartNs = 150;
constexpr int kFillNs = 500;
constexpr int kHaloNs = 150;
constexpr int kGateONs = 150;
constexpr int kGateHNs = 150;
constexpr int kHoldNs = 1200;
constexpr float kBias1 = 512.f, kBias3 = 32768.f;
constexpr int kInitMix = 1000;
constexpr int kSplit = 13;
constexpr int kSampleNs = 1000;
constexpr int kStatNs = 1500;

struct Scratch {
  uint32_t flags[kNumFlags];
  uint32_t epoch[32];
  uint4 stat1[kS];
  uint4 stat2[8 * kS];
  uint4 cs[7 * 8 * 96];
  uint4 halo[2 * 16 * 8 * 6 * 32];
  uint4 part[128 * 8 * 128];
};
struct Params {
  CUtensorMap x, wqkv, o, wo, h, wg, wu, hh, wd, out;
  CUtensorMap ost, hst, hhst;
  CUtensorMap o16, h16;
  const uint4 *wop, *wgp, *wup;
};

__device__ __align__(256) __nv_bfloat16 g_o[kS * kD];
__device__ __align__(256) __nv_bfloat16 g_h[kS * kD];
__device__ __align__(256) __nv_bfloat16 g_hh[kS * kF];
__device__ __align__(256) Scratch g_scratch;

template <bool BY_SM>
__device__ __forceinline__ int role_id() {
  uint32_t sm;
  asm("mov.u32 %0, %%smid;" : "=r"(sm));
  const int tpc = (BY_SM ? sm : blockIdx.x) >> 1, rank = blockIdx.x & 1;
  if ((tpc | 1) == 61) return 8 + 2 * tpc + rank;
  const int u = tpc - 32, s7 = (u * 37) >> 8;
  const int g = tpc < 32 ? tpc & 7 : tpc < 60 ? 1 + u - 7 * s7 : 0, s = tpc < 32 ? tpc >> 3 : tpc < 60 ? 4 + s7 : tpc - 58;
  return (g * 2 + rank) * 8 + s;
}
#define TS(i) do { } while (0)
#define TSK(i) do { } while (0)
#define TSS(i) do { } while (0)
#define TST(i)
#define TSG(i)

__device__ __forceinline__ uint32_t smem_u32(const void* p) { return (uint32_t)__cvta_generic_to_shared(p); }
__device__ __forceinline__ void mbar_init(uint32_t bar, uint32_t cnt) {
  asm volatile("mbarrier.init.shared::cta.b64 [%0], %1;" ::"r"(bar), "r"(cnt));
}
__device__ __forceinline__ void mbar_expect_tx(uint32_t bar, uint32_t bytes) {
  asm volatile("mbarrier.arrive.expect_tx.shared::cta.b64 _, [%0], %1;" ::"r"(bar), "r"(bytes) : "memory");
}
__device__ __forceinline__ uint32_t map_cta(uint32_t addr, uint32_t cta) {
  uint32_t r;
  asm("mapa.shared::cluster.u32 %0, %1, %2;" : "=r"(r) : "r"(addr), "r"(cta));
  return r;
}
__device__ __forceinline__ void mbar_arrive_cluster_if(uint32_t bar, bool cond) {
  asm volatile("{\n.reg .pred p;\nsetp.ne.u32 p, %1, 0;\n@p mbarrier.arrive.shared::cluster.b64 _, [%0];\n}\n"
               ::"r"(bar), "r"((uint32_t)cond) : "memory");
}
__device__ __forceinline__ void mbar_wait(uint32_t bar, uint32_t parity) {
  asm volatile("{\n.reg .pred p;\nLAB_WAIT:\nmbarrier.try_wait.parity.shared::cta.b64 p, [%0], %1;\n@!p bra LAB_WAIT;\n}\n"
               ::"r"(bar), "r"(parity) : "memory");
  return;
  asm volatile("{\n.reg .pred p;\n.reg .u32 c;\nmov.u32 c, 0;\n"
               "LAB_WAIT:\nmbarrier.try_wait.parity.shared::cta.b64 p, [%0], %1;\n@p bra LAB_DONE;\n"
               "add.u32 c, c, 1;\nsetp.lt.u32 p, c, 2000000;\n@p bra LAB_WAIT;\ntrap;\nLAB_DONE:\n}\n"
               ::"r"(bar), "r"(parity) : "memory");
}
__device__ __forceinline__ void mbar_arrive(uint32_t bar) {
  asm volatile("mbarrier.arrive.shared::cta.b64 _, [%0];" ::"r"(bar) : "memory");
}
__device__ __forceinline__ void flag_signal(uint32_t* flag) {
  asm volatile("red.release.gpu.global.add.u32 [%0], 1;" ::"l"(flag) : "memory");
}
__device__ __forceinline__ void st_b128(uint4* p, uint32_t a, uint32_t b, uint32_t c, uint32_t d) {
  asm volatile("{\n.reg .b128 t;\n.reg .b64 lo, hi;\nmov.b64 lo, {%1,%2};\nmov.b64 hi, {%3,%4};\nmov.b128 t, {lo, hi};\n"
               "st.relaxed.gpu.global.b128 [%0], t;\n}\n" ::"l"(p), "r"(a), "r"(b), "r"(c), "r"(d) : "memory");
}
__device__ __forceinline__ uint4 ld_b128(const uint4* p) {
  uint4 v;
  asm volatile("{\n.reg .b128 t;\n.reg .b64 lo, hi;\nld.relaxed.gpu.global.b128 t, [%4];\nmov.b128 {lo, hi}, t;\n"
               "mov.b64 {%0,%1}, lo;\nmov.b64 {%2,%3}, hi;\n}\n" : "=r"(v.x), "=r"(v.y), "=r"(v.z), "=r"(v.w) : "l"(p) : "memory");
  return v;
}
__device__ __forceinline__ uint32_t ld_epoch(Scratch* sc) {
  uint32_t v;
  asm volatile("ld.relaxed.gpu.global.u32 %0, [%1];" : "=r"(v) : "l"(sc->epoch) : "memory");
  return v + 1;
}
__device__ __forceinline__ void flag_wait(uint32_t* flag, uint32_t target) {
  asm volatile("{\n.reg .pred p;\n.reg .u32 c, v;\nmov.u32 c, 0;\n"
               "LAB_WAIT:\nld.relaxed.gpu.global.u32 v, [%0];\nsub.u32 v, v, %1;\nsetp.ge.s32 p, v, 0;\n@p bra LAB_DONE;\n"
               "add.u32 c, c, 1;\nsetp.lt.u32 p, c, 4000000;\n@p bra LAB_WAIT;\ntrap;\nLAB_DONE:\n}\n"
               ::"l"(flag), "r"(target) : "memory");
}
__device__ __forceinline__ int fresh_tid() {
  int v;
  asm volatile("mov.u32 %0, %%tid.x;" : "=r"(v));
  return v;
}
constexpr uint32_t kPoison = 0xFFFFFFFFu;
__device__ __forceinline__ bool elect_one() {
  uint32_t p;
  asm volatile("{\n.reg .pred P;\nelect.sync _|P, 0xffffffff;\nselp.u32 %0, 1, 0, P;\n}\n" : "=r"(p));
  return p != 0;
}
__device__ __forceinline__ void fence_async() { asm volatile("fence.acquire.gpu;\nfence.proxy.async.global;" ::: "memory"); }
__device__ __forceinline__ void fence_async_smem() { asm volatile("fence.proxy.async.shared::cta;" ::: "memory"); }
__device__ __forceinline__ void nb_sync(int id, int n) { asm volatile("bar.sync %0, %1;" ::"r"(id), "r"(n) : "memory"); }
__device__ __forceinline__ void nb_arrive(int id, int n) { asm volatile("bar.arrive %0, %1;" ::"r"(id), "r"(n) : "memory"); }

__device__ __forceinline__ void tma2d(uint32_t dst, const CUtensorMap* m, int c0, int c1, uint32_t bar) {
  asm volatile("cp.async.bulk.tensor.2d.shared::cluster.global.mbarrier::complete_tx::bytes [%0], [%1, {%3, %4}], [%2];"
               ::"r"(dst), "l"(m), "r"(bar), "r"(c0), "r"(c1) : "memory");
}
__device__ __forceinline__ void tma2d_mc(uint32_t dst, const CUtensorMap* m, int c0, int c1, uint32_t bar) {
  asm volatile("cp.async.bulk.tensor.2d.shared::cluster.global.mbarrier::complete_tx::bytes.multicast::cluster"
               " [%0], [%1, {%3, %4}], [%2], %5;"
               ::"r"(dst), "l"(m), "r"(bar), "r"(c0), "r"(c1), "h"((uint16_t)3) : "memory");
}
__device__ __forceinline__ void tma3d(uint32_t dst, const CUtensorMap* m, int c0, int c1, int c2, uint32_t bar) {
  asm volatile("cp.async.bulk.tensor.3d.shared::cluster.global.mbarrier::complete_tx::bytes [%0], [%1, {%3, %4, %5}], [%2];"
               ::"r"(dst), "l"(m), "r"(bar), "r"(c0), "r"(c1), "r"(c2) : "memory");
}
__device__ __forceinline__ void tma_store2d(const CUtensorMap* m, uint32_t src, int c0, int c1) {
  asm volatile("cp.async.bulk.tensor.2d.global.shared::cta.bulk_group [%0, {%2, %3}], [%1];"
               ::"l"(m), "r"(src), "r"(c0), "r"(c1) : "memory");
}
__device__ __forceinline__ void tma_store3d(const CUtensorMap* m, uint32_t src, int c0, int c1, int c2) {
  asm volatile("cp.async.bulk.tensor.3d.global.shared::cta.bulk_group [%0, {%2, %3, %4}], [%1];"
               ::"l"(m), "r"(src), "r"(c0), "r"(c1), "r"(c2) : "memory");
}
__device__ __forceinline__ void tma_prefetch2d(const CUtensorMap* m, int c0, int c1) {
  asm volatile("cp.async.bulk.prefetch.tensor.2d.L2.global [%0, {%1, %2}];" ::"l"(m), "r"(c0), "r"(c1) : "memory");
}
__device__ __forceinline__ void prefetch_map(const CUtensorMap* m) { asm volatile("prefetch.tensormap [%0];" ::"l"(m) : "memory"); }
__device__ __forceinline__ void bulk_commit() { asm volatile("cp.async.bulk.commit_group;" ::: "memory"); }
__device__ __forceinline__ void bulk_wait_all() { asm volatile("cp.async.bulk.wait_group 0;" ::: "memory"); }
__device__ __forceinline__ void bulk_wait_read() { asm volatile("cp.async.bulk.wait_group.read 0;" ::: "memory"); }
__device__ __forceinline__ void prefetch_l2(const void* p) { asm volatile("prefetch.global.L2 [%0];" ::"l"(p)); }
__device__ __forceinline__ void cluster_arrive() { asm volatile("barrier.cluster.arrive.relaxed.aligned;" ::: "memory"); }
__device__ __forceinline__ void cluster_wait() { asm volatile("barrier.cluster.wait.aligned;" ::: "memory"); }

__device__ __forceinline__ void wg_fence() { asm volatile("wgmma.fence.sync.aligned;" ::: "memory"); }
__device__ __forceinline__ void wg_commit() { asm volatile("wgmma.commit_group.sync.aligned;" ::: "memory"); }
template <int N> __device__ __forceinline__ void wg_wait() { asm volatile("wgmma.wait_group.sync.aligned %0;" ::"n"(N) : "memory"); }
__device__ __forceinline__ uint32_t desc_lo(uint32_t addr, uint32_t lbo) { return ((addr & 0x3FFFF) >> 4) | ((lbo >> 4) << 16); }
__device__ __forceinline__ uint64_t desc(uint32_t lo) { return (uint64_t)lo | (0x40000040ull << 32); }
__device__ __forceinline__ uint64_t desc_kept(uint32_t lo, uint32_t sb) { return (uint64_t)lo | (uint64_t)(0x40000040u | sb >> 31) << 32; }
constexpr int kToB = (16384 >> 4) + ((8192 - 16) >> 4 << 16);

__device__ __forceinline__ void wgmma_n128(float (&d)[96], uint64_t da, uint64_t db) {
  asm volatile(
      "wgmma.mma_async.sync.aligned.m64n128k16.f32.bf16.bf16 {"
      "%0, %1, %2, %3, %4, %5, %6, %7, %8, %9, %10, %11, %12, %13, %14, %15, "
      "%16, %17, %18, %19, %20, %21, %22, %23, %24, %25, %26, %27, %28, %29, %30, %31, "
      "%32, %33, %34, %35, %36, %37, %38, %39, %40, %41, %42, %43, %44, %45, %46, %47, "
      "%48, %49, %50, %51, %52, %53, %54, %55, %56, %57, %58, %59, %60, %61, %62, %63}, "
      "%64, %65, 1, 1, 1, 0, 1;\n"
      :
        "+f"(d[0]), "+f"(d[1]), "+f"(d[2]), "+f"(d[3]), "+f"(d[4]), "+f"(d[5]), "+f"(d[6]), "+f"(d[7]),
        "+f"(d[8]), "+f"(d[9]), "+f"(d[10]), "+f"(d[11]), "+f"(d[12]), "+f"(d[13]), "+f"(d[14]), "+f"(d[15]),
        "+f"(d[16]), "+f"(d[17]), "+f"(d[18]), "+f"(d[19]), "+f"(d[20]), "+f"(d[21]), "+f"(d[22]), "+f"(d[23]),
        "+f"(d[24]), "+f"(d[25]), "+f"(d[26]), "+f"(d[27]), "+f"(d[28]), "+f"(d[29]), "+f"(d[30]), "+f"(d[31]),
        "+f"(d[32]), "+f"(d[33]), "+f"(d[34]), "+f"(d[35]), "+f"(d[36]), "+f"(d[37]), "+f"(d[38]), "+f"(d[39]),
        "+f"(d[40]), "+f"(d[41]), "+f"(d[42]), "+f"(d[43]), "+f"(d[44]), "+f"(d[45]), "+f"(d[46]), "+f"(d[47]),
        "+f"(d[48]), "+f"(d[49]), "+f"(d[50]), "+f"(d[51]), "+f"(d[52]), "+f"(d[53]), "+f"(d[54]), "+f"(d[55]),
        "+f"(d[56]), "+f"(d[57]), "+f"(d[58]), "+f"(d[59]), "+f"(d[60]), "+f"(d[61]), "+f"(d[62]), "+f"(d[63])
      : "l"(da), "l"(db));
}

__device__ __forceinline__ void wgmma_n256(float (&d)[128], uint64_t da, uint64_t db, int add) {
  asm volatile(
      "{\n.reg .pred p;\nsetp.ne.b32 p, %130, 0;\n"
      "wgmma.mma_async.sync.aligned.m64n256k16.f32.bf16.bf16 {"
      "%0, %1, %2, %3, %4, %5, %6, %7, %8, %9, %10, %11, %12, %13, %14, %15, "
      "%16, %17, %18, %19, %20, %21, %22, %23, %24, %25, %26, %27, %28, %29, %30, %31, "
      "%32, %33, %34, %35, %36, %37, %38, %39, %40, %41, %42, %43, %44, %45, %46, %47, "
      "%48, %49, %50, %51, %52, %53, %54, %55, %56, %57, %58, %59, %60, %61, %62, %63, "
      "%64, %65, %66, %67, %68, %69, %70, %71, %72, %73, %74, %75, %76, %77, %78, %79, "
      "%80, %81, %82, %83, %84, %85, %86, %87, %88, %89, %90, %91, %92, %93, %94, %95, "
      "%96, %97, %98, %99, %100, %101, %102, %103, %104, %105, %106, %107, %108, %109, %110, %111, "
      "%112, %113, %114, %115, %116, %117, %118, %119, %120, %121, %122, %123, %124, %125, %126, %127}, "
      "%128, %129, p, 1, 1, 0, 1;\n}\n"
      :
        "+f"(d[0]), "+f"(d[1]), "+f"(d[2]), "+f"(d[3]), "+f"(d[4]), "+f"(d[5]), "+f"(d[6]), "+f"(d[7]),
        "+f"(d[8]), "+f"(d[9]), "+f"(d[10]), "+f"(d[11]), "+f"(d[12]), "+f"(d[13]), "+f"(d[14]), "+f"(d[15]),
        "+f"(d[16]), "+f"(d[17]), "+f"(d[18]), "+f"(d[19]), "+f"(d[20]), "+f"(d[21]), "+f"(d[22]), "+f"(d[23]),
        "+f"(d[24]), "+f"(d[25]), "+f"(d[26]), "+f"(d[27]), "+f"(d[28]), "+f"(d[29]), "+f"(d[30]), "+f"(d[31]),
        "+f"(d[32]), "+f"(d[33]), "+f"(d[34]), "+f"(d[35]), "+f"(d[36]), "+f"(d[37]), "+f"(d[38]), "+f"(d[39]),
        "+f"(d[40]), "+f"(d[41]), "+f"(d[42]), "+f"(d[43]), "+f"(d[44]), "+f"(d[45]), "+f"(d[46]), "+f"(d[47]),
        "+f"(d[48]), "+f"(d[49]), "+f"(d[50]), "+f"(d[51]), "+f"(d[52]), "+f"(d[53]), "+f"(d[54]), "+f"(d[55]),
        "+f"(d[56]), "+f"(d[57]), "+f"(d[58]), "+f"(d[59]), "+f"(d[60]), "+f"(d[61]), "+f"(d[62]), "+f"(d[63]),
        "+f"(d[64]), "+f"(d[65]), "+f"(d[66]), "+f"(d[67]), "+f"(d[68]), "+f"(d[69]), "+f"(d[70]), "+f"(d[71]),
        "+f"(d[72]), "+f"(d[73]), "+f"(d[74]), "+f"(d[75]), "+f"(d[76]), "+f"(d[77]), "+f"(d[78]), "+f"(d[79]),
        "+f"(d[80]), "+f"(d[81]), "+f"(d[82]), "+f"(d[83]), "+f"(d[84]), "+f"(d[85]), "+f"(d[86]), "+f"(d[87]),
        "+f"(d[88]), "+f"(d[89]), "+f"(d[90]), "+f"(d[91]), "+f"(d[92]), "+f"(d[93]), "+f"(d[94]), "+f"(d[95]),
        "+f"(d[96]), "+f"(d[97]), "+f"(d[98]), "+f"(d[99]), "+f"(d[100]), "+f"(d[101]), "+f"(d[102]), "+f"(d[103]),
        "+f"(d[104]), "+f"(d[105]), "+f"(d[106]), "+f"(d[107]), "+f"(d[108]), "+f"(d[109]), "+f"(d[110]), "+f"(d[111]),
        "+f"(d[112]), "+f"(d[113]), "+f"(d[114]), "+f"(d[115]), "+f"(d[116]), "+f"(d[117]), "+f"(d[118]), "+f"(d[119]),
        "+f"(d[120]), "+f"(d[121]), "+f"(d[122]), "+f"(d[123]), "+f"(d[124]), "+f"(d[125]), "+f"(d[126]), "+f"(d[127])
      : "l"(da), "l"(db), "r"(add));
}

__device__ __forceinline__ void wgmma_n192(float (&d)[96], uint64_t da, uint64_t db, int add = 1) {
  asm volatile(
      "{\n.reg .pred p;\nsetp.ne.b32 p, %98, 0;\n"
      "wgmma.mma_async.sync.aligned.m64n192k16.f32.bf16.bf16 {"
      "%0, %1, %2, %3, %4, %5, %6, %7, %8, %9, %10, %11, %12, %13, %14, %15, "
      "%16, %17, %18, %19, %20, %21, %22, %23, %24, %25, %26, %27, %28, %29, %30, %31, "
      "%32, %33, %34, %35, %36, %37, %38, %39, %40, %41, %42, %43, %44, %45, %46, %47, "
      "%48, %49, %50, %51, %52, %53, %54, %55, %56, %57, %58, %59, %60, %61, %62, %63, "
      "%64, %65, %66, %67, %68, %69, %70, %71, %72, %73, %74, %75, %76, %77, %78, %79, "
      "%80, %81, %82, %83, %84, %85, %86, %87, %88, %89, %90, %91, %92, %93, %94, %95}, "
      "%96, %97, p, 1, 1, 0, 1;\n}\n"
      :
        "+f"(d[0]), "+f"(d[1]), "+f"(d[2]), "+f"(d[3]), "+f"(d[4]), "+f"(d[5]), "+f"(d[6]), "+f"(d[7]),
        "+f"(d[8]), "+f"(d[9]), "+f"(d[10]), "+f"(d[11]), "+f"(d[12]), "+f"(d[13]), "+f"(d[14]), "+f"(d[15]),
        "+f"(d[16]), "+f"(d[17]), "+f"(d[18]), "+f"(d[19]), "+f"(d[20]), "+f"(d[21]), "+f"(d[22]), "+f"(d[23]),
        "+f"(d[24]), "+f"(d[25]), "+f"(d[26]), "+f"(d[27]), "+f"(d[28]), "+f"(d[29]), "+f"(d[30]), "+f"(d[31]),
        "+f"(d[32]), "+f"(d[33]), "+f"(d[34]), "+f"(d[35]), "+f"(d[36]), "+f"(d[37]), "+f"(d[38]), "+f"(d[39]),
        "+f"(d[40]), "+f"(d[41]), "+f"(d[42]), "+f"(d[43]), "+f"(d[44]), "+f"(d[45]), "+f"(d[46]), "+f"(d[47]),
        "+f"(d[48]), "+f"(d[49]), "+f"(d[50]), "+f"(d[51]), "+f"(d[52]), "+f"(d[53]), "+f"(d[54]), "+f"(d[55]),
        "+f"(d[56]), "+f"(d[57]), "+f"(d[58]), "+f"(d[59]), "+f"(d[60]), "+f"(d[61]), "+f"(d[62]), "+f"(d[63]),
        "+f"(d[64]), "+f"(d[65]), "+f"(d[66]), "+f"(d[67]), "+f"(d[68]), "+f"(d[69]), "+f"(d[70]), "+f"(d[71]),
        "+f"(d[72]), "+f"(d[73]), "+f"(d[74]), "+f"(d[75]), "+f"(d[76]), "+f"(d[77]), "+f"(d[78]), "+f"(d[79]),
        "+f"(d[80]), "+f"(d[81]), "+f"(d[82]), "+f"(d[83]), "+f"(d[84]), "+f"(d[85]), "+f"(d[86]), "+f"(d[87]),
        "+f"(d[88]), "+f"(d[89]), "+f"(d[90]), "+f"(d[91]), "+f"(d[92]), "+f"(d[93]), "+f"(d[94]), "+f"(d[95])
      : "l"(da), "l"(db), "r"(add));
}

__device__ __forceinline__ void wgmma_n192_any(float (&d)[96], uint64_t da, uint64_t db) {
  asm volatile(
      "wgmma.mma_async.sync.aligned.m64n192k16.f32.bf16.bf16 {"
      "%0, %1, %2, %3, %4, %5, %6, %7, %8, %9, %10, %11, %12, %13, %14, %15, "
      "%16, %17, %18, %19, %20, %21, %22, %23, %24, %25, %26, %27, %28, %29, %30, %31, "
      "%32, %33, %34, %35, %36, %37, %38, %39, %40, %41, %42, %43, %44, %45, %46, %47, "
      "%48, %49, %50, %51, %52, %53, %54, %55, %56, %57, %58, %59, %60, %61, %62, %63, "
      "%64, %65, %66, %67, %68, %69, %70, %71, %72, %73, %74, %75, %76, %77, %78, %79, "
      "%80, %81, %82, %83, %84, %85, %86, %87, %88, %89, %90, %91, %92, %93, %94, %95}, "
      "%96, %97, 0, 1, 1, 0, 1;\n"
      :
        "=f"(d[0]), "=f"(d[1]), "=f"(d[2]), "=f"(d[3]), "=f"(d[4]), "=f"(d[5]), "=f"(d[6]), "=f"(d[7]),
        "=f"(d[8]), "=f"(d[9]), "=f"(d[10]), "=f"(d[11]), "=f"(d[12]), "=f"(d[13]), "=f"(d[14]), "=f"(d[15]),
        "=f"(d[16]), "=f"(d[17]), "=f"(d[18]), "=f"(d[19]), "=f"(d[20]), "=f"(d[21]), "=f"(d[22]), "=f"(d[23]),
        "=f"(d[24]), "=f"(d[25]), "=f"(d[26]), "=f"(d[27]), "=f"(d[28]), "=f"(d[29]), "=f"(d[30]), "=f"(d[31]),
        "=f"(d[32]), "=f"(d[33]), "=f"(d[34]), "=f"(d[35]), "=f"(d[36]), "=f"(d[37]), "=f"(d[38]), "=f"(d[39]),
        "=f"(d[40]), "=f"(d[41]), "=f"(d[42]), "=f"(d[43]), "=f"(d[44]), "=f"(d[45]), "=f"(d[46]), "=f"(d[47]),
        "=f"(d[48]), "=f"(d[49]), "=f"(d[50]), "=f"(d[51]), "=f"(d[52]), "=f"(d[53]), "=f"(d[54]), "=f"(d[55]),
        "=f"(d[56]), "=f"(d[57]), "=f"(d[58]), "=f"(d[59]), "=f"(d[60]), "=f"(d[61]), "=f"(d[62]), "=f"(d[63]),
        "=f"(d[64]), "=f"(d[65]), "=f"(d[66]), "=f"(d[67]), "=f"(d[68]), "=f"(d[69]), "=f"(d[70]), "=f"(d[71]),
        "=f"(d[72]), "=f"(d[73]), "=f"(d[74]), "=f"(d[75]), "=f"(d[76]), "=f"(d[77]), "=f"(d[78]), "=f"(d[79]),
        "=f"(d[80]), "=f"(d[81]), "=f"(d[82]), "=f"(d[83]), "=f"(d[84]), "=f"(d[85]), "=f"(d[86]), "=f"(d[87]),
        "=f"(d[88]), "=f"(d[89]), "=f"(d[90]), "=f"(d[91]), "=f"(d[92]), "=f"(d[93]), "=f"(d[94]), "=f"(d[95])
      : "l"(da), "l"(db));
}

__device__ __forceinline__ void wgmma_n192_rs(float (&d)[96], uint32_t a0, uint32_t a1, uint32_t a23, uint64_t db) {
  asm volatile(
      "wgmma.mma_async.sync.aligned.m64n192k16.f32.bf16.bf16 {"
      "%0, %1, %2, %3, %4, %5, %6, %7, %8, %9, %10, %11, %12, %13, %14, %15, "
      "%16, %17, %18, %19, %20, %21, %22, %23, %24, %25, %26, %27, %28, %29, %30, %31, "
      "%32, %33, %34, %35, %36, %37, %38, %39, %40, %41, %42, %43, %44, %45, %46, %47, "
      "%48, %49, %50, %51, %52, %53, %54, %55, %56, %57, %58, %59, %60, %61, %62, %63, "
      "%64, %65, %66, %67, %68, %69, %70, %71, %72, %73, %74, %75, %76, %77, %78, %79, "
      "%80, %81, %82, %83, %84, %85, %86, %87, %88, %89, %90, %91, %92, %93, %94, %95}, "
      "{%96, %97, %98, %98}, %99, 1, 1, 1, 1;\n"
      :
        "+f"(d[0]), "+f"(d[1]), "+f"(d[2]), "+f"(d[3]), "+f"(d[4]), "+f"(d[5]), "+f"(d[6]), "+f"(d[7]),
        "+f"(d[8]), "+f"(d[9]), "+f"(d[10]), "+f"(d[11]), "+f"(d[12]), "+f"(d[13]), "+f"(d[14]), "+f"(d[15]),
        "+f"(d[16]), "+f"(d[17]), "+f"(d[18]), "+f"(d[19]), "+f"(d[20]), "+f"(d[21]), "+f"(d[22]), "+f"(d[23]),
        "+f"(d[24]), "+f"(d[25]), "+f"(d[26]), "+f"(d[27]), "+f"(d[28]), "+f"(d[29]), "+f"(d[30]), "+f"(d[31]),
        "+f"(d[32]), "+f"(d[33]), "+f"(d[34]), "+f"(d[35]), "+f"(d[36]), "+f"(d[37]), "+f"(d[38]), "+f"(d[39]),
        "+f"(d[40]), "+f"(d[41]), "+f"(d[42]), "+f"(d[43]), "+f"(d[44]), "+f"(d[45]), "+f"(d[46]), "+f"(d[47]),
        "+f"(d[48]), "+f"(d[49]), "+f"(d[50]), "+f"(d[51]), "+f"(d[52]), "+f"(d[53]), "+f"(d[54]), "+f"(d[55]),
        "+f"(d[56]), "+f"(d[57]), "+f"(d[58]), "+f"(d[59]), "+f"(d[60]), "+f"(d[61]), "+f"(d[62]), "+f"(d[63]),
        "+f"(d[64]), "+f"(d[65]), "+f"(d[66]), "+f"(d[67]), "+f"(d[68]), "+f"(d[69]), "+f"(d[70]), "+f"(d[71]),
        "+f"(d[72]), "+f"(d[73]), "+f"(d[74]), "+f"(d[75]), "+f"(d[76]), "+f"(d[77]), "+f"(d[78]), "+f"(d[79]),
        "+f"(d[80]), "+f"(d[81]), "+f"(d[82]), "+f"(d[83]), "+f"(d[84]), "+f"(d[85]), "+f"(d[86]), "+f"(d[87]),
        "+f"(d[88]), "+f"(d[89]), "+f"(d[90]), "+f"(d[91]), "+f"(d[92]), "+f"(d[93]), "+f"(d[94]), "+f"(d[95])
      : "r"(a0), "r"(a1), "r"(a23), "l"(db));
}

__device__ __forceinline__ uint32_t pack_bf16(float lo, float hi) {
  uint32_t r;
  asm("cvt.rn.bf16x2.f32 %0, %1, %2;" : "=r"(r) : "f"(hi), "f"(lo));
  return r;
}
__device__ __forceinline__ float bf_lo(uint32_t v) { return __uint_as_float(v << 16); }
__device__ __forceinline__ float bf_hi(uint32_t v) { return __uint_as_float(v & 0xFFFF0000u); }
__device__ __forceinline__ float ex2(float x) { float r; asm("ex2.approx.ftz.f32 %0, %1;" : "=f"(r) : "f"(x)); return r; }
__device__ __forceinline__ float rcp(float x) { float r; asm("rcp.approx.ftz.f32 %0, %1;" : "=f"(r) : "f"(x)); return r; }
__device__ __forceinline__ uint32_t movm(uint32_t a) {
  uint32_t d;
  asm volatile("movmatrix.sync.aligned.m8n8.trans.b16 %0, %1;" : "=r"(d) : "r"(a));
  return d;
}
__device__ __forceinline__ void mma16816(float (&c)[4], uint32_t a0, uint32_t a1, uint32_t a2, uint32_t a3, uint32_t b0, uint32_t b1) {
  asm volatile("mma.sync.aligned.m16n8k16.row.col.f32.bf16.bf16.f32 {%0,%1,%2,%3}, {%4,%5,%6,%7}, {%8,%9}, {%0,%1,%2,%3};"
               : "+f"(c[0]), "+f"(c[1]), "+f"(c[2]), "+f"(c[3]) : "r"(a0), "r"(a1), "r"(a2), "r"(a3), "r"(b0), "r"(b1));
}
__device__ __forceinline__ void mma1688(float (&c)[4], uint32_t a0, uint32_t a1, uint32_t b0) {
  asm volatile("mma.sync.aligned.m16n8k8.row.col.f32.bf16.bf16.f32 {%0,%1,%2,%3}, {%4,%5}, {%6}, {%0,%1,%2,%3};"
               : "+f"(c[0]), "+f"(c[1]), "+f"(c[2]), "+f"(c[3]) : "r"(a0), "r"(a1), "r"(b0));
}
__device__ __forceinline__ void stsm4(uint32_t addr, uint32_t a, uint32_t b, uint32_t c, uint32_t d) {
  asm volatile("stmatrix.sync.aligned.m8n8.x4.shared.b16 [%0], {%1,%2,%3,%4};" ::"r"(addr), "r"(a), "r"(b), "r"(c), "r"(d) : "memory");
}
__device__ __forceinline__ void stsm4_t(uint32_t addr, uint32_t a, uint32_t b, uint32_t c, uint32_t d) {
  asm volatile("stmatrix.sync.aligned.m8n8.x4.trans.shared.b16 [%0], {%1,%2,%3,%4};" ::"r"(addr), "r"(a), "r"(b), "r"(c), "r"(d) : "memory");
}
__device__ __forceinline__ void ldsm4(uint32_t addr, uint32_t (&v)[4]) {
  asm volatile("ldmatrix.sync.aligned.m8n8.x4.shared.b16 {%0,%1,%2,%3}, [%4];"
               : "=r"(v[0]), "=r"(v[1]), "=r"(v[2]), "=r"(v[3]) : "r"(addr) : "memory");
}
__device__ __forceinline__ void sts128(uint32_t addr, uint4 v) {
  asm volatile("st.shared.v4.b32 [%0], {%1,%2,%3,%4};" ::"r"(addr), "r"(v.x), "r"(v.y), "r"(v.z), "r"(v.w) : "memory");
}
__device__ __forceinline__ uint4 lds128(uint32_t addr) {
  uint4 v;
  asm volatile("ld.shared.v4.b32 {%0,%1,%2,%3}, [%4];" : "=r"(v.x), "=r"(v.y), "=r"(v.z), "=r"(v.w) : "r"(addr) : "memory");
  return v;
}
__device__ __forceinline__ void sts64(uint32_t addr, uint32_t a, uint32_t b) {
  asm volatile("st.shared.v2.b32 [%0], {%1,%2};" ::"r"(addr), "r"(a), "r"(b) : "memory");
}
__device__ __forceinline__ void sts32(uint32_t addr, uint32_t a) { asm volatile("st.shared.b32 [%0], %1;" ::"r"(addr), "r"(a) : "memory"); }
__device__ __forceinline__ uint32_t lds32(uint32_t addr) {
  uint32_t v;
  asm volatile("ld.shared.b32 %0, [%1];" : "=r"(v) : "r"(addr) : "memory");
  return v;
}
__device__ __forceinline__ float2 lds64f_const(uint32_t addr) {
  float2 v;
  asm("ld.shared.v2.f32 {%0,%1}, [%2];" : "=f"(v.x), "=f"(v.y) : "r"(addr));
  return v;
}
template <int N, bool PAIR>
__device__ __forceinline__ void load_tagged(uint3 (&out)[N], const uint4* src, int stride, uint32_t tag, int last = 0) {
  uint32_t bad;
  int spins = 0;
  do {
    if (spins != 0) __nanosleep(kBackoffNs);
    if (++spins > 2000000) __trap();
    bad = 0;
#pragma unroll
    for (int i = 0; i < N; i++) {
      const uint4 v = ld_b128(src + i * stride + (i == N - 1 ? last : 0));
      out[i] = make_uint3(v.x, v.y, v.z);
      bad |= (v.w ^ tag) | (PAIR ? v.z ^ tag : 0);
    }
  } while (N == 4 ? __any_sync(~0u, bad != 0) : bad != 0);
}
__device__ __forceinline__ void sts64f(uint32_t addr, float2 v) { sts64(addr, __float_as_uint(v.x), __float_as_uint(v.y)); }
__device__ __forceinline__ float bf_rest(float v) { return v - __uint_as_float(__float_as_uint(v) & 0xFFFF0000u); }
__device__ __forceinline__ uint32_t bf_upper(float lo, float hi) { return __byte_perm(__float_as_uint(lo), __float_as_uint(hi), 0x7632); }
__device__ __forceinline__ float low_peak(uint4 v) {
  asm("max.xorsign.abs.bf16x2 %0, %0, %1;" : "+r"(v.x) : "r"(v.y));
  asm("max.xorsign.abs.bf16x2 %0, %0, %1;" : "+r"(v.z) : "r"(v.w));
  asm("max.xorsign.abs.bf16x2 %0, %0, %1;" : "+r"(v.x) : "r"(v.z));
  asm("max.xorsign.abs.bf16x2 %0, %0, %1;" : "+r"(v.x) : "r"(v.x << 16));
  return __uint_as_float(__reduce_min_sync(~0u, v.x & 0x7FFF0000u));
}
__device__ __forceinline__ float bias_at(float v) { return __uint_as_float((__float_as_uint(fminf(v, 1e37f)) & 0x7F800000u) | 0x00400000u); }
struct RowConst {
  float nmean, k0, k1, half;
};
__device__ __forceinline__ float gate_scale(float t, const RowConst& k) {
  float th;
  asm("tanh.approx.f32 %0, %1;" : "=f"(th) : "f"(t * fmaf(t * t, k.k1, k.k0)));
  return fmaf(th, k.half, k.half);
}

template <int N>
__device__ __forceinline__ void mma_k16(float (&acc)[2][96], uint32_t a, uint32_t b, int kk, int add = 1) {
#pragma unroll
  for (int m = 0; m < 2; m++) {
    const uint64_t da = desc(a) + (m * 512 + kk * 2), db = desc(b) + kk * 128;
    if (N == 128) wgmma_n128(acc[m], da, db); else wgmma_n192(acc[m], da, db, add);
  }
}

__device__ __forceinline__ void stage_quarter(const float* acc, uint32_t frag, uint32_t frag_x, int b, const uint4* add = nullptr) {
#pragma unroll
  for (int j = 0; j < 4; j++) {
    const float* v = acc + 8 * j;
    uint32_t h[4] = {pack_bf16(v[0], v[1]), pack_bf16(v[2], v[3]), pack_bf16(v[4], v[5]), pack_bf16(v[6], v[7])};
    if (add) {
      const uint32_t a[4] = {add[j].x, add[j].y, add[j].z, add[j].w};
#pragma unroll
      for (int e = 0; e < 4; e++) asm("add.rn.bf16x2 %0, %0, %1;" : "+r"(h[e]) : "r"(a[e]));
    }
    stsm4(frag + b * 8192 + ((frag_x ^ (j * 2)) << 4), h[0], h[1], h[2], h[3]);
  }
}

__device__ __forceinline__ int g1_block(int j, int c) { return j < 16 ? j : ((j + 12) & 15) ^ (c == 5 && j >= 28 ? 2 : 0); }
__device__ __forceinline__ int g2_block(int j, int c) { return j < 8 ? j : j == 8 ? 8 + c : j - (j - 9 < c); }
__device__ __forceinline__ int g3_tile(int j) { return j < 4 ? j >> 1 : j < 18 ? 0 : j >> 4; }
__device__ __forceinline__ int g3_block(int j, int c) {
  const int i = j < 32 ? (j < 16 ? 0xDCBA976543218080ull : 0x7654321BA9FEDCFEull) >> 4 * (j & 15) : j + (~j >> 2 & 4), o = i & 7;
  return 2 * (j < 32 && (o == c || o == 0) ? c - o : o) + (i >> 3 & 1);
}
__device__ __forceinline__ bool g3_is_up(int tile, int a) { return a == 1 || (a == 2 && tile >= 2); }
__device__ __forceinline__ int g3_atom(int tile, int a, int c) { return c * 7 + (tile & 1) * 3 + (a == 2 ? 1 : tile == 4 ? 6 : tile & 2); }
__device__ __forceinline__ int g4_block(int i) {
  return i < 16 ? 7 * (i & 7) + 3 * (i >> 3) : i < 48 ? 7 * ((i & 15) >> 1) + 3 * (i >> 5) + 1 + (i & 1) : 7 * (i & 7) + (i < 56 ? 6 : 0);
}

template <int N, int TAIL>
__device__ __forceinline__ void mainloop(Scratch* sc, float (&acc)[2][96], uint32_t sb, int ph, int j0, int nsteps, int pause_at, bool last,
                                         bool hand_over, bool local, int wg, int own = -1, const CUtensorMap* out = nullptr, int out_col = 0,
                                         int out_row = 0, int warp = 0, __nv_bfloat16* outp = nullptr) {
  constexpr int NSLOT = N == 128 ? 5 : 4, SLOT = N == 128 ? 32768 : 40960;
  const int lane = fresh_tid() & 31;
  const uint32_t full = sb + kBars + 8 * ring_base(ph);
  const uint32_t empty = map_cta(full + 8 * NSLOT, lane & 1);
  const uint32_t ring = desc_lo(sb + kRing, 16);
  int bi = j0 % NSLOT, par = (j0 / NSLOT) & 1;
  const int release_end = lane < (N == 192 && !hand_over ? 4 : 2) ? (last ? nsteps - 1 - NSLOT : nsteps) : 0;
  uint32_t rel = empty;
  const uint32_t special = ph == 0 && wg == 0 ? 3 : pause_at < 0 ? 1 : 1 | 2 << pause_at;
#pragma unroll 1
  for (int i = 0; i < nsteps - (TAIL > 0 ? TAIL + 1 : 0); i++) {
    uint32_t a = ring + bi * (SLOT >> 4), b = a + kToB;
    if (TAIL > 0 && i == 0) TSG(5);
    if (special >> i & 1) {
      if (i == 0) nb_sync(kNbOrder + wg, ph == 0 && wg == 0 ? 160 : 256);
      else if (ph == 0 && wg == 0) cluster_wait();
      else if (ph < 2) nb_sync(kNbWin + 1, 256);
    }
    if (N == 192 && local) {
      a = ring + ((kStage + i * 16384) >> 4);
      b = ring + bi * (32768 >> 4) + desc_lo(32768, 8192) - desc_lo(0, 16);
    }
    if (ph == 0 && i >> 1 == own) a = ring + ((kOwn + (i & 1) * 16384) >> 4);
    if (ph == 1 && i == 8) a = ring + ((kStage + 32768) >> 4);
    if (TAIL > 0 && i == 0) TSG(6);
    mbar_wait(full + 8 * bi, par);
    if (N == 192 && local) mbar_wait(sb + kBars + 8 * (kHalfBar + i), 0);
    if (TAIL > 0 && i == 0) TSG(7);
    wg_fence();
    mma_k16<N>(acc, a, b, 0, ph == 0 ? i | wg : 1);
    mma_k16<N>(acc, a, b, 1);
    wg_commit();
    const bool release = (uint32_t)(i - 1) < (uint32_t)release_end;
    wg_wait<1>();
    mbar_arrive_cluster_if(rel, release);
    wg_fence();
    mma_k16<N>(acc, a, b, 2);
    mma_k16<N>(acc, a, b, 3);
    wg_commit();
    rel = empty + 8 * bi;
    if (++bi == NSLOT) { bi = 0; par ^= 1; }
    if (i == pause_at) nb_arrive(kNbWin, 256);
  }
  if (TAIL < 0) return;
  if (TAIL > 0) {
    uint32_t at[TAIL + 2];
    const int t = fresh_tid() & 127;
    uint32_t frag = sb + kStage + ((t >> 5) * 16 + (t & 15)) * 128, frag_x = ((t >> 4) & 1) ^ (t & 7);
    const uint32_t back = sb + kStage + (t >> 5) * 2048 + ((t >> 3) & 3) * 128, back_x = ((t ^ (t >> 3 & 3)) & 7) << 4;
    outp += (2 * (out_row + (t >> 5) * 16 + ((t >> 3) & 3)) + (blockIdx.x & 1)) * kD + out_col + (t & 7) * 8;
    static_assert(kTail == 5, "");
    uint4 part[8];
    mbar_wait(full + 8 * bi, par);
#pragma unroll
    for (int hf = 0; hf < 2; hf++) {
      const uint32_t a = ring + bi * (SLOT >> 4), b = a + kToB;
      wg_fence();
      mma_k16<N>(acc, a, b, 2 * hf);
      mma_k16<N>(acc, a, b, 2 * hf + 1);
      wg_commit();
      if (hf == 0) {
        wg_wait<1>();
        mbar_arrive_cluster_if(rel, (t & 31) < 2);
      }
      if (hf) mbar_wait(sb + kBars + 8 * kStgBar, 1);
      else nb_sync(kNbPart, 256);
#pragma unroll
      for (int k = 4 * hf; k < 4 * hf + 4; k++) part[k] = lds128(sb + kStage + 32768 + (t >> 5) * 4096 + (t & 31) * 16 + k * 512);
    }
    if (++bi == NSLOT) { bi = 0; par ^= 1; }
    auto last_rows = [&](int i0, int i1) {
#pragma unroll
      for (int i = i0; i < i1; i++) {
        if (i == 3) continue;
        at[i] = bi * (SLOT >> 4);
        mbar_wait(full + 8 * bi, par);
        if (++bi == NSLOT) { bi = 0; par ^= 1; }
      }
      wg_fence();
#pragma unroll
      for (int i = 4 * i0; i < 4 * i1; i++)
        wgmma_n128(acc[1], desc_kept(ring, sb) + ((i >> 2 != 3 ? at[i >> 2] + 512 : at[2]) + (i & 3) * 2),
                   desc_kept(ring, sb) + ((i >> 2 != 3 ? at[i >> 2] + kToB : at[0] + ((SLOT - 16) >> 4 << 16)) + (i & 3) * 128));
      wg_commit();
    };
    last_rows(0, 2);
#pragma unroll
    for (int b = 0; b < 4; b++) {
      if (b == 0) wg_wait<1>();
      if (b == 1) last_rows(3, 4);
      if (b == 2) wg_wait<0>();
      if (!(b & 1)) {
#pragma unroll
        for (int i = 0; i < 64; i++) asm volatile("" : "+f"(acc[b >> 1][i])::"memory");
        if (t == 0) TSS(b);
      }
      stage_quarter(&acc[b >> 1][32 * (b & 1)], frag, frag_x, b, b < 2 ? &part[4 * b] : nullptr);
      if (b == 3) {
        __syncwarp();
        uint4 v[4];
#pragma unroll
        for (int i = 0; i < 4; i++) v[i] = lds128(back + b * 8192 + i * 512 + ((i & 1) ? back_x ^ 64 : back_x));
#pragma unroll
        for (int i = 0; i < 4; i++) __stcs((uint4*)(outp + ((b >> 1) * 128 + i * 8) * kD + (b & 1) * 64), v[i]);
        if (t == 0) TSS(4 + b);
        continue;
      }
      if (b < 2) last_rows(2 + 2 * b, 3 + 2 * b);
      fence_async_smem();
      __syncwarp();
      if (elect_one()) tma_store3d(out, sb + kStage + b * 8192 + warp * 2048, out_col + (b & 1) * 64, out_row + (b >> 1) * 64 + warp * 16, blockIdx.x & 1);
      __syncwarp();
      if (t == 0) TSS(4 + b);
    }
    if (elect_one()) {
      bulk_commit();
      bulk_wait_read();
    }
    if (t == 0) TSS(1);
    return;
  }
  if (hand_over) nb_arrive(kNbOrder + (wg ^ 1), 256);
  if (N == 192 && !local) {
    mbar_wait(sb + kBars + 8 * (kAuxBar + wg), j0 < 32);
    if (j0 < 32) mbar_wait(sb + kBars + 8 * kStatBar, 1);
    mbar_wait(sb + kBars + 8 * (kStgBar + wg), ((j0 >> 5) ^ wg ^ 1) & 1);
  }
  wg_wait<0>();
  mbar_arrive_cluster_if(rel, release_end == nsteps);
#pragma unroll
  for (int i = 0; i < N / 2; i++) asm volatile("" : "+f"(acc[0][i]), "+f"(acc[1][i])::"memory");
}

template <int PH>
struct Ring {
  static constexpr int NSLOT = 4 + (PH & 1), SLOT = PH & 1 ? 32768 : 40960;
  uint32_t full, dst0;
  int j = PH == 0 ? 4 : 0, bi = 0, par = PH == 0 ? 0 : 1;
  __device__ __forceinline__ Ring(uint32_t sb, uint32_t ofs) : full(sb + kBars + 8 * (PH * 9 - (PH & 1))), dst0(sb + kRing + ofs) {}
  __device__ __forceinline__ uint32_t bar() const { return full + 8 * bi; }
  __device__ __forceinline__ uint32_t dst() const { return dst0 + bi * SLOT; }
  __device__ __forceinline__ void acquire_first() const {
    const bool first = j < NSLOT;
    mbar_wait(full + (first ? 8 * min(j, 3) - 32 : 8 * (NSLOT + bi)), PH == 2 && first ? 0 : par);
  }
  __device__ __forceinline__ void acquire() const { mbar_wait(full + 8 * (NSLOT + bi), par); }
  __device__ __forceinline__ void next() {
    j++;
    if (++bi == NSLOT) { bi = 0; par ^= 1; }
  }
};

__device__ __forceinline__ void check_blocks(const Params& p, Scratch* sc, uint32_t sb, int r, int c, bool g3, uint32_t& par) {
  const int lane = fresh_tid() & 31, nslot = g3 ? 4 : 5, slot_bytes = g3 ? 40960 : 32768;
  const uint32_t mine = (lane >> 2) * 132 + (lane & 3) * 32, ring_end = sb + kRing + kStage + mine;
  const uint32_t to_full = 8 * (kLandBar - (g3 ? ring_base(2) : ring_base(1)));
  uint32_t src = sb + kRing + mine + (g3 ? 0 : 4 * 32768);
  int bi = g3 ? 0 : 4, spins = 0;
#pragma unroll 1
  for (int i = g3 ? 2 : 9; i < 16;) {
    const uint32_t land = sb + kBars + 8 * (kLandBar + bi);
    mbar_wait(land, (par >> bi) & 1);
    uint32_t v[16];
#pragma unroll
    for (int k = 0; k < 16; k++) v[k] = lds32(src + k * 1024);
#pragma unroll
    for (int k = 0; k < 5; k++) v[k] = max(max(v[3 * k + 1], v[3 * k + 2]), k ? v[3 * k] : max(v[0], v[15]));
    const bool again = __any_sync(~0u, max(max(max(v[0], v[1]), v[2]), max(v[3], v[4])) == kPoison);
    asm volatile("{\n.reg .pred p;\nsetp.eq.u32 p, %1, 0;\n@p mbarrier.arrive.shared::cta.b64 _, [%0];\n}\n"
                 ::"r"(land - to_full), "r"(lane + again) : "memory");
    par ^= 1u << bi;
    if (again) {
      if (++spins > 100000) __trap();
      if (elect_one()) {
        mbar_expect_tx(land, 16384);
        tma2d(src - mine, g3 ? &p.h : &p.o, (g3 ? g3_block(i + 2, c) : g2_block(i, c)) * 64, r * 128, land);
      }
      nb_sync(kNbSelf + 1, 32);
      continue;
    }
    if (lane == 0 && (i == 2 || i == 3 || (!g3 && (i == 9 || i == 12)))) TS(i < 4 ? 88 + 2 * i : i == 9 ? 120 : 122);
    i++;
    if (++bi == nslot) bi = 0;
    src += slot_bytes;
    if (src == ring_end) src -= kStage;
  }
}

__device__ __forceinline__ void colsum_cta(const Params& p, Scratch* sc, uint32_t sb, int warp, int bid) {
  constexpr int kSlots = 4, kSlot = 49152;
  constexpr int kRows = kTail * 32768;
  static_assert(kRows + 65536 <= kCs, "");
  const int lane = threadIdx.x & 31, c0 = (bid - 128) * 2;
  const uint32_t full = sb + kBars, empty = full + 8 * kSlots;
  const uint32_t event = full + 64, stored = full + 96, rfull = full + 128, rempty = full + 192;
  if (threadIdx.x == 0) {
#pragma unroll 1
    for (int i = 0; i < 32; i++) mbar_init(full + 8 * i, i & (i < 16 ? 4 : 8) ? 8 : 1);
    asm volatile("fence.mbarrier_init.release.cluster;" ::: "memory");
  }
  __syncthreads();
  const uint32_t ep = ld_epoch(sc);
  if (warp == 8) {
    if (elect_one()) {
#pragma unroll 1
      for (int n = 0; n < 112 + kSlots; n++) {
        const int u = n >> 4, c = c0 + ((n >> 3) & 1), k0 = (n & 7) * 128, slot = n & (kSlots - 1);
        if (n == kQuietAt) flag_wait(sc->flags + kFlPace, ep);
        const uint32_t bar = full + 8 * slot;
        mbar_wait(empty + 8 * slot, ((n / kSlots) & 1) ^ 1);
        if (n == 108) mbar_arrive(event);
        if (u == 7) continue;
        mbar_expect_tx(bar, u == 6 ? 32768 : 49152);
#pragma unroll
        for (int a = 0; a < 3; a++) {
          if (a == 2 && u == 6) break;
          const CUtensorMap* m = u < 2 ? &p.wqkv : g3_is_up(u - 2, a) ? &p.wu : &p.wg;
          const int col = (u < 2 ? a * 16 + u * 8 + c : g3_atom(u - 2, a, c)) * 64;
          tma2d(sb + slot * kSlot + a * 8192, m, col, k0, bar);
          tma2d(sb + slot * kSlot + a * 8192 + 24576, m, col, k0 + 64, bar);
        }
      }
      mbar_wait(event + 8, 0);
      fence_async();
#pragma unroll 1
      for (int n = 0, r = 0, i = 0; r < 16; n++) {
        const uint32_t bar = rfull + 8 * (n & 7);
        mbar_wait(bar + 64, ~n >> 3 & 1);
        mbar_expect_tx(bar, r ? 8192 : 40960);
        tma2d(sb + kRows + (n & 7) * 8192, &p.hhst, i * (7 * 64), r * 128, bar);
#pragma unroll 1
        for (int a = r ? 4 : 0; a < 4; a++) tma2d(sb + i * 32768 + a * 8192, &p.wd, (c0 * 2 + a) * 64, i * (7 * 64), bar);
        if (++i == kTail) { i = 0; r++; }
      }
    }
  } else if (warp < 8) {
    uint32_t src[3];
#pragma unroll
    for (int j = 0; j < 3; j++) src[j] = sb + ((warp * 3 + j) >> 3) * 8192 + lane * 128 + ((((warp * 3 + j) & 7) ^ (lane & 7)) << 4);
    const uint32_t ones = 0x3F803F80u;
#pragma unroll 1
    for (int s = 0; s < 112; s++) {
      float a[3][2][4] = {};
#pragma unroll 1
      for (;; s++) {
      const int slot = s & (kSlots - 1);
      mbar_wait(full + 8 * slot, (s / kSlots) & 1);
      uint32_t b[3][4][4];
#pragma unroll
      for (int j = 0; j < 3; j++)
#pragma unroll
        for (int k = 0; k < 4; k++)
          asm volatile("ldmatrix.sync.aligned.m8n8.x4.trans.shared.b16 {%0,%1,%2,%3}, [%4];"
                       : "=r"(b[j][k][0]), "=r"(b[j][k][1]), "=r"(b[j][k][2]), "=r"(b[j][k][3])
                       : "r"(src[j] + slot * kSlot + (k >> 1) * 24576 + (k & 1) * 4096) : "memory");
      __syncwarp();
      if (lane == 0) mbar_arrive(empty + 8 * slot);
#pragma unroll
      for (int k = 0; k < 4; k++)
#pragma unroll
        for (int j = 0; j < 3; j++) {
          mma16816(a[j][0], ones, ones, ones, ones, b[j][k][0], b[j][k][1]);
          mma16816(a[j][1], ones, ones, ones, ones, b[j][k][2], b[j][k][3]);
        }
      if ((s & 7) == 7) break;
      }
      {
        if (lane < 12) {
          const int j = lane >> 2;
          const float x = j == 0 ? a[0][0][0] + a[0][1][0] : j == 1 ? a[1][0][0] + a[1][1][0] : a[2][0][0] + a[2][1][0];
          const float y = j == 0 ? a[0][0][1] + a[0][1][1] : j == 1 ? a[1][0][1] + a[1][1][1] : a[2][0][1] + a[2][1][1];
          const float x1 = bf_rest(x), y1 = bf_rest(y);
          const bool split = s < 32;
          st_b128(sc->cs + ((s >> 4) * 8 + c0 + ((s >> 3) & 1)) * 96 + warp * 12 + lane, split ? bf_upper(x, y) : __float_as_uint(x),
                  split ? bf_upper(x1, y1) : __float_as_uint(y), bf_upper(bf_rest(x1), bf_rest(y1)), ep);
        }
        if (threadIdx.x == 0 && (s & 8)) TSK(s >> 4);
      }
    }
    const int wg = warp >> 2;
#pragma unroll 1
    for (int r = wg; r < 16; r += 2) {
      float acc[128];
#pragma unroll
      for (int i = 0; i < 128; i++) asm volatile("" : "=f"(acc[i]));
      const uint32_t da = desc_lo(sb + kRows, 16);
      uint32_t db = desc_lo(sb, 8192);
      int n = r * kTail - 1;
      if (r) nb_sync(kNbOrder + wg, 256);
#pragma unroll 1
      for (int i = 0; i < kTail; i++, db += 2048) {
        const uint32_t done = rempty + 8 * (n & 7);
        n++;
        mbar_wait(rfull + 8 * (n & 7), n >> 3 & 1);
        wg_fence();
#pragma unroll
        for (int k = 0; k < 4; k++) wgmma_n256(acc, desc(da + (n & 7) * 512) + k * 2, desc(db) + k * 128, k | i);
        wg_commit();
        wg_wait<1>();
        if (lane < 2 && i) mbar_arrive(done);
      }
      if (r < 15) nb_arrive(kNbOrder + (wg ^ 1), 256);
      wg_wait<0>();
#pragma unroll
      for (int i = 0; i < 128; i++) asm volatile("" : "+f"(acc[i])::"memory");
      if (lane < 2) mbar_arrive(rempty + 8 * (n & 7));
#pragma unroll
      for (int i = 0; i < 16; i++) {
        const float* v = &acc[8 * i];
        __stcg(sc->part + (r * 8 + c0) * 1024 + (warp & 3) * 256 + lane + (i >> 3) * 1024 + (i & 7) * 32,
               make_uint4(pack_bf16(v[0], v[1]), pack_bf16(v[2], v[3]), pack_bf16(v[4], v[5]), pack_bf16(v[6], v[7])));
      }
      __syncwarp();
      if ((r & 2) && lane == 0) mbar_arrive(stored + 8 * (r >> 2));
    }
  } else if (warp == 10) {
    mbar_wait(event, 0);
    flag_wait(sc->flags + kFlHH + (lane & 15) * kFlRow, ep * 8);
    fence_async();
    __syncwarp();
    if (lane == 0) mbar_arrive(event + 8);
  } else if (threadIdx.x == 352) {
#pragma unroll 1
    for (int r = 0; r < 16; r += 4) {
      mbar_wait(stored + 2 * r, 0);
      flag_signal(sc->flags + kFlPart + (c0 >> 1) + r * kFlRow);
    }
    TSK(7);
  }
}

#define PROF_BEGIN
template <bool BY_SM>
__global__ void __cluster_dims__(2, 1, 1) __launch_bounds__(kThreads, 1) fused_block_kernel(Scratch* sc, const __nv_bfloat16* xp, const __nv_bfloat16* wqkvp, __nv_bfloat16* outp,
                                                                   const __grid_constant__ Params p) {
  extern __shared__ __align__(1024) uint8_t smem_raw[];
  if (threadIdx.x < 56) {
    const int l = threadIdx.x & 31, b = blockIdx.x & 127;
    if (threadIdx.x < 32) prefetch_l2(xp + (b * 16 + (l & 15)) * kD + (l >> 4) * 64);
    else prefetch_l2(wqkvp + b * (3 * kD) + (l >> 3) * kD + (l & 7) * 64);
  }
  const uint32_t sb = smem_u32(smem_raw);
  const int bid = role_id<BY_SM>();
  const int r = bid >> 3, c = bid & 7, rank = blockIdx.x & 1;
  auto first_fill = [&](int j) {
    const uint32_t fb = sb + kBars + 8 * j, dst = sb + kRing + j * 40960;
    mbar_expect_tx(fb, 40960);
    tma3d(j >> 1 == c ? sb + kOwn + (j & 1) * 16384 : dst, &p.x, j * 64, (r >> 1) * 128, rank, fb);
#pragma unroll
    for (int a = 0; a < 3; a++) tma2d(dst + 16384 + a * 8192, &p.wqkv, a * kD + c * 64, j * 64, fb);
    mbar_arrive(fb);
  };
  const int tid = threadIdx.x, warp = __shfl_sync(~0u, tid >> 5, 0), wg = warp >> 2;
  if (bid >= 128) {
    if (tid == 0) PROF_BEGIN;
    colsum_cta(p, sc, sb, warp, bid);
    return;
  }
  if (wg == 2) {
    if (warp == 8 && elect_one()) {
#pragma unroll
      for (int j = 0; j < 4; j++) mbar_init(sb + kBars + 8 * j, 2);
      asm volatile("fence.mbarrier_init.release.cluster;" ::: "memory");
      first_fill(0);
      TSS(0);
    }
    __syncwarp();
    if (warp == 8) nb_arrive(kNbOrder, 160);
    asm volatile("setmaxnreg.dec.sync.aligned.u32 40;");
    if (warp == 8) {
      cluster_arrive();
      if (elect_one()) {
#pragma unroll 1
        for (int j = 1; j < 4; j++) first_fill(j);
        TSS(1);
      }
      __syncwarp();
    } else {
      if (elect_one()) {
        uint64_t shifts = warp == 9 ? bar_shifts(4) : warp == 10 ? bar_shifts(22) : bar_shifts(40);
#pragma unroll 1
        for (int i = 0; i < 18; i++, shifts >>= 3) mbar_init(sb + kBars + 8 * (18 * warp - 158 + i), 1u << (shifts & 7));
        sts32(sb + kZero, 0);
        sts32(sb + kScale + 4, 0);
        sts32(sb + kRole, bid);
        sts128(sb + kOnes, make_uint4(0x3F803F80u, 0, 0, 0x3F803F80u));
        asm volatile("fence.mbarrier_init.release.cluster;" ::: "memory");
      }
      __syncwarp();
      cluster_arrive();
    }
    cluster_wait();
    const uint32_t ep = ld_epoch(sc);
    if (tid == 320) sts32(sb + kEpoch, ep);
    if (tid == 320) PROF_BEGIN;
    const int pw = warp & 3;
    if (pw == 0) {
      if (elect_one()) {
        const int row = r * 128;
        const uint32_t land = sb + kBars + 8 * kLandBar;
#pragma unroll 1
        for (Ring<0> q(sb, 0); q.j < 32; q.next()) {
          q.acquire();
          const int kb = g1_block(q.j, c);
          if (q.j >= 16 && (q.j < 20 || kb >> 1 == c)) { mbar_arrive(q.bar()); continue; }
          mbar_expect_tx(q.bar(), 16384);
          tma3d(kb >> 1 == c ? sb + kOwn + (kb & 1) * 16384 : q.dst(), &p.x, kb * 64, (r >> 1) * 128, rank, q.bar());
        }
        prefetch_map(&p.o);
        prefetch_map(&p.o16);
        flag_wait(sc->flags + kFlO + r * kFlRow, ep * 8);
        fence_async();
        TS(40);
#pragma unroll 1
        for (Ring<1> q(sb, 0); q.j < 16; q.next()) {
          q.acquire_first();
          if (q.j == 8) {
            prefetch_map(&p.wg);
            prefetch_map(&p.wu);
            prefetch_map(&p.h);
            prefetch_map(&p.h16);
            mbar_wait(sb + kBars + 8 * kSentBar, 0);
            mbar_arrive(q.bar());
            mbar_arrive(sb + kBars + 8 * (kStgBar + 1));
            if (bid == 0) __stcg(sc->flags + kFlPace, ep);
            __nanosleep(kGateONs);
            continue;
          }
          const uint32_t bar = q.j < 8 ? q.bar() : land + 8 * q.bi;
          if (q.j == 9) TS(41);
          mbar_expect_tx(bar, 16384);
          tma2d(q.dst(), &p.o, g2_block(q.j, c) * 64, row, bar);
        }
#pragma unroll 1
        for (Ring<2> q(sb, 0); q.j < 64; q.next()) {
          q.acquire_first();
          if ((0x000F000F003C000Full >> q.j & 1) && q.j != 28 + c) { mbar_arrive(q.bar()); continue; }
          if (q.j == 4) { __nanosleep(kGateHNs); TS(42); }
          const uint32_t bar = q.j < 18 ? land + 8 * q.bi : q.bar();
          mbar_expect_tx(bar, 16384);
          tma2d(q.dst(), &p.h, g3_block(q.j, c) * 64, row, bar);
        }
        prefetch_map(&p.hh);
        prefetch_map(&p.out);
        Ring<3> q(sb, 0);
#pragma unroll 1
        for (; q.j < 16; q.next()) {
          q.acquire_first();
          if (q.j == 0) { mbar_arrive(q.bar()); continue; }
          mbar_expect_tx(q.bar(), 16384);
          tma2d(q.dst(), &p.h, ((q.j + 9) & 15) * 64, row, q.bar());
        }
#pragma unroll 1
        for (int wv = 0; wv < 5; wv++) {
          if (wv == 3 && c < kTail) tma_prefetch2d(&p.hhst, c * (7 * 64), row + 64);
          if (wv == 0 || wv >= 3) {
            mbar_wait(sb + kBars + 8 * (kWaveBar + (wv >> 1)), 0);
            fence_async();
          }
          const int dbl = wv == 2 || wv == 3, f0 = wv == 4 ? 6 : (wv & 1) * 3 + dbl;
#pragma unroll 1
          for (int i = wv ? 0 : kTail; i < 8 << dbl; i++, q.next()) {
            q.acquire();
            mbar_expect_tx(q.bar(), 16384);
            tma2d(q.dst(), &p.hh, ((i >> dbl) * 7 + f0 + (i & dbl)) * 64, row, q.bar());
          }
        }
#pragma unroll 1
        for (int i = 0; i < kTail - 1; i++, q.next()) {
          q.acquire();
          mbar_expect_tx(q.bar(), i < 3 ? 16384 : 8192);
          tma2d(q.dst() + 8192, &p.hhst, i * (7 * 64), row + 64, q.bar());
          if (i == 2) tma2d(q.dst(), &p.hhst, (kTail - 1) * (7 * 64), row + 64, q.bar());
          if (i == rank) tma2d_mc(q.dst(), &p.wd, (c * 2 + rank) * 64, (kTail - 1) * (7 * 64), q.bar());
        }
      }
    } else if (pw == 1) {
      if (elect_one()) {
        const int rp = r >> 1;
#pragma unroll 1
        for (Ring<0> q(sb, 16384); q.j < 32; q.next()) {
          q.acquire();
          mbar_expect_tx(q.bar(), 24576);
          const int col = ((q.j >> 4) * 8 + c) * 64, k0 = g1_block(q.j, c) * 64;
          tma2d_mc(q.dst() + rank * 8192, &p.wqkv, rank * kD + col, k0, q.bar());
          if ((q.j & 1) == rank) tma2d_mc(q.dst() + 16384, &p.wqkv, 2 * kD + col, k0, q.bar());
          if (q.j == max(r, 4))
            for (int a = 0; a < 3; a++) tma_prefetch2d(&p.wqkv, a * kD + (8 + c) * 64, ((r + 12) & 15) * 64);
          if (q.j >> 1 == rp + 8) tma_prefetch2d(&p.wo, (c * 2 + rank) * 64, (q.j & 15) * 64);
        }
        if (r < 6) tma_prefetch2d(rp == 1 ? &p.wu : &p.wg, (c * 7 + 3 + (rp >> 1)) * 64, (c * 2 + rank) * 64);
#pragma unroll 1
        for (Ring<1> q(sb, 16384 + rank * 8192); q.j < 16; q.next()) {
          q.acquire_first();
          mbar_expect_tx(q.bar(), 16384);
          tma2d_mc(q.dst(), &p.wo, (c * 2 + rank) * 64, g2_block(q.j, c) * 64, q.bar());
        }
        const CUtensorMap* mine = rank ? &p.wu : &p.wg;
#pragma unroll 1
        for (Ring<2> q(sb, 16384); q.j < 64; q.next()) {
          const int tile = g3_tile(q.j), f0 = c * 7 + (tile & 1) * 3, fp = f0 + (tile & 2);
          const int k0 = g3_block(q.j, c) * 64;
          q.acquire_first();
          mbar_expect_tx(q.bar(), 24576);
          const uint32_t dst = q.j < 4 ? sb + kRing + (q.j + 1) * 32768 : q.dst();
          tma2d_mc(dst + rank * 8192, mine, fp * 64, k0, q.bar());
          if ((q.j & 1) == rank) tma2d_mc(dst + 16384, tile & 2 ? &p.wu : &p.wg, (f0 + 1) * 64, k0, q.bar());
          const int d = q.j - kPfStep - (c & 1) * 5 - (r >> 2);
          if (d == 0 || d == 11 || d == 22) {
            const int f = c * 7 + (d == 0 ? 2 : d == 11 ? 5 : 6);
            tma_prefetch2d(&p.wg, f * 64, r * 64);
            tma_prefetch2d(&p.wu, f * 64, r * 64);
            if (d != 22) tma_prefetch2d(&p.wu, (f - 1) * 64, r * 64);
            else if (rp < kTail) tma_prefetch2d(&p.wd, (c * 2 + rank) * 64, rp * (7 * 64));
          }
          if (q.j >> 1 == rp + 24) tma_prefetch2d(&p.wd, (c * 2 + rank) * 64, g4_block(q.j & 15) * 64);
        }
        Ring<3> q(sb, 16384 + rank * 8192);
#pragma unroll 1
        for (; q.j < 16; q.next()) {
          q.acquire_first();
          mbar_expect_tx(q.bar(), 16384);
          tma2d_mc(q.dst(), mine, (c * 7 + 6) * 64, ((q.j + 9) & 15) * 64, q.bar());
          if (q.j >> 1 == rp) tma_prefetch2d(&p.wd, (c * 2 + rank) * 64, g4_block(q.j + 16) * 64);
        }
#pragma unroll 1
        for (int wv = 0; wv < 6; wv++) {
          const int dbl = wv == 2 || wv == 3, f0 = wv == 4 ? 6 : wv == 5 ? 0 : (wv & 1) * 3 + dbl;
#pragma unroll 1
          for (int i = wv ? 0 : kTail; i < (wv == 5 ? kTail - 1 : 8 << dbl); i++, q.next()) {
            q.acquire();
            mbar_expect_tx(q.bar(), 16384);
            tma2d_mc(q.dst(), &p.wd, (c * 2 + rank) * 64, ((i >> dbl) * 7 + f0 + (i & dbl)) * 64, q.bar());
            __builtin_assume(q.j >= 16);
            if ((q.j & 15) >> 1 == rp && q.j < 40 + kTail) tma_prefetch2d(&p.wd, (c * 2 + rank) * 64, g4_block(q.j + 16) * 64);
          }
        }
      }
    } else {
      const int cw = pw - 2;
      const uint32_t stg = sb + kStage + cw * 32768, rb = sb + kBars + 8 * kResBar;
      uint32_t land_par = 0;
      if (cw == 0) {
#pragma unroll 1
        for (int i = 0; i < 16; i++) sts128(sb + kFill + i * 512 + (tid & 31) * 16, make_uint4(kPoison, kPoison, kPoison, kPoison));
        __nanosleep(kSampleNs);
        const uint32_t l15 = tid & 15;
        const uint4 os = __ldg(p.wop + ((tid & 31) * 128 + c * 16 + l15));
        const uint4 gs = __ldg((tid & 16 ? p.wup : p.wgp) + (l15 * 451 + c * 56));
        const uint4 ws = __ldg((const uint4*)wqkvp + ((tid & 7) * 385 + (tid & 24) * 16 + (8 + c) * 8));
        sts64(sb + kScale, __float_as_uint(low_peak(os) * kBias3 * low_peak(gs)), __float_as_uint(low_peak(ws) * kBias1) | 1);
        if (tid == 320) TS(93);
      }
#pragma unroll 1
      for (int ev = -1; ev < 4; ev++) {
        const bool quads = cw == 0 && ev == 1;
        if (ev >= cw && !quads) nb_sync(kNbPub + cw, 160);
        if (ev >= cw && elect_one()) {
          if (quads) {
            mbar_wait(sb + kBars + 8 * (kHalfBar + 1), 0);
#pragma unroll 1
            for (int i = 0; i < 2; i++) {
              __nanosleep(i ? kPaceNs : kHoldNs);
              tma_store2d(&p.hst, stg + 16384 + i * 8192, c * 128 + 64, r * 128 + i * 64);
              TS(100 + i);
            }
            bulk_commit();
            bulk_wait_read();
            mbar_arrive(sb + kBars + 8 * kStgBar);
          } else {
            const int it = ev - 2 + cw, f0 = c * 7 + (1 - cw) * 3, fp = it == 2 ? c * 7 + 6 : f0 + 2 * it;
            const bool is_o = ev == 0;
            const CUtensorMap* m = is_o ? &p.ost : &p.hhst;
            const int b0 = is_o ? c : f0 + 1, b1 = fp;
#pragma unroll 1
            for (int i = is_o || it == 1 ? 0 : 2; i < (is_o ? 2 : 4); i++) {
              tma_store2d(m, stg + i * 8192, (i < 2 ? b0 : b1) * 64, r * 128 + (i & 1) * 64);
              if (!is_o) {
                bulk_commit();
                bulk_wait_read();
                __nanosleep(kPaceNs);
              }
            }
            bulk_commit();
            bulk_wait_all();
            mbar_arrive(sb + kBars + 8 * (kStgBar + cw));
            flag_signal(sc->flags + kFlHH + ev * 2 - 3 + cw + r * kFlRow);
            TS(44 + cw * 8 + ev);
            if (ev == 2 && cw) {
              mbar_expect_tx(rb, 16384);
#pragma unroll 1
              for (int i = 0; i < 2; i++) tma2d(stg + 8192 + i * 16384, &p.hst, c * 128 + i * 64, r * 128 + 64, rb);
            }
          }
        }
        nb_sync(kNbSelf + cw, 32);
        if (ev >= 2 && ev + cw >= 3 && elect_one()) {
          const int wv = cw == 0 ? 3 : ev == 2 ? 0 : 4;
#pragma unroll 1
          for (int i = wv; i <= max(wv, 2); i++) flag_wait(sc->flags + kFlHH + i + r * kFlRow, ep * 8);
          fence_async();
          mbar_arrive(sb + kBars + 8 * (kWaveBar + (wv >> 1)));
          if (wv == 4) {
            flag_wait(sc->flags + kFlPart + (c >> 1) + (r & 12) * kFlRow, ep);
            fence_async();
            mbar_expect_tx(sb + kBars + 8 * kPartBar, 32768);
#pragma unroll 1
            for (int i = 0; i < 2; i++) {
              tma2d(stg + 16384 + i * 8192, &p.hst, c * 128 + i * 64, r * 128, sb + kBars + 8 * kPartBar);
              asm volatile("cp.async.bulk.shared::cluster.global.mbarrier::complete_tx::bytes [%0], [%1], 8192, [%2];"
                           ::"r"(stg + i * 8192), "l"(sc->part + bid * 1024 + i * 512), "r"(sb + kBars + 8 * kPartBar) : "memory");
              __nanosleep(kPartNs);
            }
            TSK(56);
          }
        }
        nb_sync(kNbSelf + cw, 32);
#pragma unroll 1
        for (int sub = 0; ev < 3 && (ev != 0 || cw == 1); sub++) {
          nb_sync(kNbSelf + cw, 32);
          if (ev == 0) check_blocks(p, sc, sb, r, c, sub, land_par);
          const int u = ev < 0 ? cw : 2 * ev + 1 + cw, lane = fresh_tid() & 31;
          if (u == 1 && !sub) {
            uint3 st[5];
            load_tagged<5, true>(st, sc->stat1 + r * 128 + lane, 32, ep, (r < 2 ? -8 : -264) - (lane & 24));
#pragma unroll
            for (int i = 0; i < 4; i++) sts64(sb + kStat + (i * 32 + lane) * 8, st[i].x, st[i].y);
            sts64(sb + kStat - 64 + (lane & 7) * 8, st[4].x, st[4].y);
            nb_sync(kNbSelf + cw, 32);
            if (lane < 4) mbar_arrive(sb + kBars + 8 * kStatBar);
            if (lane == 0) TS(17);
          }
          if (u == 1) {
            const uint4* gh = sc->halo + ((sub * 16 + r - 2) * 8 + c) * 192 + lane;
            uint4 hv[6] = {};
            nb_sync(kNbHalo, 64);
            uint32_t ns = sub ? kHaloNs : 2 * kBackoffNs;
#pragma unroll 1
            for (int spins = 0; r >= 2; spins++) {
              if (ns) __nanosleep(ns);
              ns = sub ? 0 : kBackoffNs;
              if (spins > 2000000) __trap();
#pragma unroll
              for (int i = 0; i < 6; i++) hv[i] = ld_b128(gh + i * 32);
              uint32_t bad = (hv[5].y ^ ep) | (hv[5].z ^ ep);
#pragma unroll
              for (int i = 0; i < 6; i++) bad |= hv[i].w ^ ep;
              if (!__any_sync(~0u, bad != 0)) break;
            }
            const uint32_t dst = sb + kStage + sub * 32768 + lane * 16;
            sts128(dst, make_uint4(hv[0].x, hv[0].y, hv[0].z, hv[1].x));
            sts128(dst + 512, make_uint4(hv[1].y, hv[1].z, hv[2].x, hv[2].y));
            sts128(dst + 1024, make_uint4(hv[2].z, hv[3].x, hv[3].y, hv[3].z));
            sts128(dst + 1536, make_uint4(hv[4].x, hv[4].y, hv[4].z, hv[5].x));
            nb_arrive(kNbHalo + 1, 64);
            if (lane == 0) TS(123 + sub);
          }
          if (sub) break;
          uint3 v[3];
          load_tagged<3, false>(v, sc->cs + c * 96 + (u * 768 + lane), 32, ep);
          if (u < 2) {
#pragma unroll
            for (int i = 0; i < 3; i++)
#pragma unroll
              for (int k = 0; k < 8; k++)
                sts32(sb + kAug + cw * 4096 + i * 1024 + k * 128 + ((lane * 4) ^ (k * 16)), k == 7 ? 0x3F803F80u : k == 4 || k == 6 ? v[i].z : k & 1 && k != 5 ? v[i].y : v[i].x);
            fence_async_smem();
          } else {
#pragma unroll
            for (int i = 0; i < 3; i++) sts64(sb + kCs + cw * 768 + (i * 32 + lane) * 8, v[i].x, v[i].y);
          }
          nb_sync(kNbSelf + cw, 32);
          if (lane == 0) { mbar_arrive(sb + kBars + 8 * (kAuxBar + cw)); TS(104 + u); }
        }
        nb_sync(kNbSelf + cw, 32);
        if (ev < 0 && cw == 0 && elect_one()) {
#pragma unroll 1
          for (int i = 0; i < 6; i++) {
            __nanosleep(i == 0 ? (c >> 1) * (kFillNs / 4) : kFillNs);
            tma_store2d(i < 2 ? &p.ost : &p.hst, sb + kFill, i < 2 ? (8 + c) * 64 : (c * 2 - 1 + (i >> 1)) * 64, r * 128 + (i & 1) * 64);
            bulk_commit();
          }
          uint32_t peer;
          asm volatile("ld.shared::cluster.b32 %0, [%1];" : "=r"(peer) : "r"(map_cta(sb + kRole, rank ^ 1)) : "memory");
          if (peer != (bid ^ 8)) __trap();
          TS(90);
        }
        nb_sync(kNbSelf + cw, 32);
      }
    }
  } else {
    if (tid == 0) TSS(2);
    cluster_arrive();
    float bias = 0.f;
    float sx = 0.f, mx = 0.f;
    asm volatile("setmaxnreg.inc.sync.aligned.u32 232;");
    if (tid == 0) TSS(4);
    int task;
    asm volatile("mov.u32 %0, %1;" : "=r"(task) : "r"(8 - wg));

#pragma unroll 1
    for (task = __shfl_sync(~0u, task, 0);; task++) {
      if (task == 1 + wg || task == 9 - wg) {
        const int t = fresh_tid();
        uint2 scale;
        do asm volatile("ld.volatile.shared.v2.b32 {%0, %1}, [%2];" : "=r"(scale.x), "=r"(scale.y) : "r"(sb + kScale) : "memory");
        while (scale.y == 0);
        __syncwarp();
        bias = bias_at(low_peak(lds128(sb + (task > 5 ? kRing : kStage + wg * 32768) + (t & 126) * 64 + (t & 14) * 8 + (t & 1) * 8192)) *
                       __uint_as_float(task > 5 ? scale.y : scale.x));
        if (t == 128 && task > 5) TS(95);
      }
      if (wg == 0 && (task == 1 || task == 4)) {
        float acc[2][96];
        const int t = fresh_tid() & 127;
        const uint32_t frag = sb + kOwn + ((t >> 5) * 16 + (t & 15)) * 128, frag_x = ((t >> 4) & 1) ^ (t & 7);
        TSG(2);
        if (task == 4) mbar_wait(sb + kBars + 8 * kResBar, 0);
        auto residual = [&](int m) {
#pragma unroll
          for (int i = 0; i < 8; i++) {
            uint32_t v[4];
            ldsm4(frag + (i >> 2) * 16384 + m * 8192 + ((frag_x ^ (i * 2 & 6)) << 4), v);
#pragma unroll
            for (int e = 0; e < 4; e++) {
              float* d = &acc[m][8 * i + 2 * e];
              asm("shl.b32 %0, %1, 16;" : "=f"(d[0]) : "r"(v[e]));
              asm("and.b32 %0, %1, 0xFFFF0000;" : "=f"(d[1]) : "r"(v[e]));
            }
          }
        };
        residual(1);
        if (task == 1) {
          residual(0);
        } else {
#pragma unroll
          for (int i = 0; i < 64; i++) acc[0][i] = 0.f;
        }
        __syncwarp();
        if ((t & 31) == 0) mbar_arrive(sb + kBars + 8 * kResFreeBar);
        TSG(4);
        if ((tid & 127) == 0) TS(task == 1 ? 6 : 14);
        if (task == 4) {
          mainloop<128, kTail>(sc, acc, sb, 3, 16, 56, -2, true, false, false, 0, -1, &p.out, c * 128, (r >> 1) * 128, warp, outp);
          if ((tid & 127) == 0) TSK(15);
          if (fresh_tid() == 0) {
            if (bid == 0) __stcg(sc->epoch, lds32(sb + kEpoch));
            TSK(19);
          }
          break;
        }
        mainloop<128, -1>(sc, acc, sb, 1, 0, 15, kPauseG2, false, true, false, 0);
        const int t2 = fresh_tid() & 127;
        const uint32_t frag2 = sb + kStage + ((t2 >> 5) * 16 + (t2 & 15)) * 128, frag2_x = ((t2 >> 4) & 1) ^ (t2 & 7);
        const uint32_t empty = map_cta(sb + kBars + 8 * (ring_base(1) + 5), t2 & 1);
        mbar_wait(sb + kBars + 8 * kStgBar, 0);
        mbar_wait(sb + kBars + 8 * ring_base(1), 1);
#pragma unroll
        for (int m = 0; m < 2; m++) {
          const uint32_t a = desc_lo(sb + kRing, 16);
          wg_fence();
#pragma unroll
          for (int k = 0; k < 4; k++) wgmma_n128(acc[m], desc_kept(a, sb) + (m * 512 + k * 2), desc_kept(a, sb) + (kToB + k * 128));
          wg_commit();
          if (m) nb_arrive(kNbOrder + 1, 256);
          wg_wait<1>();
          if (!m) mbar_arrive_cluster_if(empty + 8 * 4, (t2 & 31) < 2);
        }
#pragma unroll
        for (int b = 0; b < 4; b++) {
          if (b == 1) {
            wg_wait<0>();
            if (t2 == 0) TSK(7);
          }
          if (b < 2) {
#pragma unroll
            for (int i = 0; i < 64; i++) asm volatile("" : "+f"(acc[b][i])::"memory");
          }
          stage_quarter(&acc[b & 1][32 * (b >> 1)], frag2, frag2_x, b);
          if (b & 1) {
            fence_async_smem();
            __syncwarp();
            if (elect_one()) {
              mbar_arrive(sb + kBars + 8 * (kHalfBar + (b >> 1)));
#pragma unroll
              for (int m = 0; m < 2; m++)
                if (b == 1) tma_store2d(&p.h16, sb + kStage + m * 8192 + warp * 2048, c * 128, r * 128 + m * 64 + warp * 16);
            }
            __syncwarp();
          }
        }
        if (t2 == 0) TS(8);
        sx = mx = 0.f;
        continue;
      }
      float acc[2][96];
      if (task == 8 + wg) {
        wg_fence();
#pragma unroll
        for (int m = 0; m < 2; m++) wgmma_n192_any(acc[m], desc(64 + m), desc(64 + m));
        wg_commit();
        wg_wait<0>();
#pragma unroll
        for (int i = 0; i < 96; i++) asm volatile("" : "+f"(acc[0][i]), "+f"(acc[1][i])::"memory");
      } else {
        const uint32_t z = fresh_tid() >> 10;
#pragma unroll
        for (int i = 0; i < 96; i++) {
#pragma unroll
          for (int m = 0; m < 2; m++) {
            if ((2 * i + m) % kInitMix == kInitMix - 1) asm("fma.rn.f32 %0, %1, %2, %3;" : "=f"(acc[m][i]) : "f"(__uint_as_float(z)), "f"(2 * i + m + 2.f), "f"(bias));
            else asm("{\n.reg .b32 t;\nlop3.b32 t, %1, %2, %3, 0xEA;\nmov.b32 %0, t;\n}\n" : "=f"(acc[m][i]) : "r"(z), "r"(2 * i + m + 1), "r"(__float_as_uint(bias)));
          }
        }
      }
      if (task > 5) {
      if (wg) {
        if (task == 7) cluster_wait();
        if (tid == 128 && task == 7) { TSS(5); TSK(69); }
        const int t = fresh_tid() & 127, lr = c * 16 + (t >> 3);
        uint32_t pf = t < 64 ? (bid * 16 + (t >> 2)) * kD + (t & 3) * 64 : (r * 48 + t - 64) * kD + c * 64;
        const uint32_t src = sb + kRing + lr * 128 + (((t ^ lr) & 7) << 4), empty = map_cta(sb + kBars + 8 * 4, t & 1), zero = fresh_tid() >> 10;
#pragma unroll 1
        for (int j = task == 7 ? 0 : kSplit; j < (task == 7 ? kSplit : 16); j++) {
          mbar_wait(sb + kBars + 8 * (j & 3), (j >> 2) & 1);
          if (j < 2 && t == 0) TS(102 + j);
          const uint4 v = lds128(src + (j >> 1 == c ? kOwn + (j & 1) * 16384 : (j & 3) * 40960));
          __syncwarp();
          mbar_arrive_cluster_if(empty + 8 * (j & 3) + (v.x & zero), (t & 31) < 2);
          if ((j == 0 || j == 3 || j == 6) && t < 112) { pf += t < 64 ? 256 : 256 * 3 * kD; prefetch_l2((t < 64 ? xp : wqkvp) + pf); }
          const uint32_t u[4] = {v.x, v.y, v.z, v.w};
#pragma unroll
          for (int e = 0; e < 4; e++) {
            const float d0 = bf_lo(u[e]), d1 = bf_hi(u[e]);
            sx += d0 + d1;
            mx = fmaf(d1, d1, fmaf(d0, d0, mx));
          }
        }
        if (task == 7) {
          if (t == 0) TS(96);
          continue;
        }
#pragma unroll
        for (int o = 4; o > 0; o >>= 1) { sx += __shfl_xor_sync(~0u, sx, o); mx += __shfl_xor_sync(~0u, mx, o); }
        const float mean = sx * (1.f / kD);
        float rstd;
        asm("rsqrt.approx.ftz.f32 %0, %1;" : "=f"(rstd) : "f"(fmaxf(mx * (1.f / kD) - mean * mean, 0.f) + 1e-5f));
        const uint32_t ep = lds32(sb + kEpoch);
        const int t2 = fresh_tid();
        if ((t2 & 7) == 0) st_b128(sc->stat1 + (bid * 16 + (t2 >> 3 & 15)), __float_as_uint(rstd), __float_as_uint(-mean), ep, ep);
        if (t == 0) TS(16);
      }
      if (tid == 0) TSS(6);
      mainloop<192, -1>(sc, acc, sb, 0, wg * 16, wg ? 16 - kAhead : 16, wg ? kPauseG1 : -2, false, wg == 0, false, wg,
                        wg ? min((c + 2) & 7, 6) : c);
      const int t = fresh_tid() & 127, w = warp & 3, lane = t & 31, g = lane >> 2, q = lane & 3;
      const uint32_t stg = sb + kStage + wg * 32768;
      auto tail = [&](int m, int k0, int k1) {
        wg_fence();
#pragma unroll
        for (int k = k0; k < k1; k++) {
          const uint64_t a = desc_kept(desc_lo(sb + kRing, 16), sb) + (4 - kAhead + (k >> 2)) * (40960 >> 4);
          wgmma_n192(acc[m], a + (m * 512 + (k & 3) * 2), a + (kToB + (k & 3) * 128));
        }
      };
      auto release = [&](int j, bool cond) { mbar_arrive_cluster_if(map_cta(sb + kBars + 8 * (4 + (j & 3)), lane & 1), cond); };
      if (wg) {
#pragma unroll
        for (int j = 32 - kAhead; j < 32; j++) {
          TST(2 * (j & 1));
          mbar_wait(sb + kBars + 8 * (j & 3), 1);
          TST(2 * (j & 1) + 1);
          tail(1, 4 * (j - 32 + kAhead), 4 * (j - 31 + kAhead));
          wg_commit();
          if (j == 32 - kAhead) {
            wg_wait<1>();
            release(j - 1, lane < 4);
            mbar_wait(sb + kBars + 8 * kResFreeBar, 0);
          }
        }
      } else {
        nb_arrive(kNbOrder + 1, 256);
        wg_wait<0>();
        release(15, lane < 2);
        if (t == 0) TSK(1);
      }
      TST(4);
      mbar_wait(sb + kBars + 8 * (kAuxBar + wg), 0);
      mbar_wait(sb + kBars + 8 * kStatBar, 0);
      {
        uint32_t am[4];
#pragma unroll
        for (int i = 0; i < 4; i++) {
          const float m1 = __uint_as_float(lds32(sb + kStat + (w * 16 + g) * 8 + 4 + (i >> 1) * 512 + (i & 1) * 64));
          const float m2 = bf_rest(m1), lo = q & 1 ? m2 : m1;
          am[i] = bf_upper(lo, q == 3 ? -bias : q == 2 ? bf_rest(m2) : lo);
        }
        const uint64_t db = (uint64_t)desc_lo(sb + kAug + wg * 4096, 1024) | (0x40000000ull << 32);
        TST(5);
        wg_fence();
        wgmma_n192_rs(acc[1], am[2], am[3], 0u, db);
        wg_commit();
        TST(6);
        wg_fence();
        wgmma_n192_rs(acc[0], am[0], am[1], 0u, db);
        wg_commit();
        if (wg) {
          tail(0, 0, 4 * kAhead);
          wg_commit();
          wg_wait<2>();
        } else {
          wg_wait<1>();
        }
        TST(8);
#pragma unroll
        for (int i = 0; i < 96; i++) asm volatile("" : "+f"(acc[1][i])::"memory");
      }
      const uint32_t ep = lds32(sb + kEpoch);
      uint32_t pk[2][48];
      auto fold = [&](int pp, int jn, int hf) {
        const uint32_t v = pack_bf16(acc[pp][4 * jn + 2 * hf], acc[pp][4 * jn + 2 * hf + 1]);
        pk[pp][2 * jn + hf] = jn >= 16 ? movm(v) : v;
      };
      if (t == 96) TS(115 + wg);
#pragma unroll
      for (int jn = 8; jn < 24; jn++) fold(1, jn, 1);
      if (w < 3) {
#pragma unroll
        for (int i = 0; i < 4; i++)
          sts128(stg + (w + 5) * 2048 + i * 512 + lane * 16, make_uint4(pk[1][17 + 8 * i], pk[1][19 + 8 * i], pk[1][21 + 8 * i], pk[1][23 + 8 * i]));
      } else if (r < 14) {
        uint4* gh = sc->halo + ((wg * 16 + r) * 8 + c) * 192 + lane;
#pragma unroll
        for (int i = 0; i < 6; i++) st_b128(gh + i * 32, pk[1][17 + 6 * i], i < 5 ? pk[1][(19 + 6 * i) % 48] : ep, i < 5 ? pk[1][(21 + 6 * i) % 48] : ep, ep);
        if (wg == 0) {
#pragma unroll 1
          for (int i = 0; i < 6; i++, gh += 32) st_b128(gh + 128 * 192, 0, 0, 0, ep - 1);
        }
      }
      if (w == 3) nb_arrive(kNbHalo, 64);
      if (wg) nb_arrive(kNbOrder, 256);
      TST(9);
      if (t == 96) TS(111 + wg);
#pragma unroll
      for (int jn = 23; jn >= 0; jn--) {
        fold(1, jn, 0);
        if (jn < 8) fold(1, jn, 1);
      }
      const bool sel0 = 2 * q > g, sel1 = 2 * q + 1 > g, no_prev = (r < 2 && w == 0);
      const uint4 ones = lds128(sb + kOnes);
      const uint32_t lowmask = (sel0 ? 0x0000FFFFu : 0u) | (sel1 ? 0xFFFF0000u : 0u) | ones.y;
      float rs[4][2], rk[4][2];
#pragma unroll
      for (int i = 0; i < 4; i++) {
        const uint32_t a = sb + kStat + w * 128 + (i >> 1) * 512 + (i & 1) * 64;
        const float rq = __uint_as_float(lds32(a + g * 8)) * (0.17677669529663687f * 1.4426950408889634f);
        rk[i][0] = __uint_as_float(lds32(a + q * 16 - (sel0 ? 64 : 0)));
        rk[i][1] = __uint_as_float(lds32(a + q * 16 + 8 - (sel1 ? 64 : 0)));
        rs[i][0] = rk[i][0] * rq;
        rs[i][1] = rk[i][1] * rq;
      }
      {
        uint32_t all = ~0u;
#pragma unroll
        for (int i = 0; i < 48; i++) if (i < 16 || !(i & 1)) all &= pk[1][i];
        if (all == kPoison) sts32(sb + kZero + 8, 0);
      }
      TST(10);
      wg_wait<0>();
      TST(11);
#pragma unroll
      for (int j = 32 - kAhead; j < 32; j++) release(j, lane < 4 * wg && (w != 0 || j < 31));
#pragma unroll
      for (int i = 0; i < 96; i++) asm volatile("" : "+f"(acc[0][i])::"memory");
      if (t == 0 && wg) TSK(21);
#pragma unroll
      for (int jn = 8; jn < 24; jn++) fold(0, jn, 1);
#pragma unroll
      for (int i = 0; i < 4; i++)
        sts128(stg + (w + 1) * 2048 + i * 512 + lane * 16, make_uint4(pk[0][17 + 8 * i], pk[0][19 + 8 * i], pk[0][21 + 8 * i], pk[0][23 + 8 * i]));
#pragma unroll
      for (int jn = 23; jn >= 0; jn--) {
        fold(0, jn, 0);
        if (jn < 8) fold(0, jn, 1);
      }
      if (t == 0) TS(113 + wg);
      nb_sync(kNbWg + wg, 128);
      uint32_t hal[2][16];
      auto load_halo = [&](int m) {
#pragma unroll
        for (int i = 0; i < 4; i++) {
          const uint4 v = lds128(stg + w * 2048 + m * 8192 + i * 512 + lane * 16);
          uint32_t* h = &hal[m][i * 4];
          h[0] = v.x; h[1] = v.y; h[2] = v.z; h[3] = v.w;
        }
      };
      load_halo(1);
      if (w == 0) {
        nb_sync(kNbHalo + 1, 64);
        release(31, lane < 4 * wg);
      }
      load_halo(0);
      __syncwarp();
      if (t == 0) TS(2 + wg * 20);
      {
        uint32_t all = lowmask;
#pragma unroll
        for (int i = 0; i < 32; i++) if (i < 16 || !(i & 1)) all &= pk[0][i];
#pragma unroll
        for (int i = 0; i < 8; i++) all &= __float_as_uint(rs[i >> 1][i & 1]);
        if (all == kPoison) sts32(sb + kZero + 8, 0);
      }
      nb_sync(kNbWin, 256);
      if (t == 0) TS(9 + wg * 20);
      const uint32_t zero = lds32(sb + kZero);
      float s0[4][4], s1[4][4], s2[4][4];
#pragma unroll
      for (int k = 0; k < 4; k++) {
        pk[k >> 1][8 * (k & 1)] |= zero;
#pragma unroll
        for (int e = 0; e < 4; e++) s0[k][e] = s1[k][e] = s2[k][e] = 0.f;
      }
#pragma unroll
      for (int ks = 0; ks < 2; ks++)
#pragma unroll
        for (int k = 0; k < 4; k++) {
          const uint32_t* qf = &pk[k >> 1][8 * (k & 1) + 4 * ks];
          const uint32_t* kf = &pk[k >> 1][16 + 8 * (k & 1) + 4 * ks];
          const uint32_t* hf = &hal[k >> 1][4 * (k & 1) + 2 * ks];
          mma16816(s0[k], qf[0], qf[1], qf[2], qf[3], hf[0], hf[1]);
          mma16816(s1[k], qf[0], qf[1], qf[2], qf[3], kf[0], kf[2]);
          mma16816(s2[k], qf[0], qf[1], qf[2], qf[3], kf[1], kf[3]);
        }
      float ea[4][2], eb[4][2], ma[4], mb[4];
#pragma unroll
      for (int k = 0; k < 4; k++) {
        const float *ra = rs[k & 2], *rb = rs[(k & 2) + 1];
        if (no_prev && k < 2) s0[k][0] = s0[k][1] = -INFINITY;
        ea[k][0] = (sel0 ? s0[k][0] : s1[k][0]) * ra[0]; ea[k][1] = (sel1 ? s0[k][1] : s1[k][1]) * ra[1];
        eb[k][0] = (sel0 ? s1[k][2] : s2[k][2]) * rb[0]; eb[k][1] = (sel1 ? s1[k][3] : s2[k][3]) * rb[1];
        ma[k] = fmaxf(ea[k][0], ea[k][1]); mb[k] = fmaxf(eb[k][0], eb[k][1]);
      }
#pragma unroll
      for (int o = 1; o < 4; o <<= 1)
#pragma unroll
        for (int k = 0; k < 4; k++) {
          ma[k] = fmaxf(ma[k], __shfl_xor_sync(~0u, ma[k], o));
          mb[k] = fmaxf(mb[k], __shfl_xor_sync(~0u, mb[k], o));
        }
      float ov[4][4][4], ls[4][4];
      uint32_t all = 0;
#pragma unroll
      for (int k = 0; k < 4; k++) {
        const float *ra = rk[k & 2], *rb = rk[(k & 2) + 1];
        ea[k][0] = ex2(ea[k][0] - ma[k]); ea[k][1] = ex2(ea[k][1] - ma[k]);
        eb[k][0] = ex2(eb[k][0] - mb[k]); eb[k][1] = ex2(eb[k][1] - mb[k]);
        const uint32_t pa = pack_bf16(ea[k][0] * ra[0], ea[k][1] * ra[1]), pb = pack_bf16(eb[k][0] * rb[0], eb[k][1] * rb[1]);
        const uint32_t* vf = &pk[k >> 1][32 + 8 * (k & 1)];
        const uint32_t* hf = &hal[k >> 1][8 + 4 * (k & 1)];
#pragma unroll
        for (int d2 = 0; d2 < 2; d2++) {
#pragma unroll
          for (int e = 0; e < 4; e++) ov[k][d2][e] = ov[k][2 + d2][e] = 0.f;
          mma1688(ov[k][d2], hf[2 * d2], hf[2 * d2 + 1], pa & lowmask);
          mma1688(ov[k][2 + d2], vf[4 * d2], vf[4 * d2 + 2], pb & lowmask);
        }
#pragma unroll
        for (int d2 = 0; d2 < 2; d2++) {
          mma1688(ov[k][d2], vf[4 * d2], vf[4 * d2 + 2], pa & ~lowmask);
          mma1688(ov[k][2 + d2], vf[4 * d2 + 1], vf[4 * d2 + 3], pb & ~lowmask);
        }
        ls[k][0] = ls[k][1] = ls[k][2] = ls[k][3] = 0.f;
        mma16816(ls[k], ones.x, ones.y, ones.z, ones.w, pack_bf16(ea[k][0], ea[k][1]), pack_bf16(eb[k][0], eb[k][1]));
        if (k >= kDone) all |= pa & pb;
      }
#pragma unroll
      for (int k = 0; k < 4; k++) {
        if (k == kDone) {
          if (all == 0xFFFFFFFFu) sts32(sb + kZero + 8, 0);
          nb_arrive(kNbWin + 1, 256);
          all = 0;
        }
        all |= (__float_as_uint(ov[k][0][0]) & __float_as_uint(ov[k][1][0]) & __float_as_uint(ov[k][2][0])) &
               (__float_as_uint(ov[k][3][0]) & __float_as_uint(ls[k][0]));
      }
      const uint32_t nil = lds32(sb + kZero);
      const uint32_t frag = stg + (w * 16 + (lane & 15)) * 128, frag_x = (lane >> 4) ^ (lane & 7);
      uint32_t after = all;
#pragma unroll
      for (int k = 0; k < 4; k++) {
        uint32_t h[2][4];
#pragma unroll
        for (int hf = 0; hf < 2; hf++) {
          const float i0 = rcp(__uint_as_float(__float_as_uint(ls[k][2 * hf]) | (after & nil)));
          const float i1 = rcp(__uint_as_float(__float_as_uint(ls[k][2 * hf + 1]) | (after & nil)));
#pragma unroll
          for (int e = 0; e < 4; e++) h[e >> 1][2 * (e & 1) + hf] = pack_bf16(ov[k][2 * hf + (e >> 1)][2 * (e & 1)] * i0, ov[k][2 * hf + (e >> 1)][2 * (e & 1) + 1] * i1);
          after = h[0][hf];
        }
#pragma unroll
        for (int d2 = 0; d2 < 2; d2++) stsm4_t(frag + (k >> 1) * 8192 + ((frag_x ^ ((k & 1) * 4 + d2 * 2)) << 4), h[d2][0], h[d2][1], h[d2][2], h[d2][3]);
      }
      fence_async_smem();
      if (wg) {
        __syncwarp();
        if (elect_one()) {
          tma_store2d(&p.o16, stg + w * 2048, (8 + c) * 64, r * 128 + w * 16);
          tma_store2d(&p.o16, stg + 8192 + w * 2048, (8 + c) * 64, r * 128 + 64 + w * 16);
          bulk_commit();
          bulk_wait_read();
          mbar_arrive(sb + kBars + 8 * kSentBar);
        }
        __syncwarp();
      } else {
        nb_arrive(kNbPub, 160);
      }
      if (t == 0) TS(3 + wg * 20);
      task = wg;
      sx = mx = bias = 0.f;
      continue;
      }

      {
#pragma unroll 1
        for (int part = task != 2; part < 2; part++) {
          if ((tid & 127) == 0) TS(6 + 2 * task + wg * 20);
          if (task + part == 5) {
            mainloop<128, 0>(sc, acc, sb, 3, 0, 16, -2, false, true, false, 1);
            continue;
          }
          const int j0 = task == 3 ? 48 - wg * 16 : part == 0 ? 2 - 2 * wg : 18 - 14 * wg;
          mainloop<192, 0>(sc, acc, sb, 2, j0, task != 2 ? 16 : part == 0 ? 2 : 14, -2, false, true, part == 0, wg);
          if (part == 0 && wg == 0) {
            const int t = fresh_tid() & 127;
            const uint32_t ep = lds32(sb + kEpoch);
            {
              float s = 0.f, ss = 0.f;
#pragma unroll 1
              for (int i = 0; i < 16; i++) {
                const uint4 v = lds128(sb + kStage + t * 128 + (i >> 3) * 16384 + (((i ^ t) & 7) << 4));
                const uint32_t u[4] = {v.x, v.y, v.z, v.w};
#pragma unroll
                for (int e = 0; e < 4; e++) {
                  const float d0 = bf_lo(u[e]), d1 = bf_hi(u[e]);
                  s = (s + d0) + d1;
                  ss = fmaf(d1, d1, fmaf(d0, d0, ss));
                }
              }
              st_b128(sc->stat2 + c * kS + r * 128 + t, __float_as_uint(s), __float_as_uint(ss), ep, ep);
            }
            __nanosleep(kStatNs);
            float2 sum = make_float2(0.f, 0.f);
#pragma unroll 1
            for (int i = 0; i < 2; i++) {
              uint3 a[4];
              load_tagged<4, true>(a, sc->stat2 + i * 4 * kS + r * 128 + t, kS, ep);
              sum.x += (__uint_as_float(a[0].x) + __uint_as_float(a[1].x)) + (__uint_as_float(a[2].x) + __uint_as_float(a[3].x));
              sum.y += (__uint_as_float(a[0].y) + __uint_as_float(a[1].y)) + (__uint_as_float(a[2].y) + __uint_as_float(a[3].y));
            }
            const float mean = sum.x * (1.f / kD);
            sts64f(sb + kStat + t * 8, make_float2(fmaxf(sum.y * (1.f / kD) - mean * mean, 0.f) + 1e-5f, -mean));
            __syncwarp();
            if (elect_one()) {
              bulk_commit();
              bulk_wait_read();
              mbar_arrive(sb + kBars + 8 * kStatBar);
            }
            __syncwarp();
            if (t == 0) TS(37);
          }
        }
      }
      const int t = fresh_tid() & 127, w = warp & 3, lane = t & 31, g = lane >> 2, q = lane & 3;
      const uint32_t stg = sb + kStage + wg * 32768;
      uint32_t csv = sb + kCs + wg * 768 + q * 8;
      uint32_t statv = sb + kStat + (w * 16 + g) * 8;
      const uint32_t frag = stg + (w * 16 + (lane & 15)) * 128;
      const uint32_t frag_x = (lane >> 4) ^ (lane & 7);
      const uint32_t priv = stg + w * 2048 + lane * 16;
      if (t == 0) TSK(7 + 2 * task + wg * 20);

      if (task == 4) {
        mbar_wait(sb + kBars + 8 * (kAuxBar + 1), 1);
        mbar_wait(sb + kBars + 8 * kResFreeBar, 1);
        mbar_wait(sb + kBars + 8 * (kStgBar + 1), 0);
      }
      asm volatile("" : "+r"(csv), "+r"(statv)::"memory");

      {
#pragma unroll
        for (int i = 0; i < 96; i++) asm volatile("sub.f32 %0, %0, %1;" : "+f"(acc[0][i]) : "f"(bias));
#define NEXT(i) asm volatile("sub.f32 %0, %1, %2;" : "=f"(acc[0][i]) : "f"(acc[1][i]), "f"(bias))
#pragma unroll 1
        for (int pp = 0; pp < 2; pp++) {
          TSG(pp);
          RowConst rc[2];
#pragma unroll
          for (int hf = 0; hf < 2; hf++) {
            const float2 st = lds64f_const(statv + pp * 512 + hf * 64);
            float rstd;
            asm("rsqrt.approx.ftz.f32 %0, %1;" : "=f"(rstd) : "f"(st.x));
            rc[hf] = {st.y, 0.7978845608f * rstd, 0.0356774081f * rstd * rstd * rstd, 0.5f * rstd * rstd};
          }
#pragma unroll
          for (int j2 = 0; j2 < 4; j2++) {
            uint32_t hv[4];
#pragma unroll
            for (int jj = 0; jj < 2; jj++) {
              const int jn = 2 * j2 + jj;
              const float2 cg = lds64f_const(csv + jn * 32), cu = lds64f_const(csv + 256 + jn * 32);
#pragma unroll
              for (int hf = 0; hf < 2; hf++) {
                const float nm = rc[hf].nmean;
                const float g0 = fmaf(nm, cg.x, acc[0][4 * jn + 2 * hf]), g1 = fmaf(nm, cg.y, acc[0][4 * jn + 2 * hf + 1]);
                const float u0 = fmaf(nm, cu.x, acc[0][32 + 4 * jn + 2 * hf]), u1 = fmaf(nm, cu.y, acc[0][33 + 4 * jn + 2 * hf]);
                hv[2 * jj + hf] = pack_bf16(g0 * u0 * gate_scale(g0, rc[hf]), g1 * u1 * gate_scale(g1, rc[hf]));
              }
            }
            stsm4(frag + 16384 + pp * 8192 + ((frag_x ^ (j2 * 2)) << 4), hv[0], hv[1], hv[2], hv[3]);
          }
          if (task < 4) {
            if (task == 2) {
#pragma unroll
              for (int j2 = 0; j2 < 4; j2++) {
                uint32_t hv[4];
#pragma unroll
                for (int jj = 0; jj < 2; jj++) {
                  const int jn = 16 + 2 * j2 + jj;
                  const float2 cs = lds64f_const(csv + jn * 32);
#pragma unroll
                  for (int hf = 0; hf < 2; hf++) {
                    const float nm = rc[hf].nmean;
                    const float t0 = fmaf(nm, cs.x, acc[0][4 * jn + 2 * hf]), t1 = fmaf(nm, cs.y, acc[0][4 * jn + 2 * hf + 1]);
                    hv[2 * jj + hf] = pack_bf16(t0 * gate_scale(t0, rc[hf]), t1 * gate_scale(t1, rc[hf]));
                  }
                }
                sts128(priv + pp * 8192 + j2 * 512, make_uint4(hv[0], hv[1], hv[2], hv[3]));
              }
            } else {
              uint4 park[4];
#pragma unroll
              for (int j2 = 0; j2 < 4; j2++) park[j2] = lds128(priv + pp * 8192 + j2 * 512);
              __syncwarp();
#pragma unroll
              for (int j2 = 0; j2 < 4; j2++) {
                const uint32_t pv[4] = {park[j2].x, park[j2].y, park[j2].z, park[j2].w};
                uint32_t hv[4];
#pragma unroll
                for (int jj = 0; jj < 2; jj++) {
                  const int jn = 16 + 2 * j2 + jj;
                  const float2 cs = lds64f_const(csv + jn * 32);
#pragma unroll
                  for (int hf = 0; hf < 2; hf++) {
                    const float nm = rc[hf].nmean;
                    const float t0 = fmaf(nm, cs.x, acc[0][4 * jn + 2 * hf]), t1 = fmaf(nm, cs.y, acc[0][4 * jn + 2 * hf + 1]);
                    asm("mul.rn.bf16x2 %0, %1, %2;" : "=r"(hv[2 * jj + hf]) : "r"(pack_bf16(t0, t1)), "r"(pv[2 * jj + hf]));
                  }
                }
                stsm4(frag + pp * 8192 + ((frag_x ^ (j2 * 2)) << 4), hv[0], hv[1], hv[2], hv[3]);
              }
            }
            if (pp == 1) break;
#pragma unroll
            for (int i = 64; i < 96; i++) NEXT(i);
          }
          if (pp == 1) break;
#pragma unroll
          for (int i = 0; i < 64; i++) NEXT(i);
        }
      }
      fence_async_smem();
      nb_arrive(kNbPub + wg, 160);
      if (t == 0) TS(task == 4 ? 57 : 56 + task + wg * 2);
      if (task == 4) {
        mbar_wait(sb + kBars + 8 * kPartBar, 0);
#pragma unroll 1
        for (int k = 0; k < 8; k++) {
          const uint32_t at = priv + w * 2048 + k * 512;
          uint4 v = lds128(at);
          uint32_t h[4];
          ldsm4(frag + 16384 + (k & 4) * 2048 + ((frag_x ^ (k * 2 & 6)) << 4), h);
          asm("add.rn.bf16x2 %0, %0, %1;" : "+r"(v.x) : "r"(h[0]));
          asm("add.rn.bf16x2 %0, %0, %1;" : "+r"(v.y) : "r"(h[1]));
          asm("add.rn.bf16x2 %0, %0, %1;" : "+r"(v.z) : "r"(h[2]));
          asm("add.rn.bf16x2 %0, %0, %1;" : "+r"(v.w) : "r"(h[3]));
          sts128(at, v);
        }
        nb_arrive(kNbPart, 256);
        break;
      }
      sx = mx = 0.f;
    }
  }
}

typedef CUresult (*EncodeTiledFn)(CUtensorMap*, CUtensorMapDataType, cuuint32_t, void*, const cuuint64_t*, const cuuint64_t*,
                                  const cuuint32_t*, const cuuint32_t*, CUtensorMapInterleave, CUtensorMapSwizzle,
                                  CUtensorMapL2promotion, CUtensorMapFloatOOBfill);

void encode(EncodeTiledFn fn, CUtensorMap* m, const void* base, int rank, cuuint64_t d0, cuuint64_t d1, cuuint64_t d2,
            cuuint64_t s1, cuuint64_t s2, cuuint32_t b2, cuuint32_t b1 = 64) {
  const cuuint64_t dims[3] = {d0, d1, d2}, strides[2] = {s1, s2};
  const cuuint32_t box[3] = {64, b1, b2}, es[3] = {1, 1, 1};
  fn(m, CU_TENSOR_MAP_DATA_TYPE_BFLOAT16, rank, const_cast<void*>(base), dims, strides, box, es, CU_TENSOR_MAP_INTERLEAVE_NONE,
     CU_TENSOR_MAP_SWIZZLE_128B, CU_TENSOR_MAP_L2_PROMOTION_L2_128B, CU_TENSOR_MAP_FLOAT_OOB_FILL_NONE);
}

}

extern "C" void kernel_launch(void* const* d_in, const int* in_sizes, int n_in, void* d_out, int out_size) {
  void* fnp = nullptr;
  cudaDriverEntryPointQueryResult qr;
  cudaGetDriverEntryPoint("cuTensorMapEncodeTiled", &fnp, cudaEnableDefault, &qr);
  EncodeTiledFn fn = (EncodeTiledFn)fnp;
  void *o, *h, *hh;
  cudaGetSymbolAddress(&o, g_o);
  cudaGetSymbolAddress(&h, g_h);
  cudaGetSymbolAddress(&hh, g_hh);

  Params p;
  Scratch* sc;
  cudaGetSymbolAddress((void**)&sc, g_scratch);
  encode(fn, &p.x, d_in[0], 3, kD, kS / 2, 2, 4 * kD, 2 * kD, 1, 128);
  encode(fn, &p.out, d_out, 3, kD, kS / 2, 2, 4 * kD, 2 * kD, 1, 16);
  encode(fn, &p.wqkv, d_in[1], 2, 3 * kD, kD, 1, 6 * kD, 0, 1);
  encode(fn, &p.wo, d_in[2], 2, kD, kD, 1, 2 * kD, 0, 1);
  encode(fn, &p.wd, d_in[6], 2, kD, kF, 1, 2 * kD, 0, 1);
  encode(fn, &p.wg, d_in[4], 2, kF, kD, 1, 2 * kF, 0, 1);
  encode(fn, &p.wu, d_in[5], 2, kF, kD, 1, 2 * kF, 0, 1);
  encode(fn, &p.o, o, 2, kD, kS, 1, 2 * kD, 0, 1, 128);
  encode(fn, &p.h, h, 2, kD, kS, 1, 2 * kD, 0, 1, 128);
  encode(fn, &p.hh, hh, 2, kF, kS, 1, 2 * kF, 0, 1, 128);
  encode(fn, &p.ost, o, 2, kD, kS, 1, 2 * kD, 0, 1);
  encode(fn, &p.o16, o, 2, kD, kS, 1, 2 * kD, 0, 1, 16);
  encode(fn, &p.h16, h, 2, kD, kS, 1, 2 * kD, 0, 1, 16);
  encode(fn, &p.hst, h, 2, kD, kS, 1, 2 * kD, 0, 1);
  encode(fn, &p.hhst, hh, 2, kF, kS, 1, 2 * kF, 0, 1);
  p.wop = (const uint4*)d_in[2];
  p.wgp = (const uint4*)d_in[4];
  p.wup = (const uint4*)d_in[5];

  int dev = 0, sms = 0;
  cudaGetDevice(&dev);
  cudaDeviceGetAttribute(&sms, cudaDevAttrMultiProcessorCount, dev);
  auto* kernel = sms == 132 ? fused_block_kernel<true> : fused_block_kernel<false>;
  cudaFuncSetAttribute(kernel, cudaFuncAttributeMaxDynamicSharedMemorySize, kSmemBytes);
  kernel<<<132, kThreads, kSmemBytes, cudaStreamPerThread>>>(sc, (const __nv_bfloat16*)d_in[0], (const __nv_bfloat16*)d_in[1],
                                                                  (__nv_bfloat16*)d_out, p);
}
```

```cpp
#include <cuda_runtime.h>
#include <cuda_bf16.h>
#include <cuda.h>
#include <stddef.h>
#include <stdint.h>

namespace {

constexpr int kS = 2048, kD = 1024, kF = 3584;
constexpr int kThreads = 384;

constexpr int kRing = 0;
constexpr int kStage = 163840;
constexpr int kAug = kStage + 16384;
constexpr int kOwn = kStage + 32768;
constexpr int kFill = kStage + 24576;
constexpr int kCs = kStage + 65536;
constexpr int kStat = kCs + 1536;
constexpr int kBars = kStat + 1024;
constexpr int kSmemBytes = kBars + 512;
constexpr int kResBar = 38;
constexpr int kAuxBar = 39;
constexpr int kStgBar = 41;
constexpr int kResFreeBar = 43;
constexpr int kStatBar = 44;
constexpr int kPartBar = 45;
constexpr int kWaveBar = 46;
constexpr int kHalfBar = 49;
constexpr int kSentBar = 51;
constexpr int kLandBar = 52;
constexpr int kNumBars = 58;
static_assert(kNumBars == 4 + 3 * 18, "barrier initialisation is split 4 + 3 x 18");
__host__ __device__ constexpr int bar_count(int i) {
  const int ph = i < 8 ? 0 : i < 18 ? 1 : i < 26 ? 2 : 3, base = ph * 9 - (ph & 1);
  return i < 38 ? (i - base < 4 + (ph & 1) + (ph == 3) ? 2 : ph == 0 ? 16 : 8) : i == kResFreeBar || i == kStatBar || (i >= kHalfBar && i < kLandBar) ? 4 : 1;
}
__host__ __device__ constexpr uint64_t bar_shifts(int first) {
  uint64_t m = 0;
  for (int i = 17; i >= 0; i--) {
    const int n = bar_count(first + i);
    m = m << 3 | (n == 16 ? 4 : n == 8 ? 3 : n >> 1);
  }
  return m;
}
constexpr int kScale = kBars + 464;
constexpr int kPlan = kBars + 472;
constexpr int kOnes = kBars + 480;
constexpr int kZero = kBars + 496;
constexpr int kRole = kBars + 508;
constexpr int kEpoch = kBars + 500;
__device__ __forceinline__ int ring_base(int ph) { return ph * 9 - (ph & 1); }
constexpr int kWide = 25;
constexpr int kFirstShared = 15;
constexpr int kNbOrder = 1;
constexpr int kNbWg = 3;
constexpr int kNbPub = 5;
constexpr int kNbWin = 7;
constexpr int kNbSelf = 13;
constexpr int kNbPart = 11;
constexpr int kNbHalo = 9;

constexpr int kFlO = 0;
constexpr int kFlPace = 1;
constexpr int kFlHH = 3;
constexpr int kFlRow = 32;
constexpr int kNumFlags = 16 * kFlRow;

constexpr int kPauseG1 = 7;
constexpr int kPauseG2 = 1;
constexpr int kAhead = 2;
constexpr int kTail = 4;
constexpr int kShare = 5;
constexpr int kMost = 8;
constexpr int kBudget = 328;
constexpr int kRemain = 65500;
constexpr int kStepNs = 167;
constexpr int kDone = 3;
constexpr int kQuietAt = 48;
constexpr int kPfStep = 8;
constexpr int kBackoffNs = 200;
constexpr int kPaceNs = 300;
constexpr int kPartNs = 500;
constexpr int kFillNs = 500;
constexpr int kHaloNs = 150;
constexpr int kGateONs = 150;
constexpr int kGateHNs = 150;
constexpr int kHoldNs = 1200;
constexpr float kBias1 = 512.f, kBias3 = 32768.f;
constexpr int kInitMix = 1000;
constexpr int kSplit = 13;
constexpr int kSampleNs = 1000;
constexpr int kStatNs = 1500;

struct Scratch {
  uint32_t flags[kNumFlags];
  uint32_t epoch[32];
  uint4 stat1[kS];
  uint4 stat2[8 * kS];
  uint4 cs[7 * 8 * 96];
  uint2 finish[128];
  uint2 plan[16];
  uint4 halo[2 * 16 * 8 * 6 * 32];
  uint4 part[128 * 8 * 128];
};
struct Params {
  CUtensorMap x, wqkv, o, wo, h, wg, wu, hh, wd, out;
  CUtensorMap ost, hst, hhst;
  CUtensorMap o16, h16;
  const uint4 *wop, *wgp, *wup;
  uint8_t g1[8][32], g2[8][16], g3[8][64], g4[56];
};

__device__ __align__(256) __nv_bfloat16 g_o[kS * kD];
__device__ __align__(256) __nv_bfloat16 g_h[kS * kD];
__device__ __align__(256) __nv_bfloat16 g_hh[kS * kF];
__device__ __align__(256) Scratch g_scratch;

template <bool BY_SM>
__device__ __forceinline__ int role_id() {
  uint32_t sm;
  asm("mov.u32 %0, %%smid;" : "=r"(sm));
  const int tpc = (BY_SM ? sm : blockIdx.x) >> 1, rank = blockIdx.x & 1;
  if ((tpc | 1) == 61) return 8 + 2 * tpc + rank;
  const int u = tpc - 32, s7 = (u * 37) >> 8;
  const int g = tpc < 32 ? tpc & 7 : tpc < 60 ? 1 + u - 7 * s7 : 0, s = tpc < 32 ? tpc >> 3 : tpc < 60 ? 4 + s7 : tpc - 58;
  return (g * 2 + rank) * 8 + s;
}
#define TS(i) do { } while (0)
#define TSK(i) do { } while (0)
#define TSS(i) do { } while (0)
#define TST(i)
#define TSG(i)

__device__ __forceinline__ uint32_t smem_u32(const void* p) { return (uint32_t)__cvta_generic_to_shared(p); }
template <class T>
__device__ __forceinline__ T* plus(T* p, uint32_t n) {
  uint64_t r;
  asm("{\n.reg .b32 lo, hi;\nmov.b64 {lo, hi}, %1;\nadd.cc.u32 lo, lo, %2;\naddc.u32 hi, hi, 0;\nmov.b64 %0, {lo, hi};\n}\n"
      : "=l"(r) : "l"(p), "r"(n * (uint32_t)sizeof(T)));
  return (T*)r;
}
#define SC_AT(member, n) ((decltype(+sc->member))((char*)plus((decltype(+sc->member))sc, n) + offsetof(Scratch, member)))
__device__ __forceinline__ void mbar_init(uint32_t bar, uint32_t cnt) {
  asm volatile("mbarrier.init.shared::cta.b64 [%0], %1;" ::"r"(bar), "r"(cnt));
}
__device__ __forceinline__ void mbar_expect_tx(uint32_t bar, uint32_t bytes) {
  asm volatile("mbarrier.arrive.expect_tx.shared::cta.b64 _, [%0], %1;" ::"r"(bar), "r"(bytes) : "memory");
}
__device__ __forceinline__ uint32_t map_cta(uint32_t addr, uint32_t cta) {
  uint32_t r;
  asm("mapa.shared::cluster.u32 %0, %1, %2;" : "=r"(r) : "r"(addr), "r"(cta));
  return r;
}
__device__ __forceinline__ void mbar_arrive_cluster_if(uint32_t bar, bool cond) {
  asm volatile("{\n.reg .pred p;\nsetp.ne.u32 p, %1, 0;\n@p mbarrier.arrive.shared::cluster.b64 _, [%0];\n}\n"
               ::"r"(bar), "r"((uint32_t)cond) : "memory");
}
__device__ __forceinline__ void mbar_wait(uint32_t bar, uint32_t parity) {
  asm volatile("{\n.reg .pred p;\nLAB_WAIT:\nmbarrier.try_wait.parity.shared::cta.b64 p, [%0], %1;\n@!p bra LAB_WAIT;\n}\n"
               ::"r"(bar), "r"(parity) : "memory");
  return;
  asm volatile("{\n.reg .pred p;\n.reg .u32 c;\nmov.u32 c, 0;\n"
               "LAB_WAIT:\nmbarrier.try_wait.parity.shared::cta.b64 p, [%0], %1;\n@p bra LAB_DONE;\n"
               "add.u32 c, c, 1;\nsetp.lt.u32 p, c, 2000000;\n@p bra LAB_WAIT;\ntrap;\nLAB_DONE:\n}\n"
               ::"r"(bar), "r"(parity) : "memory");
}
__device__ __forceinline__ void mbar_arrive(uint32_t bar) {
  asm volatile("mbarrier.arrive.shared::cta.b64 _, [%0];" ::"r"(bar) : "memory");
}
__device__ __forceinline__ void flag_signal(uint32_t* flag) {
  asm volatile("red.release.gpu.global.add.u32 [%0], 1;" ::"l"(flag) : "memory");
}
__device__ __forceinline__ void st_b128(uint4* p, uint32_t a, uint32_t b, uint32_t c, uint32_t d) {
  asm volatile("{\n.reg .b128 t;\n.reg .b64 lo, hi;\nmov.b64 lo, {%1,%2};\nmov.b64 hi, {%3,%4};\nmov.b128 t, {lo, hi};\n"
               "st.relaxed.gpu.global.b128 [%0], t;\n}\n" ::"l"(p), "r"(a), "r"(b), "r"(c), "r"(d) : "memory");
}
__device__ __forceinline__ uint4 ld_b128(const uint4* p) {
  uint4 v;
  asm volatile("{\n.reg .b128 t;\n.reg .b64 lo, hi;\nld.relaxed.gpu.global.b128 t, [%4];\nmov.b128 {lo, hi}, t;\n"
               "mov.b64 {%0,%1}, lo;\nmov.b64 {%2,%3}, hi;\n}\n" : "=r"(v.x), "=r"(v.y), "=r"(v.z), "=r"(v.w) : "l"(p) : "memory");
  return v;
}
__device__ __forceinline__ uint32_t ld_epoch(Scratch* sc) {
  uint32_t v;
  asm volatile("ld.relaxed.gpu.global.u32 %0, [%1];" : "=r"(v) : "l"(sc->epoch) : "memory");
  return v + 1;
}
__device__ __forceinline__ void flag_wait(uint32_t* flag, uint32_t target) {
  asm volatile("{\n.reg .pred p;\n.reg .u32 c, v;\nmov.u32 c, 0;\n"
               "LAB_WAIT:\nld.relaxed.gpu.global.u32 v, [%0];\nsub.u32 v, v, %1;\nsetp.ge.s32 p, v, 0;\n@p bra LAB_DONE;\n"
               "add.u32 c, c, 1;\nsetp.lt.u32 p, c, 4000000;\n@p bra LAB_WAIT;\ntrap;\nLAB_DONE:\n}\n"
               ::"l"(flag), "r"(target) : "memory");
}
__device__ __forceinline__ void send_word(uint2* p, uint32_t v, uint32_t tag) {
  asm volatile("{\n.reg .b64 t;\nmov.b64 t, {%1, %2};\nst.relaxed.gpu.global.b64 [%0], t;\n}\n" ::"l"(p), "r"(v), "r"(tag) : "memory");
}
__device__ __forceinline__ uint32_t await_word(const uint2* p, uint32_t tag) {
  uint32_t v;
  asm volatile("{\n.reg .pred p;\n.reg .u32 c, g;\n.reg .b64 t;\nmov.u32 c, 0;\n"
               "LAB_WAIT:\nld.relaxed.gpu.global.b64 t, [%1];\nmov.b64 {%0, g}, t;\nsetp.eq.u32 p, g, %2;\n@p bra LAB_DONE;\n"
               "add.u32 c, c, 1;\nsetp.lt.u32 p, c, 4000000;\n@p bra LAB_WAIT;\ntrap;\nLAB_DONE:\n}\n"
               : "=r"(v) : "l"(p), "r"(tag) : "memory");
  return v;
}
__device__ __forceinline__ uint32_t global_ns() {
  uint32_t v;
  asm volatile("mov.u32 %0, %%globaltimer_lo;" : "=r"(v));
  return v;
}
__device__ __forceinline__ int fresh_tid() {
  int v;
  asm volatile("mov.u32 %0, %%tid.x;" : "=r"(v));
  return v;
}
constexpr uint32_t kPoison = 0xFFFFFFFFu;
__device__ __forceinline__ bool elect_one() {
  uint32_t p;
  asm volatile("{\n.reg .pred P;\nelect.sync _|P, 0xffffffff;\nselp.u32 %0, 1, 0, P;\n}\n" : "=r"(p));
  return p != 0;
}
__device__ __forceinline__ void fence_async() { asm volatile("fence.acquire.gpu;\nfence.proxy.async.global;" ::: "memory"); }
__device__ __forceinline__ void fence_async_smem() { asm volatile("fence.proxy.async.shared::cta;" ::: "memory"); }
__device__ __forceinline__ void nb_sync(int id, int n) { asm volatile("bar.sync %0, %1;" ::"r"(id), "r"(n) : "memory"); }
__device__ __forceinline__ void nb_arrive(int id, int n) { asm volatile("bar.arrive %0, %1;" ::"r"(id), "r"(n) : "memory"); }

__device__ __forceinline__ void tma2d(uint32_t dst, const CUtensorMap* m, int c0, int c1, uint32_t bar) {
  asm volatile("cp.async.bulk.tensor.2d.shared::cluster.global.mbarrier::complete_tx::bytes [%0], [%1, {%3, %4}], [%2];"
               ::"r"(dst), "l"(m), "r"(bar), "r"(c0), "r"(c1) : "memory");
}
__device__ __forceinline__ void tma2d_mc(uint32_t dst, const CUtensorMap* m, int c0, int c1, uint32_t bar) {
  asm volatile("cp.async.bulk.tensor.2d.shared::cluster.global.mbarrier::complete_tx::bytes.multicast::cluster"
               " [%0], [%1, {%3, %4}], [%2], %5;"
               ::"r"(dst), "l"(m), "r"(bar), "r"(c0), "r"(c1), "h"((uint16_t)3) : "memory");
}
__device__ __forceinline__ void tma3d(uint32_t dst, const CUtensorMap* m, int c0, int c1, int c2, uint32_t bar) {
  asm volatile("cp.async.bulk.tensor.3d.shared::cluster.global.mbarrier::complete_tx::bytes [%0], [%1, {%3, %4, %5}], [%2];"
               ::"r"(dst), "l"(m), "r"(bar), "r"(c0), "r"(c1), "r"(c2) : "memory");
}
__device__ __forceinline__ void tma_store2d(const CUtensorMap* m, uint32_t src, int c0, int c1) {
  asm volatile("cp.async.bulk.tensor.2d.global.shared::cta.bulk_group [%0, {%2, %3}], [%1];"
               ::"l"(m), "r"(src), "r"(c0), "r"(c1) : "memory");
}
__device__ __forceinline__ void tma_store3d(const CUtensorMap* m, uint32_t src, int c0, int c1, int c2) {
  asm volatile("cp.async.bulk.tensor.3d.global.shared::cta.bulk_group [%0, {%2, %3, %4}], [%1];"
               ::"l"(m), "r"(src), "r"(c0), "r"(c1), "r"(c2) : "memory");
}
__device__ __forceinline__ void tma_prefetch2d(const CUtensorMap* m, int c0, int c1) {
  asm volatile("cp.async.bulk.prefetch.tensor.2d.L2.global [%0, {%1, %2}];" ::"l"(m), "r"(c0), "r"(c1) : "memory");
}
__device__ __forceinline__ void prefetch_map(const CUtensorMap* m) { asm volatile("prefetch.tensormap [%0];" ::"l"(m) : "memory"); }
__device__ __forceinline__ void bulk_commit() { asm volatile("cp.async.bulk.commit_group;" ::: "memory"); }
__device__ __forceinline__ void bulk_wait_all() { asm volatile("cp.async.bulk.wait_group 0;" ::: "memory"); }
__device__ __forceinline__ void bulk_wait_read() { asm volatile("cp.async.bulk.wait_group.read 0;" ::: "memory"); }
__device__ __forceinline__ void prefetch_l2(const void* p) { asm volatile("prefetch.global.L2 [%0];" ::"l"(p)); }
__device__ __forceinline__ void cluster_arrive() { asm volatile("barrier.cluster.arrive.relaxed.aligned;" ::: "memory"); }
__device__ __forceinline__ void cluster_wait() { asm volatile("barrier.cluster.wait.aligned;" ::: "memory"); }

__device__ __forceinline__ void wg_fence() { asm volatile("wgmma.fence.sync.aligned;" ::: "memory"); }
__device__ __forceinline__ void wg_commit() { asm volatile("wgmma.commit_group.sync.aligned;" ::: "memory"); }
template <int N> __device__ __forceinline__ void wg_wait() { asm volatile("wgmma.wait_group.sync.aligned %0;" ::"n"(N) : "memory"); }
__device__ __forceinline__ uint32_t desc_lo(uint32_t addr, uint32_t lbo) { return ((addr & 0x3FFFF) >> 4) | ((lbo >> 4) << 16); }
__device__ __forceinline__ uint64_t desc(uint32_t lo) { return (uint64_t)lo | (0x40000040ull << 32); }
__device__ __forceinline__ uint64_t desc_kept(uint32_t lo, uint32_t sb) { return (uint64_t)lo | (uint64_t)(0x40000040u | sb >> 31) << 32; }
constexpr int kToB = (16384 >> 4) + ((8192 - 16) >> 4 << 16);

__device__ __forceinline__ void wgmma_n128(float (&d)[96], uint64_t da, uint64_t db, int add = 1) {
  asm volatile(
      "{\n.reg .pred p;\nsetp.ne.b32 p, %66, 0;\n"
      "wgmma.mma_async.sync.aligned.m64n128k16.f32.bf16.bf16 {"
      "%0, %1, %2, %3, %4, %5, %6, %7, %8, %9, %10, %11, %12, %13, %14, %15, "
      "%16, %17, %18, %19, %20, %21, %22, %23, %24, %25, %26, %27, %28, %29, %30, %31, "
      "%32, %33, %34, %35, %36, %37, %38, %39, %40, %41, %42, %43, %44, %45, %46, %47, "
      "%48, %49, %50, %51, %52, %53, %54, %55, %56, %57, %58, %59, %60, %61, %62, %63}, "
      "%64, %65, p, 1, 1, 0, 1;\n}\n"
      :
        "+f"(d[0]), "+f"(d[1]), "+f"(d[2]), "+f"(d[3]), "+f"(d[4]), "+f"(d[5]), "+f"(d[6]), "+f"(d[7]),
        "+f"(d[8]), "+f"(d[9]), "+f"(d[10]), "+f"(d[11]), "+f"(d[12]), "+f"(d[13]), "+f"(d[14]), "+f"(d[15]),
        "+f"(d[16]), "+f"(d[17]), "+f"(d[18]), "+f"(d[19]), "+f"(d[20]), "+f"(d[21]), "+f"(d[22]), "+f"(d[23]),
        "+f"(d[24]), "+f"(d[25]), "+f"(d[26]), "+f"(d[27]), "+f"(d[28]), "+f"(d[29]), "+f"(d[30]), "+f"(d[31]),
        "+f"(d[32]), "+f"(d[33]), "+f"(d[34]), "+f"(d[35]), "+f"(d[36]), "+f"(d[37]), "+f"(d[38]), "+f"(d[39]),
        "+f"(d[40]), "+f"(d[41]), "+f"(d[42]), "+f"(d[43]), "+f"(d[44]), "+f"(d[45]), "+f"(d[46]), "+f"(d[47]),
        "+f"(d[48]), "+f"(d[49]), "+f"(d[50]), "+f"(d[51]), "+f"(d[52]), "+f"(d[53]), "+f"(d[54]), "+f"(d[55]),
        "+f"(d[56]), "+f"(d[57]), "+f"(d[58]), "+f"(d[59]), "+f"(d[60]), "+f"(d[61]), "+f"(d[62]), "+f"(d[63])
      : "l"(da), "l"(db), "r"(add));
}

__device__ __forceinline__ void wgmma_n192(float (&d)[96], uint64_t da, uint64_t db, int add = 1) {
  asm volatile(
      "{\n.reg .pred p;\nsetp.ne.b32 p, %98, 0;\n"
      "wgmma.mma_async.sync.aligned.m64n192k16.f32.bf16.bf16 {"
      "%0, %1, %2, %3, %4, %5, %6, %7, %8, %9, %10, %11, %12, %13, %14, %15, "
      "%16, %17, %18, %19, %20, %21, %22, %23, %24, %25, %26, %27, %28, %29, %30, %31, "
      "%32, %33, %34, %35, %36, %37, %38, %39, %40, %41, %42, %43, %44, %45, %46, %47, "
      "%48, %49, %50, %51, %52, %53, %54, %55, %56, %57, %58, %59, %60, %61, %62, %63, "
      "%64, %65, %66, %67, %68, %69, %70, %71, %72, %73, %74, %75, %76, %77, %78, %79, "
      "%80, %81, %82, %83, %84, %85, %86, %87, %88, %89, %90, %91, %92, %93, %94, %95}, "
      "%96, %97, p, 1, 1, 0, 1;\n}\n"
      :
        "+f"(d[0]), "+f"(d[1]), "+f"(d[2]), "+f"(d[3]), "+f"(d[4]), "+f"(d[5]), "+f"(d[6]), "+f"(d[7]),
        "+f"(d[8]), "+f"(d[9]), "+f"(d[10]), "+f"(d[11]), "+f"(d[12]), "+f"(d[13]), "+f"(d[14]), "+f"(d[15]),
        "+f"(d[16]), "+f"(d[17]), "+f"(d[18]), "+f"(d[19]), "+f"(d[20]), "+f"(d[21]), "+f"(d[22]), "+f"(d[23]),
        "+f"(d[24]), "+f"(d[25]), "+f"(d[26]), "+f"(d[27]), "+f"(d[28]), "+f"(d[29]), "+f"(d[30]), "+f"(d[31]),
        "+f"(d[32]), "+f"(d[33]), "+f"(d[34]), "+f"(d[35]), "+f"(d[36]), "+f"(d[37]), "+f"(d[38]), "+f"(d[39]),
        "+f"(d[40]), "+f"(d[41]), "+f"(d[42]), "+f"(d[43]), "+f"(d[44]), "+f"(d[45]), "+f"(d[46]), "+f"(d[47]),
        "+f"(d[48]), "+f"(d[49]), "+f"(d[50]), "+f"(d[51]), "+f"(d[52]), "+f"(d[53]), "+f"(d[54]), "+f"(d[55]),
        "+f"(d[56]), "+f"(d[57]), "+f"(d[58]), "+f"(d[59]), "+f"(d[60]), "+f"(d[61]), "+f"(d[62]), "+f"(d[63]),
        "+f"(d[64]), "+f"(d[65]), "+f"(d[66]), "+f"(d[67]), "+f"(d[68]), "+f"(d[69]), "+f"(d[70]), "+f"(d[71]),
        "+f"(d[72]), "+f"(d[73]), "+f"(d[74]), "+f"(d[75]), "+f"(d[76]), "+f"(d[77]), "+f"(d[78]), "+f"(d[79]),
        "+f"(d[80]), "+f"(d[81]), "+f"(d[82]), "+f"(d[83]), "+f"(d[84]), "+f"(d[85]), "+f"(d[86]), "+f"(d[87]),
        "+f"(d[88]), "+f"(d[89]), "+f"(d[90]), "+f"(d[91]), "+f"(d[92]), "+f"(d[93]), "+f"(d[94]), "+f"(d[95])
      : "l"(da), "l"(db), "r"(add));
}

__device__ __forceinline__ void wgmma_n192_any(float (&d)[96], uint64_t da, uint64_t db) {
  asm volatile(
      "wgmma.mma_async.sync.aligned.m64n192k16.f32.bf16.bf16 {"
      "%0, %1, %2, %3, %4, %5, %6, %7, %8, %9, %10, %11, %12, %13, %14, %15, "
      "%16, %17, %18, %19, %20, %21, %22, %23, %24, %25, %26, %27, %28, %29, %30, %31, "
      "%32, %33, %34, %35, %36, %37, %38, %39, %40, %41, %42, %43, %44, %45, %46, %47, "
      "%48, %49, %50, %51, %52, %53, %54, %55, %56, %57, %58, %59, %60, %61, %62, %63, "
      "%64, %65, %66, %67, %68, %69, %70, %71, %72, %73, %74, %75, %76, %77, %78, %79, "
      "%80, %81, %82, %83, %84, %85, %86, %87, %88, %89, %90, %91, %92, %93, %94, %95}, "
      "%96, %97, 0, 1, 1, 0, 1;\n"
      :
        "=f"(d[0]), "=f"(d[1]), "=f"(d[2]), "=f"(d[3]), "=f"(d[4]), "=f"(d[5]), "=f"(d[6]), "=f"(d[7]),
        "=f"(d[8]), "=f"(d[9]), "=f"(d[10]), "=f"(d[11]), "=f"(d[12]), "=f"(d[13]), "=f"(d[14]), "=f"(d[15]),
        "=f"(d[16]), "=f"(d[17]), "=f"(d[18]), "=f"(d[19]), "=f"(d[20]), "=f"(d[21]), "=f"(d[22]), "=f"(d[23]),
        "=f"(d[24]), "=f"(d[25]), "=f"(d[26]), "=f"(d[27]), "=f"(d[28]), "=f"(d[29]), "=f"(d[30]), "=f"(d[31]),
        "=f"(d[32]), "=f"(d[33]), "=f"(d[34]), "=f"(d[35]), "=f"(d[36]), "=f"(d[37]), "=f"(d[38]), "=f"(d[39]),
        "=f"(d[40]), "=f"(d[41]), "=f"(d[42]), "=f"(d[43]), "=f"(d[44]), "=f"(d[45]), "=f"(d[46]), "=f"(d[47]),
        "=f"(d[48]), "=f"(d[49]), "=f"(d[50]), "=f"(d[51]), "=f"(d[52]), "=f"(d[53]), "=f"(d[54]), "=f"(d[55]),
        "=f"(d[56]), "=f"(d[57]), "=f"(d[58]), "=f"(d[59]), "=f"(d[60]), "=f"(d[61]), "=f"(d[62]), "=f"(d[63]),
        "=f"(d[64]), "=f"(d[65]), "=f"(d[66]), "=f"(d[67]), "=f"(d[68]), "=f"(d[69]), "=f"(d[70]), "=f"(d[71]),
        "=f"(d[72]), "=f"(d[73]), "=f"(d[74]), "=f"(d[75]), "=f"(d[76]), "=f"(d[77]), "=f"(d[78]), "=f"(d[79]),
        "=f"(d[80]), "=f"(d[81]), "=f"(d[82]), "=f"(d[83]), "=f"(d[84]), "=f"(d[85]), "=f"(d[86]), "=f"(d[87]),
        "=f"(d[88]), "=f"(d[89]), "=f"(d[90]), "=f"(d[91]), "=f"(d[92]), "=f"(d[93]), "=f"(d[94]), "=f"(d[95])
      : "l"(da), "l"(db));
}

__device__ __forceinline__ void wgmma_n192_rs(float (&d)[96], uint32_t a0, uint32_t a1, uint32_t a23, uint64_t db) {
  asm volatile(
      "wgmma.mma_async.sync.aligned.m64n192k16.f32.bf16.bf16 {"
      "%0, %1, %2, %3, %4, %5, %6, %7, %8, %9, %10, %11, %12, %13, %14, %15, "
      "%16, %17, %18, %19, %20, %21, %22, %23, %24, %25, %26, %27, %28, %29, %30, %31, "
      "%32, %33, %34, %35, %36, %37, %38, %39, %40, %41, %42, %43, %44, %45, %46, %47, "
      "%48, %49, %50, %51, %52, %53, %54, %55, %56, %57, %58, %59, %60, %61, %62, %63, "
      "%64, %65, %66, %67, %68, %69, %70, %71, %72, %73, %74, %75, %76, %77, %78, %79, "
      "%80, %81, %82, %83, %84, %85, %86, %87, %88, %89, %90, %91, %92, %93, %94, %95}, "
      "{%96, %97, %98, %98}, %99, 1, 1, 1, 1;\n"
      :
        "+f"(d[0]), "+f"(d[1]), "+f"(d[2]), "+f"(d[3]), "+f"(d[4]), "+f"(d[5]), "+f"(d[6]), "+f"(d[7]),
        "+f"(d[8]), "+f"(d[9]), "+f"(d[10]), "+f"(d[11]), "+f"(d[12]), "+f"(d[13]), "+f"(d[14]), "+f"(d[15]),
        "+f"(d[16]), "+f"(d[17]), "+f"(d[18]), "+f"(d[19]), "+f"(d[20]), "+f"(d[21]), "+f"(d[22]), "+f"(d[23]),
        "+f"(d[24]), "+f"(d[25]), "+f"(d[26]), "+f"(d[27]), "+f"(d[28]), "+f"(d[29]), "+f"(d[30]), "+f"(d[31]),
        "+f"(d[32]), "+f"(d[33]), "+f"(d[34]), "+f"(d[35]), "+f"(d[36]), "+f"(d[37]), "+f"(d[38]), "+f"(d[39]),
        "+f"(d[40]), "+f"(d[41]), "+f"(d[42]), "+f"(d[43]), "+f"(d[44]), "+f"(d[45]), "+f"(d[46]), "+f"(d[47]),
        "+f"(d[48]), "+f"(d[49]), "+f"(d[50]), "+f"(d[51]), "+f"(d[52]), "+f"(d[53]), "+f"(d[54]), "+f"(d[55]),
        "+f"(d[56]), "+f"(d[57]), "+f"(d[58]), "+f"(d[59]), "+f"(d[60]), "+f"(d[61]), "+f"(d[62]), "+f"(d[63]),
        "+f"(d[64]), "+f"(d[65]), "+f"(d[66]), "+f"(d[67]), "+f"(d[68]), "+f"(d[69]), "+f"(d[70]), "+f"(d[71]),
        "+f"(d[72]), "+f"(d[73]), "+f"(d[74]), "+f"(d[75]), "+f"(d[76]), "+f"(d[77]), "+f"(d[78]), "+f"(d[79]),
        "+f"(d[80]), "+f"(d[81]), "+f"(d[82]), "+f"(d[83]), "+f"(d[84]), "+f"(d[85]), "+f"(d[86]), "+f"(d[87]),
        "+f"(d[88]), "+f"(d[89]), "+f"(d[90]), "+f"(d[91]), "+f"(d[92]), "+f"(d[93]), "+f"(d[94]), "+f"(d[95])
      : "r"(a0), "r"(a1), "r"(a23), "l"(db));
}

__device__ __forceinline__ uint32_t pack_bf16(float lo, float hi) {
  uint32_t r;
  asm("cvt.rn.bf16x2.f32 %0, %1, %2;" : "=r"(r) : "f"(hi), "f"(lo));
  return r;
}
__device__ __forceinline__ float bf_lo(uint32_t v) { return __uint_as_float(v << 16); }
__device__ __forceinline__ float bf_hi(uint32_t v) { return __uint_as_float(v & 0xFFFF0000u); }
__device__ __forceinline__ float ex2(float x) { float r; asm("ex2.approx.ftz.f32 %0, %1;" : "=f"(r) : "f"(x)); return r; }
__device__ __forceinline__ float rcp(float x) { float r; asm("rcp.approx.ftz.f32 %0, %1;" : "=f"(r) : "f"(x)); return r; }
__device__ __forceinline__ uint32_t movm(uint32_t a) {
  uint32_t d;
  asm volatile("movmatrix.sync.aligned.m8n8.trans.b16 %0, %1;" : "=r"(d) : "r"(a));
  return d;
}
__device__ __forceinline__ void mma16816(float (&c)[4], uint32_t a0, uint32_t a1, uint32_t a2, uint32_t a3, uint32_t b0, uint32_t b1) {
  asm volatile("mma.sync.aligned.m16n8k16.row.col.f32.bf16.bf16.f32 {%0,%1,%2,%3}, {%4,%5,%6,%7}, {%8,%9}, {%0,%1,%2,%3};"
               : "+f"(c[0]), "+f"(c[1]), "+f"(c[2]), "+f"(c[3]) : "r"(a0), "r"(a1), "r"(a2), "r"(a3), "r"(b0), "r"(b1));
}
__device__ __forceinline__ void mma1688(float (&c)[4], uint32_t a0, uint32_t a1, uint32_t b0) {
  asm volatile("mma.sync.aligned.m16n8k8.row.col.f32.bf16.bf16.f32 {%0,%1,%2,%3}, {%4,%5}, {%6}, {%0,%1,%2,%3};"
               : "+f"(c[0]), "+f"(c[1]), "+f"(c[2]), "+f"(c[3]) : "r"(a0), "r"(a1), "r"(b0));
}
__device__ __forceinline__ void stsm4(uint32_t addr, uint32_t a, uint32_t b, uint32_t c, uint32_t d) {
  asm volatile("stmatrix.sync.aligned.m8n8.x4.shared.b16 [%0], {%1,%2,%3,%4};" ::"r"(addr), "r"(a), "r"(b), "r"(c), "r"(d) : "memory");
}
__device__ __forceinline__ void stsm4_t(uint32_t addr, uint32_t a, uint32_t b, uint32_t c, uint32_t d) {
  asm volatile("stmatrix.sync.aligned.m8n8.x4.trans.shared.b16 [%0], {%1,%2,%3,%4};" ::"r"(addr), "r"(a), "r"(b), "r"(c), "r"(d) : "memory");
}
__device__ __forceinline__ void ldsm4(uint32_t addr, uint32_t (&v)[4]) {
  asm volatile("ldmatrix.sync.aligned.m8n8.x4.shared.b16 {%0,%1,%2,%3}, [%4];"
               : "=r"(v[0]), "=r"(v[1]), "=r"(v[2]), "=r"(v[3]) : "r"(addr) : "memory");
}
__device__ __forceinline__ void sts128(uint32_t addr, uint4 v) {
  asm volatile("st.shared.v4.b32 [%0], {%1,%2,%3,%4};" ::"r"(addr), "r"(v.x), "r"(v.y), "r"(v.z), "r"(v.w) : "memory");
}
__device__ __forceinline__ uint4 lds128(uint32_t addr) {
  uint4 v;
  asm volatile("ld.shared.v4.b32 {%0,%1,%2,%3}, [%4];" : "=r"(v.x), "=r"(v.y), "=r"(v.z), "=r"(v.w) : "r"(addr) : "memory");
  return v;
}
__device__ __forceinline__ void sts64(uint32_t addr, uint32_t a, uint32_t b) {
  asm volatile("st.shared.v2.b32 [%0], {%1,%2};" ::"r"(addr), "r"(a), "r"(b) : "memory");
}
__device__ __forceinline__ void sts32(uint32_t addr, uint32_t a) { asm volatile("st.shared.b32 [%0], %1;" ::"r"(addr), "r"(a) : "memory"); }
__device__ __forceinline__ uint32_t lds32(uint32_t addr) {
  uint32_t v;
  asm volatile("ld.shared.b32 %0, [%1];" : "=r"(v) : "r"(addr) : "memory");
  return v;
}
__device__ __forceinline__ float2 lds64f_const(uint32_t addr) {
  float2 v;
  asm("ld.shared.v2.f32 {%0,%1}, [%2];" : "=f"(v.x), "=f"(v.y) : "r"(addr));
  return v;
}
template <int N, bool PAIR>
__device__ __forceinline__ void load_tagged(uint3 (&out)[N], const uint4* src, int stride, uint32_t tag, const uint4* last = nullptr) {
  uint32_t bad;
  int spins = 0;
  do {
    if (spins != 0) __nanosleep(kBackoffNs);
    if (++spins > 2000000) __trap();
    bad = 0;
#pragma unroll
    for (int i = 0; i < N; i++) {
      const uint4 v = ld_b128(N == 5 && i == 4 ? last : src + i * stride);
      out[i] = make_uint3(v.x, v.y, v.z);
      bad |= (v.w ^ tag) | (PAIR ? v.z ^ tag : 0);
    }
  } while (N == 4 ? __any_sync(~0u, bad != 0) : bad != 0);
}
__device__ __forceinline__ void sts64f(uint32_t addr, float2 v) { sts64(addr, __float_as_uint(v.x), __float_as_uint(v.y)); }
__device__ __forceinline__ float bf_rest(float v) { return v - __uint_as_float(__float_as_uint(v) & 0xFFFF0000u); }
__device__ __forceinline__ uint32_t bf_upper(float lo, float hi) { return __byte_perm(__float_as_uint(lo), __float_as_uint(hi), 0x7632); }
__device__ __forceinline__ float low_peak(uint4 v) {
  asm("max.xorsign.abs.bf16x2 %0, %0, %1;" : "+r"(v.x) : "r"(v.y));
  asm("max.xorsign.abs.bf16x2 %0, %0, %1;" : "+r"(v.z) : "r"(v.w));
  asm("max.xorsign.abs.bf16x2 %0, %0, %1;" : "+r"(v.x) : "r"(v.z));
  asm("max.xorsign.abs.bf16x2 %0, %0, %1;" : "+r"(v.x) : "r"(v.x << 16));
  return __uint_as_float(__reduce_min_sync(~0u, v.x & 0x7FFF0000u));
}
__device__ __forceinline__ float bias_at(float v) { return __uint_as_float((__float_as_uint(fminf(v, 1e37f)) & 0x7F800000u) | 0x00400000u); }
struct RowConst {
  float nmean, k0, k1, half;
};
__device__ __forceinline__ float gate_scale(float t, const RowConst& k) {
  float th;
  asm("tanh.approx.f32 %0, %1;" : "=f"(th) : "f"(t * fmaf(t * t, k.k1, k.k0)));
  return fmaf(th, k.half, k.half);
}

template <int N>
__device__ __forceinline__ void mma_k16(float (&acc)[2][96], uint32_t a, uint32_t b, int kk, int add = 1) {
#pragma unroll
  for (int m = 0; m < 2; m++) {
    const uint64_t da = desc(a) + (m * 512 + kk * 2), db = desc(b) + kk * 128;
    if (N == 128) wgmma_n128(acc[m], da, db); else wgmma_n192(acc[m], da, db, add);
  }
}

__device__ __forceinline__ void stage_quarter(const float* acc, uint32_t frag, uint32_t frag_x, int b, const uint4* add = nullptr) {
#pragma unroll
  for (int j = 0; j < 4; j++) {
    const float* v = acc + 8 * j;
    uint32_t h[4] = {pack_bf16(v[0], v[1]), pack_bf16(v[2], v[3]), pack_bf16(v[4], v[5]), pack_bf16(v[6], v[7])};
    if (add) {
      const uint32_t a[4] = {add[j].x, add[j].y, add[j].z, add[j].w};
#pragma unroll
      for (int e = 0; e < 4; e++) asm("add.rn.bf16x2 %0, %0, %1;" : "+r"(h[e]) : "r"(a[e]));
    }
    stsm4(frag + b * 8192 + ((frag_x ^ (j * 2)) << 4), h[0], h[1], h[2], h[3]);
  }
}

inline int g1_block(int j, int c) { return j < 16 ? j : ((j + 12) & 15) ^ (c == 5 && j >= 28 ? 2 : 0); }
inline int g2_block(int j, int c) { return j < 8 ? j : j == 8 ? 8 + c : j - (j - 9 < c); }
inline int g3_tile(int j) { return j < 4 ? j >> 1 : j < 18 ? 0 : j >> 4; }
inline int g3_block(int j, int c) {
  const int i = j < 32 ? (j < 16 ? 0xDCBA976543218080ull : 0x7654321BA9FEDCFEull) >> 4 * (j & 15) : j + (~j >> 2 & 4), o = i & 7;
  return 2 * (j < 32 && (o == c || o == 0) ? c - o : o) + (i >> 3 & 1);
}
__device__ __forceinline__ bool g3_is_up(int tile, int a) { return a == 1 || (a == 2 && tile >= 2); }
__device__ __forceinline__ int g3_atom(int tile, int a, int c) { return c * 7 + (tile & 1) * 3 + (a == 2 ? 1 : tile == 4 ? 6 : tile & 2); }
inline int g4_block(int i) {
  const int n = i * 43 >> 7, j = i - 3 * n, m = j ? n : n + (16 - kFirstShared / 3);
  return i < 48 ? 7 * (m & 7) + 3 * (m >> 3 & 1) + j : 7 * i - 330;
}

constexpr int kInPlace = 16, kShared = 64, kNextWave = 128;

template <int N, int TAIL>
__device__ __forceinline__ void mainloop(Scratch* sc, float (&acc)[2][96], uint32_t sb, int ph, int j0, int nsteps, int pause_at, bool last,
                                         bool hand_over, bool local, int wg, int own = -1, const CUtensorMap* out = nullptr, int out_col = 0,
                                         int out_row = 0, int warp = 0, __nv_bfloat16* outp = nullptr) {
  constexpr int NSLOT = N == 128 ? 5 : 4, SLOT = N == 128 ? 32768 : 40960;
  const int lane = fresh_tid() & 31;
  const uint32_t full = sb + kBars + 8 * ring_base(ph);
  const uint32_t empty = map_cta(full + 8 * (NSLOT + (ph == 3)), lane & 1);
  const uint32_t ring = desc_lo(sb + kRing, 16);
  int bi = j0 % NSLOT, par = (j0 / NSLOT) & 1;
  const int release_end = lane < (N == 192 && !hand_over ? 4 : 2) ? (last ? nsteps - 1 - NSLOT : nsteps) : 0;
  uint32_t rel = empty;
  const uint32_t special = ph == 0 && wg == 0 ? 3 : pause_at < 0 ? 1 : 1 | 2 << pause_at;
  int i = 0;
#pragma unroll 1
  for (;;) {
  const int end = TAIL <= 0 ? nsteps : !own ? nsteps - TAIL - 1 : i ? i + 2 : kFirstShared;
#pragma unroll 1
  do {
    uint32_t a = ring + bi * (SLOT >> 4), b = a + kToB;
    if (TAIL > 0 ? i == 0 : special >> i & 1) {
      if (i == 0) nb_sync(kNbOrder + wg, ph == 0 && wg == 0 ? 160 : 256);
      else if (ph == 0 && wg == 0) cluster_wait();
      else if (ph < 2) nb_sync(kNbWin + 1, 256);
    }
    if (N == 192 && local) {
      a = ring + ((kStage + i * 16384) >> 4);
      b = ring + bi * (32768 >> 4) + desc_lo(32768, 8192) - desc_lo(0, 16);
    }
    if (ph == 0 && i >> 1 == own) a = ring + ((kOwn + (i & 1) * 16384) >> 4);
    if (ph == 1 && i == 8) a = ring + ((kStage + 32768) >> 4);
    mbar_wait(full + 8 * bi, par);
    if (N == 192 && local) mbar_wait(sb + kBars + 8 * (kHalfBar + i), 0);
    const bool release = (uint32_t)(i - 1) < (uint32_t)release_end;
    wg_fence();
    mma_k16<N>(acc, a, b, 0, ph == 0 ? i | wg : 1);
    mma_k16<N>(acc, a, b, 1);
    wg_commit();
    wg_wait<1>();
    mbar_arrive_cluster_if(rel, release);
    wg_fence();
    mma_k16<N>(acc, a, b, 2);
    mma_k16<N>(acc, a, b, 3);
    wg_commit();
    rel = empty + 8 * bi;
    if (++bi == NSLOT + (TAIL > 0 && i >= kWide - 16)) { bi = 0; par ^= 1; }
    if (ph < 2 && i == pause_at) nb_arrive(kNbWin, 256);
  } while (++i < end);
  if (TAIL <= 0 || own-- == 0) break;
  const uint32_t a = ring + bi * (SLOT >> 4);
  mbar_wait(full + 8 * bi, par);
  wg_fence();
#pragma unroll
  for (int k = 0; k < 4; k++) wgmma_n128(acc[1], desc(a) + (512 + k * 2), desc(a + kToB) + k * 128);
  wg_commit();
  wg_wait<1>();
  mbar_arrive_cluster_if(rel, lane < 2);
  rel = empty + 8 * bi;
  if (++bi == NSLOT + 1) { bi = 0; par ^= 1; }
  i++;
  }
  if (TAIL < 0) return;
  if (TAIL > 0) {
    uint32_t at[TAIL + 2];
    bi = par = 0;
    const int t = fresh_tid() & 127;
    uint32_t frag = sb + kStage + ((t >> 5) * 16 + (t & 15)) * 128, frag_x = ((t >> 4) & 1) ^ (t & 7);
    const uint32_t back = sb + kStage + (t >> 5) * 2048 + ((t >> 3) & 3) * 128, back_x = ((t ^ (t >> 3 & 3)) & 7) << 4;
    outp = plus(outp, (2 * (out_row + (t >> 5) * 16 + ((t >> 3) & 3)) + (blockIdx.x & 1)) * kD + out_col + (t & 7) * 8);
    auto rows = [&](int m, int i0, int i1) {
      wg_fence();
#pragma unroll
      for (int i = 4 * i0; i < 4 * i1; i++)
        wgmma_n128(acc[m], desc_kept(ring, sb) + (at[i >> 2] + m * 512 + (i & 3) * 2), desc_kept(ring, sb) + (at[i >> 2] + kToB + (i & 3) * 128));
      wg_commit();
    };
    auto last_rows = [&](int i0, int i1) { rows(1, i0, i1); };
    uint4 part[8];
#pragma unroll
    for (int i = 0; i <= TAIL; i++) {
      at[i] = bi * (SLOT >> 4);
      mbar_wait(full + 8 * bi, par);
      if (++bi == NSLOT) { bi = 0; par ^= 1; }
      rows(0, i, i + 1);
      if (i == 1 || i == 2) {
        if (i == 2) mbar_wait(sb + kBars + 8 * kStgBar, 1);
        else nb_sync(kNbPart, 256);
#pragma unroll
        for (int k = 4 * i - 4; k < 4 * i; k++) part[k] = lds128(sb + kStage + 32768 + (t >> 5) * 4096 + (t & 31) * 16 + k * 512);
      }
    }
    last_rows(0, 2);
#pragma unroll
    for (int b = 0; b < 4; b++) {
      if (b == 0) wg_wait<1>();
      if (b == 1) last_rows(3, 4);
      if (b == 2) wg_wait<0>();
      if (!(b & 1)) {
#pragma unroll
        for (int i = 0; i < 64; i++) asm volatile("" : "+f"(acc[b >> 1][i])::"memory");
        if (t == 0) TSS(b);
      }
      stage_quarter(&acc[b >> 1][32 * (b & 1)], frag, frag_x, b, b < 2 ? &part[4 * b] : nullptr);
      if (b == 3) {
        __syncwarp();
        uint4 v[4];
#pragma unroll
        for (int i = 0; i < 4; i++) v[i] = lds128(back + b * 8192 + i * 512 + ((i & 1) ? back_x ^ 64 : back_x));
#pragma unroll
        for (int i = 0; i < 4; i++) __stcs((uint4*)(outp + ((b >> 1) * 128 + i * 8) * kD + (b & 1) * 64), v[i]);
        if (t == 0) TSS(4 + b);
        continue;
      }
      if (b < 2) last_rows(2 + 2 * b, 3 + 2 * b);
      fence_async_smem();
      __syncwarp();
      if (elect_one()) tma_store3d(out, sb + kStage + b * 8192 + warp * 2048, out_col + (b & 1) * 64, out_row + (b >> 1) * 64 + warp * 16, blockIdx.x & 1);
      __syncwarp();
      if (t == 0) TSS(4 + b);
    }
    if (elect_one()) {
      bulk_commit();
      bulk_wait_read();
    }
    if (t == 0) TSS(1);
    return;
  }
  if (hand_over) nb_arrive(kNbOrder + (wg ^ 1), 256);
  if (N == 192 && !local) {
    mbar_wait(sb + kBars + 8 * (kAuxBar + wg), j0 < 32);
    if (j0 < 32) mbar_wait(sb + kBars + 8 * kStatBar, 1);
    mbar_wait(sb + kBars + 8 * (kStgBar + wg), ((j0 >> 5) ^ wg ^ 1) & 1);
  }
  wg_wait<0>();
  mbar_arrive_cluster_if(rel, release_end == nsteps);
#pragma unroll
  for (int i = 0; i < N / 2; i++) asm volatile("" : "+f"(acc[0][i]), "+f"(acc[1][i])::"memory");
}

template <int PH>
struct Ring {
  static constexpr int NSLOT = 4 + (PH & 1), SLOT = PH & 1 ? 32768 : 40960;
  uint32_t full, dst0;
  int j = PH == 0 ? 4 : 0, bi = 0, par = PH == 0 ? 0 : 1;
  __device__ __forceinline__ Ring(uint32_t sb, uint32_t ofs) : full(sb + kBars + 8 * (PH * 9 - (PH & 1))), dst0(sb + kRing + ofs) {}
  __device__ __forceinline__ uint32_t bar() const { return full + 8 * bi; }
  __device__ __forceinline__ uint32_t dst() const { return dst0 + bi * SLOT; }
  __device__ __forceinline__ void acquire_first() const {
    const bool first = j < NSLOT;
    mbar_wait(full + (first ? 8 * min(j, 3) - 32 : 8 * (NSLOT + (PH == 3) + bi)), PH == 2 && first ? 0 : par);
  }
  __device__ __forceinline__ void acquire() const { mbar_wait(full + 8 * (NSLOT + (PH == 3) + bi), par); }
  __device__ __forceinline__ void next() {
    j++;
    if (++bi == NSLOT + (PH == 3 && j > kWide)) { bi = 0; par ^= 1; }
  }
};

__device__ __forceinline__ void check_blocks(const Params& p, Scratch* sc, uint32_t sb, int r, int c, bool g3, uint32_t& par) {
  const int lane = fresh_tid() & 31, nslot = g3 ? 4 : 5, slot_bytes = g3 ? 40960 : 32768;
  const uint32_t mine = (lane >> 2) * 132 + (lane & 3) * 32, ring_end = sb + kRing + kStage + mine;
  const uint32_t to_full = 8 * (kLandBar - (g3 ? ring_base(2) : ring_base(1)));
  uint32_t src = sb + kRing + mine + (g3 ? 0 : 4 * 32768);
  int bi = g3 ? 0 : 4, spins = 0;
#pragma unroll 1
  for (int i = g3 ? 2 : 9; i < 16;) {
    const uint32_t land = sb + kBars + 8 * (kLandBar + bi);
    mbar_wait(land, (par >> bi) & 1);
    uint32_t v[16];
#pragma unroll
    for (int k = 0; k < 16; k++) v[k] = lds32(src + k * 1024);
#pragma unroll
    for (int k = 0; k < 5; k++) v[k] = max(max(v[3 * k + 1], v[3 * k + 2]), k ? v[3 * k] : max(v[0], v[15]));
    const bool again = __any_sync(~0u, max(max(max(v[0], v[1]), v[2]), max(v[3], v[4])) == kPoison);
    asm volatile("{\n.reg .pred p;\nsetp.eq.u32 p, %1, 0;\n@p mbarrier.arrive.shared::cta.b64 _, [%0];\n}\n"
                 ::"r"(land - to_full), "r"(lane + again) : "memory");
    par ^= 1u << bi;
    if (again) {
      if (++spins > 100000) __trap();
      if (elect_one()) {
        mbar_expect_tx(land, 16384);
        tma2d(src - mine, g3 ? &p.h : &p.o, ((g3 ? p.g3[c][i + 2] : p.g2[c][i]) & 15) * 64, r * 128, land);
      }
      nb_sync(kNbSelf + 1, 32);
      continue;
    }
    if (lane == 0 && (i == 2 || i == 3 || (!g3 && (i == 9 || i == 12)))) TS(i < 4 ? 88 + 2 * i : i == 9 ? 120 : 122);
    i++;
    if (++bi == nslot) bi = 0;
    src += slot_bytes;
    if (src == ring_end) src -= kStage;
  }
}

__device__ __forceinline__ void colsum_cta(const Params& p, Scratch* sc, uint32_t sb, int warp, int bid) {
  constexpr int kSlots = 4, kSlot = 49152;
  constexpr int kRows = kMost * 16384, kIn = (kCs - kRows) / 8192;
  const int lane = threadIdx.x & 31, c0 = (bid - 128) * 2;
  const uint32_t full = sb + kBars, empty = full + 8 * kSlots;
  const uint32_t event = full + 64, rfull = full + 128, rempty = full + 256;
  if (threadIdx.x == 0) {
#pragma unroll 1
    for (int i = 0; i < 48; i++) mbar_init(full + 8 * i, i & (i < 16 ? 4 : 32) ? 8 : 1);
    asm volatile("fence.mbarrier_init.release.cluster;" ::: "memory");
  }
  __syncthreads();
  const uint32_t ep = ld_epoch(sc);
  if (warp == 8) {
    if (elect_one()) {
#pragma unroll 1
      for (int n = 0; n < 112 + kSlots; n++) {
        const int u = n >> 4, c = c0 + ((n >> 3) & 1), k0 = (n & 7) * 128, slot = n & (kSlots - 1);
        if (n == kQuietAt) flag_wait(sc->flags + kFlPace, ep);
        const uint32_t bar = full + 8 * slot;
        mbar_wait(empty + 8 * slot, ((n / kSlots) & 1) ^ 1);
        if (n == 108) mbar_arrive(event);
        if (u == 7) continue;
        mbar_expect_tx(bar, u == 6 ? 32768 : 49152);
#pragma unroll
        for (int a = 0; a < 3; a++) {
          if (a == 2 && u == 6) break;
          const CUtensorMap* m = u < 2 ? &p.wqkv : g3_is_up(u - 2, a) ? &p.wu : &p.wg;
          const int col = (u < 2 ? a * 16 + u * 8 + c : g3_atom(u - 2, a, c)) * 64;
          tma2d(sb + slot * kSlot + a * 8192, m, col, k0, bar);
          tma2d(sb + slot * kSlot + a * 8192 + 24576, m, col, k0 + 64, bar);
        }
      }
      mbar_wait(event + 8, 0);
      asm volatile("fence.proxy.async.global;" ::: "memory");
      int slot = 0, par = 1, w = 0;
#pragma unroll 1
      for (int job = 0; job < 32; job++) {
        const int k = lds32(sb + kPlan + (job >> 4) * 4) >> (job & 14) * 2 & 15;
        if (job == 16) {
          mbar_wait(rempty + 8 * (slot ? slot - 1 : kIn - 1), par ^ (slot != 0));
          w = 0;
        }
#pragma unroll 1
        for (int i = 0; i < k; i++) {
          const uint32_t bar = rfull + 8 * slot;
          mbar_wait(bar + 128, par);
          mbar_expect_tx(bar, w < kMost ? 24576 : 8192);
          tma2d(sb + kRows + slot * 8192, &p.hhst, i * (7 * 64), (job & 15) * 128, bar);
          if (w < kMost) {
#pragma unroll
            for (int a = 0; a < 2; a++)
              tma2d(sb + w * 16384 + a * 8192, &p.wd, ((c0 + (job >> 4)) * 2 + a) * 64, w * (7 * 64), bar);
            w++;
          }
          if (++slot == kIn) { slot = 0; par ^= 1; }
        }
      }
    }
  } else if (warp < 8) {
    uint32_t src[3];
#pragma unroll
    for (int j = 0; j < 3; j++) src[j] = sb + ((warp * 3 + j) >> 3) * 8192 + lane * 128 + ((((warp * 3 + j) & 7) ^ (lane & 7)) << 4);
    const uint32_t ones = 0x3F803F80u;
#pragma unroll 1
    for (int s = 0; s < 112; s++) {
      float a[3][2][4] = {};
#pragma unroll 1
      for (;; s++) {
      const int slot = s & (kSlots - 1);
      mbar_wait(full + 8 * slot, (s / kSlots) & 1);
      uint32_t b[3][4][4];
#pragma unroll
      for (int j = 0; j < 3; j++)
#pragma unroll
        for (int k = 0; k < 4; k++)
          asm volatile("ldmatrix.sync.aligned.m8n8.x4.trans.shared.b16 {%0,%1,%2,%3}, [%4];"
                       : "=r"(b[j][k][0]), "=r"(b[j][k][1]), "=r"(b[j][k][2]), "=r"(b[j][k][3])
                       : "r"(src[j] + slot * kSlot + (k >> 1) * 24576 + (k & 1) * 4096) : "memory");
      __syncwarp();
      if (lane == 0) mbar_arrive(empty + 8 * slot);
#pragma unroll
      for (int k = 0; k < 4; k++)
#pragma unroll
        for (int j = 0; j < 3; j++) {
          mma16816(a[j][0], ones, ones, ones, ones, b[j][k][0], b[j][k][1]);
          mma16816(a[j][1], ones, ones, ones, ones, b[j][k][2], b[j][k][3]);
        }
      if ((s & 7) == 7) break;
      }
      {
        if (lane < 12) {
          const int j = lane >> 2;
          const float x = j == 0 ? a[0][0][0] + a[0][1][0] : j == 1 ? a[1][0][0] + a[1][1][0] : a[2][0][0] + a[2][1][0];
          const float y = j == 0 ? a[0][0][1] + a[0][1][1] : j == 1 ? a[1][0][1] + a[1][1][1] : a[2][0][1] + a[2][1][1];
          const float x1 = bf_rest(x), y1 = bf_rest(y);
          const bool split = s < 32;
          st_b128(SC_AT(cs, ((s >> 4) * 8 + c0 + ((s >> 3) & 1)) * 96 + warp * 12 + lane), split ? bf_upper(x, y) : __float_as_uint(x),
                  split ? bf_upper(x1, y1) : __float_as_uint(y), bf_upper(bf_rest(x1), bf_rest(y1)), ep);
        }
        if (threadIdx.x == 0 && (s & 8)) TSK(s >> 4);
      }
    }
    const int wg = warp >> 2;
    mbar_wait(event + 8, 0);
#pragma unroll 1
    for (int job = wg, first = 0; job < 32; job += 2) {
      float acc[96];
#pragma unroll
      for (int i = 0; i < 64; i++) asm volatile("" : "=f"(acc[i]));
      const int k = __shfl_sync(~0u, lds32(sb + kPlan + (job >> 4) * 4), 0) >> (job & 14) * 2 & 15;
      int slot = first + wg * k, par = slot / kIn, i = 0;
      slot -= par * kIn;
      first += 2 * k;
      uint32_t done = 0;
      if (job) nb_sync(kNbOrder + wg, 256);
#pragma unroll 1
      do {
        mbar_wait(rfull + 8 * slot, par & 1);
        wg_fence();
#pragma unroll
        for (int kk = 0; kk < 4; kk++)
          wgmma_n128(acc, desc(desc_lo(sb + kRows, 16) + slot * 512) + kk * 2, desc(desc_lo(sb, 8192) + i * 1024) + kk * 128, kk | i);
        wg_commit();
        wg_wait<1>();
        if (lane < 2 && i) mbar_arrive(done);
        done = rempty + 8 * slot;
        if (++slot == kIn) { slot = 0; par++; }
      } while (++i < k);
      if (job < 31) nb_arrive(kNbOrder + (wg ^ 1), 256);
      wg_wait<0>();
#pragma unroll
      for (int i = 0; i < 64; i++) asm volatile("" : "+f"(acc[i])::"memory");
      if (lane < 2) mbar_arrive(done);
#pragma unroll
      for (int i = 0; i < 8; i++) {
        const float* v = &acc[8 * i];
        asm volatile("st.relaxed.gpu.global.v4.b32 [%0], {%1, %2, %3, %4};"
                     ::"l"(SC_AT(part, ((job & 15) * 8 + c0 + (job >> 4)) * 1024 + (warp & 3) * 256 + lane) + i * 32),
                     "r"(pack_bf16(v[0], v[1])), "r"(pack_bf16(v[2], v[3])), "r"(pack_bf16(v[4], v[5])), "r"(pack_bf16(v[6], v[7])) : "memory");
      }
    }
    if (threadIdx.x == 128) TSK(7);
  } else if (warp == 10) {
    mbar_wait(event, 0);
    flag_wait(sc->flags + kFlHH + (lane & 15) * kFlRow, ep * 8);
    int late = await_word(sc->finish + (uint32_t)((lane & 15) * 8 + c0 + (lane >> 4)), ep);
    __syncwarp();
    late -= __shfl_sync(~0u, late, 0);
    late = max(late, __shfl_xor_sync(~0u, late, 1));
    late = max(min(late - (__reduce_add_sync(~0u, late) >> 5) + kShare * kStepNs, 4096), 0);
    int k;
#pragma unroll 1
    do {
      k = min(max(late * (8192 / kStepNs) >> 13, 0) + 1, kMost);
      late -= kStepNs / 4;
    } while (__reduce_add_sync(~0u, max(2 * k, k + 4)) > kBudget);
    k <<= (lane & 14) * 2;
#pragma unroll
    for (int o = 2; o < 16; o <<= 1) k |= __shfl_xor_sync(~0u, k, o);
    asm volatile("fence.acquire.gpu;" ::: "memory");
    send_word(sc->plan + (uint32_t)(c0 + (lane >> 4)), k, ep);
    sts32(sb + kPlan + (lane >> 4) * 4, k);
    __syncwarp();
    if (lane == 0) mbar_arrive(event + 8);
  }
}

#define PROF_BEGIN
template <bool BY_SM>
__global__ void __cluster_dims__(2, 1, 1) __launch_bounds__(kThreads, 1) fused_block_kernel(Scratch* sc, const __nv_bfloat16* xp, const __nv_bfloat16* wqkvp, __nv_bfloat16* outp,
                                                                   const __grid_constant__ Params p) {
  extern __shared__ __align__(1024) uint8_t smem_raw[];
  if (threadIdx.x < 56) {
    const int l = threadIdx.x & 31, b = blockIdx.x & 127;
    if (threadIdx.x < 32) prefetch_l2(xp + (b * 16 + (l & 15)) * kD + (l >> 4) * 64);
    else prefetch_l2(wqkvp + b * (3 * kD) + (l >> 3) * kD + (l & 7) * 64);
  }
  const uint32_t sb = smem_u32(smem_raw);
  const int bid = role_id<BY_SM>();
  const int r = bid >> 3, c = bid & 7, rank = blockIdx.x & 1;
  auto first_fill = [&](int j) {
    const uint32_t fb = sb + kBars + 8 * j, dst = sb + kRing + j * 40960;
    mbar_expect_tx(fb, 40960);
    tma3d(j >> 1 == c ? sb + kOwn + (j & 1) * 16384 : dst, &p.x, j * 64, (r >> 1) * 128, rank, fb);
#pragma unroll
    for (int a = 0; a < 3; a++) tma2d(dst + 16384 + a * 8192, &p.wqkv, a * kD + c * 64, j * 64, fb);
    mbar_arrive(fb);
  };
  const int tid = threadIdx.x, warp = __shfl_sync(~0u, tid >> 5, 0), wg = warp >> 2;
  if (bid >= 128) {
    if (tid == 0) PROF_BEGIN;
    colsum_cta(p, sc, sb, warp, bid);
    return;
  }
  if (wg == 2) {
    if (warp == 8 && elect_one()) {
#pragma unroll
      for (int j = 0; j < 4; j++) mbar_init(sb + kBars + 8 * j, 2);
      asm volatile("fence.mbarrier_init.release.cluster;" ::: "memory");
      first_fill(0);
      TSS(0);
    }
    __syncwarp();
    if (warp == 8) nb_arrive(kNbOrder, 160);
    asm volatile("setmaxnreg.dec.sync.aligned.u32 40;");
    if (warp == 8) {
      cluster_arrive();
      if (elect_one()) {
#pragma unroll 1
        for (int j = 1; j < 4; j++) first_fill(j);
        TSS(1);
      }
      __syncwarp();
    } else {
      if (elect_one()) {
        uint64_t shifts = warp == 9 ? bar_shifts(4) : warp == 10 ? bar_shifts(22) : bar_shifts(40);
#pragma unroll 1
        for (int i = 0; i < 18; i++, shifts >>= 3) mbar_init(sb + kBars + 8 * (18 * warp - 158 + i), 1u << (shifts & 7));
        if (warp == 10) asm volatile("mbarrier.arrive.shared::cta.b64 _, [%0], 2;" ::"r"(sb + kBars + 8 * 31) : "memory");
        sts32(sb + kZero, 0);
        sts32(sb + kScale + 4, 0);
        sts32(sb + kRole, bid);
        sts128(sb + kOnes, make_uint4(0x3F803F80u, 0, 0, 0x3F803F80u));
        asm volatile("fence.mbarrier_init.release.cluster;" ::: "memory");
      }
      __syncwarp();
      cluster_arrive();
    }
    cluster_wait();
    const uint32_t ep = ld_epoch(sc);
    if (tid == 320) sts32(sb + kEpoch, ep);
    if (tid == 320) PROF_BEGIN;
    const int pw = warp & 3;
    if (pw == 0) {
      if (elect_one()) {
        const int row = r * 128;
        const uint32_t land = sb + kBars + 8 * kLandBar;
#pragma unroll 1
        for (Ring<0> q(sb, 0); q.j < 32; q.next()) {
          q.acquire();
          const int kb = p.g1[c][q.j];
          if (kb & kInPlace) { mbar_arrive(q.bar()); continue; }
          mbar_expect_tx(q.bar(), 16384);
          tma3d(kb >> 1 == c ? sb + kOwn + (kb & 1) * 16384 : q.dst(), &p.x, kb * 64, (r >> 1) * 128, rank, q.bar());
        }
        prefetch_map(&p.o);
        prefetch_map(&p.o16);
        flag_wait(sc->flags + kFlO + r * kFlRow, ep * 8);
        fence_async();
        TS(40);
#pragma unroll 1
        for (Ring<1> q(sb, 0); q.j < 16; q.next()) {
          q.acquire_first();
          if (q.j == 8) {
            prefetch_map(&p.wg);
            prefetch_map(&p.wu);
            prefetch_map(&p.h);
            prefetch_map(&p.h16);
            mbar_wait(sb + kBars + 8 * kSentBar, 0);
            mbar_arrive(q.bar());
            mbar_arrive(sb + kBars + 8 * (kStgBar + 1));
            if (bid == 0) __stcg(sc->flags + kFlPace, ep);
            __nanosleep(kGateONs);
            continue;
          }
          const uint32_t bar = q.j < 8 ? q.bar() : land + 8 * q.bi;
          if (q.j == 9) TS(41);
          mbar_expect_tx(bar, 16384);
          tma2d(q.dst(), &p.o, p.g2[c][q.j] * 64, row, bar);
        }
#pragma unroll 1
        for (Ring<2> q(sb, 0); q.j < 64; q.next()) {
          q.acquire_first();
          const int kb = p.g3[c][q.j];
          if (kb & kInPlace) { mbar_arrive(q.bar()); continue; }
          if (q.j == 4) { __nanosleep(kGateHNs); TS(42); }
          const uint32_t bar = q.j < 18 ? land + 8 * q.bi : q.bar();
          mbar_expect_tx(bar, 16384);
          tma2d(q.dst(), &p.h, (kb & 15) * 64, row, bar);
        }
        prefetch_map(&p.hh);
        prefetch_map(&p.out);
        Ring<3> q(sb, 0);
#pragma unroll 1
        for (; q.j < 16; q.next()) {
          q.acquire_first();
          if (q.j == 0) { mbar_arrive(q.bar()); continue; }
          mbar_expect_tx(q.bar(), 16384);
          tma2d(q.dst(), &p.h, ((q.j + 9) & 15) * 64, row, q.bar());
        }
        uint32_t wave = sb + kBars + 8 * kWaveBar;
        int share = 0;
#pragma unroll 1
        for (; q.j < 72; q.next()) {
          const int kb = p.g4[q.j - 16];
          if (kb & kNextWave) {
            mbar_wait(wave, 0);
            fence_async();
            wave += 8;
            if (q.j == 16) share = lds32(sb + kPlan);
          }
          q.acquire();
          const bool half = (kb & kShared) && --share >= 0;
          mbar_expect_tx(q.bar(), half ? 8192 : 16384);
          tma2d(q.dst() + half * 8192, half ? &p.hhst : &p.hh, (kb & 63) * 64, row + half * 64, q.bar());
        }
      }
    } else if (pw == 1) {
      if (elect_one()) {
        const int rp = r >> 1;
#pragma unroll 1
        for (Ring<0> q(sb, 16384); q.j < 32; q.next()) {
          q.acquire();
          mbar_expect_tx(q.bar(), 24576);
          const int col = ((q.j >> 4) * 8 + c) * 64, k0 = (p.g1[c][q.j] & 15) * 64;
          tma2d_mc(q.dst() + rank * 8192, &p.wqkv, rank * kD + col, k0, q.bar());
          if ((q.j & 1) == rank) tma2d_mc(q.dst() + 16384, &p.wqkv, 2 * kD + col, k0, q.bar());
          if (q.j == max(r, 4))
            for (int a = 0; a < 3; a++) tma_prefetch2d(&p.wqkv, a * kD + (8 + c) * 64, ((r + 12) & 15) * 64);
          if (q.j >> 1 == rp + 8) tma_prefetch2d(&p.wo, (c * 2 + rank) * 64, (q.j & 15) * 64);
        }
        if (r < 6) tma_prefetch2d(rp == 1 ? &p.wu : &p.wg, (c * 7 + 3 + (rp >> 1)) * 64, (c * 2 + rank) * 64);
#pragma unroll 1
        for (Ring<1> q(sb, 16384 + rank * 8192); q.j < 16; q.next()) {
          q.acquire_first();
          mbar_expect_tx(q.bar(), 16384);
          tma2d_mc(q.dst(), &p.wo, (c * 2 + rank) * 64, p.g2[c][q.j] * 64, q.bar());
        }
        const CUtensorMap* mine = rank ? &p.wu : &p.wg;
#pragma unroll 1
        for (Ring<2> q(sb, 16384); q.j < 64; q.next()) {
          const int kb = p.g3[c][q.j], tile = kb >> 5, f0 = c * 7 + (tile & 1) * 3, fp = f0 + (tile & 2);
          const int k0 = (kb & 15) * 64;
          q.acquire_first();
          mbar_expect_tx(q.bar(), 24576);
          const uint32_t dst = q.j < 4 ? sb + kRing + (q.j + 1) * 32768 : q.dst();
          tma2d_mc(dst + rank * 8192, mine, fp * 64, k0, q.bar());
          if ((q.j & 1) == rank) tma2d_mc(dst + 16384, tile & 2 ? &p.wu : &p.wg, (f0 + 1) * 64, k0, q.bar());
          const int d = q.j - kPfStep - (c & 1) * 5 - (r >> 2);
          if (d == 0 || d == 11 || d == 22) {
            const int f = c * 7 + (d == 0 ? 2 : d == 11 ? 5 : 6);
            tma_prefetch2d(&p.wg, f * 64, r * 64);
            tma_prefetch2d(&p.wu, f * 64, r * 64);
            if (d != 22) tma_prefetch2d(&p.wu, (f - 1) * 64, r * 64);
            else tma_prefetch2d(&p.wd, (c * 2 + rank) * 64, rp * (7 * 64));
          }
          if (q.j >> 1 == rp + 24) tma_prefetch2d(&p.wd, (c * 2 + rank) * 64, (p.g4[q.j & 15] & 63) * 64);
        }
        Ring<3> q(sb, 16384 + rank * 8192);
#pragma unroll 1
        for (; q.j < 16; q.next()) {
          q.acquire_first();
          mbar_expect_tx(q.bar(), 16384);
          tma2d_mc(q.dst(), mine, (c * 7 + 6) * 64, ((q.j + 9) & 15) * 64, q.bar());
          if (q.j >> 1 == rp) tma_prefetch2d(&p.wd, (c * 2 + rank) * 64, (p.g4[q.j + 16] & 63) * 64);
        }
#pragma unroll 1
        for (; q.j < 72; q.next()) {
          q.acquire();
          mbar_expect_tx(q.bar(), 16384);
          tma2d_mc(q.dst(), &p.wd, (c * 2 + rank) * 64, (p.g4[q.j - 16] & 63) * 64, q.bar());
          if ((q.j & 15) >> 1 == rp && q.j < 40) tma_prefetch2d(&p.wd, (c * 2 + rank) * 64, (p.g4[q.j + 16] & 63) * 64);
        }
      }
    } else {
      const int cw = pw - 2;
      const uint32_t stg = sb + kStage + cw * 32768, rb = sb + kBars + 8 * kResBar;
      uint32_t land_par = 0;
      sts64(sb + kPlan, global_ns(), clock());
      if (cw == 0) {
#pragma unroll 1
        for (int i = 0; i < 16; i++) sts128(sb + kFill + i * 512 + (tid & 31) * 16, make_uint4(kPoison, kPoison, kPoison, kPoison));
        __nanosleep(kSampleNs);
        const uint32_t l15 = tid & 15;
        const uint4 os = __ldg(plus(p.wop, (tid & 31) * 128 + c * 16 + l15));
        const uint4 gs = __ldg(plus(tid & 16 ? p.wup : p.wgp, l15 * 451 + c * 56));
        const uint4 ws = __ldg(plus((const uint4*)wqkvp, (tid & 7) * 385 + (tid & 24) * 16 + (8 + c) * 8));
        sts64(sb + kScale, __float_as_uint(low_peak(os) * kBias3 * low_peak(gs)), __float_as_uint(low_peak(ws) * kBias1) | 1);
        if (tid == 320) TS(93);
      }
#pragma unroll 1
      for (int ev = -1; ev < 4; ev++) {
        const bool quads = cw == 0 && ev == 1;
        if (ev >= cw && !quads) nb_sync(kNbPub + cw, 160);
        if (ev >= cw && elect_one()) {
          if (quads) {
            mbar_wait(sb + kBars + 8 * (kHalfBar + 1), 0);
#pragma unroll 1
            for (int i = 0; i < 2; i++) {
              __nanosleep(i ? kPaceNs : kHoldNs);
              tma_store2d(&p.hst, stg + 16384 + i * 8192, c * 128 + 64, r * 128 + i * 64);
              TS(100 + i);
            }
            bulk_commit();
            bulk_wait_read();
            mbar_arrive(sb + kBars + 8 * kStgBar);
          } else {
            if (ev == 1) {
              const uint32_t now = global_ns();
              const float left = (float)(now - lds32(sb + kPlan)) * (float)kRemain * rcp((float)((uint32_t)clock() - lds32(sb + kPlan + 4)));
              send_word(sc->finish + (uint32_t)bid, now + (uint32_t)left, ep);
            }
            const int it = ev - 2 + cw, f0 = c * 7 + (1 - cw) * 3, fp = it == 2 ? c * 7 + 6 : f0 + 2 * it;
            const bool is_o = ev == 0;
            const CUtensorMap* m = is_o ? &p.ost : &p.hhst;
            const int b0 = is_o ? c : f0 + 1, b1 = fp;
#pragma unroll 1
            for (int i = is_o || it == 1 ? 0 : 2; i < (is_o ? 2 : 4); i++) {
              tma_store2d(m, stg + i * 8192, (i < 2 ? b0 : b1) * 64, r * 128 + (i & 1) * 64);
              if (!is_o) {
                bulk_commit();
                bulk_wait_read();
                __nanosleep(kPaceNs);
              }
            }
            bulk_commit();
            bulk_wait_all();
            mbar_arrive(sb + kBars + 8 * (kStgBar + cw));
            if (ev == 3 + cw) {
#pragma unroll
              for (int i = 0; i < 2; i++) asm volatile("mbarrier.arrive.shared::cluster.b64 _, [%0], 4;" ::"r"(map_cta(sb + kBars + 8 * 37, i)) : "memory");
            }
            flag_signal(SC_AT(flags, kFlHH + ev * 2 - 3 + cw + r * kFlRow));
            TS(44 + cw * 8 + ev);
            if (ev == 2 && cw) {
              sts32(sb + kPlan, await_word(sc->plan + (uint32_t)c, ep) >> (r >> 1) * 4 & 15);
              mbar_expect_tx(rb, 16384);
#pragma unroll 1
              for (int i = 0; i < 2; i++) tma2d(stg + 8192 + i * 16384, &p.hst, c * 128 + i * 64, r * 128 + 64, rb);
            }
          }
        }
        nb_sync(kNbSelf + cw, 32);
        if (ev >= 2 && ev + cw >= 3 && elect_one()) {
          const int wv = cw == 0 ? 3 : ev == 2 ? 0 : 4;
#pragma unroll 1
          for (int i = wv; i <= max(wv, 2); i++) flag_wait(SC_AT(flags, kFlHH + i + r * kFlRow), ep * 8);
          fence_async();
          mbar_arrive(sb + kBars + 8 * (kWaveBar + (wv >> 1)));
          if (wv == 4) {
            mbar_expect_tx(sb + kBars + 8 * kPartBar, 16384);
#pragma unroll 1
            for (int i = 0; i < 2; i++) tma2d(stg + 16384 + i * 8192, &p.hst, c * 128 + i * 64, r * 128, sb + kBars + 8 * kPartBar);
          }
        }
        nb_sync(kNbSelf + cw, 32);
#pragma unroll 1
        for (int sub = 0; ev < 3 && (ev != 0 || cw == 1); sub++) {
          nb_sync(kNbSelf + cw, 32);
          if (ev == 0) check_blocks(p, sc, sb, r, c, sub, land_par);
          const int u = ev < 0 ? cw : 2 * ev + 1 + cw, lane = fresh_tid() & 31;
          if (u == 1 && !sub) {
            uint3 st[5];
            load_tagged<5, true>(st, SC_AT(stat1, r * 128 + lane), 32, ep, SC_AT(stat1, (r < 2 ? r : r - 2) * 128 + (lane & 7)) + 120);
#pragma unroll
            for (int i = 0; i < 4; i++) sts64(sb + kStat + (i * 32 + lane) * 8, st[i].x, st[i].y);
            sts64(sb + kStat - 64 + (lane & 7) * 8, st[4].x, st[4].y);
            nb_sync(kNbSelf + cw, 32);
            if (lane < 4) mbar_arrive(sb + kBars + 8 * kStatBar);
            if (lane == 0) TS(17);
          }
          if (u == 1) {
            const uint4* gh = SC_AT(halo, (sub * 128 + bid) * 192 + lane) - 16 * 192;
            uint4 hv[6] = {};
            nb_sync(kNbHalo, 64);
            uint32_t ns = sub ? kHaloNs : 2 * kBackoffNs;
#pragma unroll 1
            for (int spins = 0; r >= 2; spins++) {
              if (ns) __nanosleep(ns);
              ns = sub ? 0 : kBackoffNs;
              if (spins > 2000000) __trap();
#pragma unroll
              for (int i = 0; i < 6; i++) hv[i] = ld_b128(gh + i * 32);
              uint32_t bad = (hv[5].y ^ ep) | (hv[5].z ^ ep);
#pragma unroll
              for (int i = 0; i < 6; i++) bad |= hv[i].w ^ ep;
              if (!__any_sync(~0u, bad != 0)) break;
            }
            const uint32_t dst = sb + kStage + sub * 32768 + lane * 16;
            sts128(dst, make_uint4(hv[0].x, hv[0].y, hv[0].z, hv[1].x));
            sts128(dst + 512, make_uint4(hv[1].y, hv[1].z, hv[2].x, hv[2].y));
            sts128(dst + 1024, make_uint4(hv[2].z, hv[3].x, hv[3].y, hv[3].z));
            sts128(dst + 1536, make_uint4(hv[4].x, hv[4].y, hv[4].z, hv[5].x));
            nb_arrive(kNbHalo + 1, 64);
            if (lane == 0) TS(123 + sub);
          }
          if (sub) break;
          uint3 v[3];
          load_tagged<3, false>(v, SC_AT(cs, c * 96 + u * 768 + lane), 32, ep);
          if (u < 2) {
#pragma unroll
            for (int i = 0; i < 3; i++)
#pragma unroll
              for (int k = 0; k < 8; k++)
                sts32(sb + kAug + cw * 4096 + i * 1024 + k * 128 + ((lane * 4) ^ (k * 16)), k == 7 ? 0x3F803F80u : k == 4 || k == 6 ? v[i].z : k & 1 && k != 5 ? v[i].y : v[i].x);
            fence_async_smem();
          } else {
#pragma unroll
            for (int i = 0; i < 3; i++) sts64(sb + kCs + cw * 768 + (i * 32 + lane) * 8, v[i].x, v[i].y);
          }
          nb_sync(kNbSelf + cw, 32);
          if (lane == 0) { mbar_arrive(sb + kBars + 8 * (kAuxBar + cw)); TS(104 + u); }
        }
        nb_sync(kNbSelf + cw, 32);
        if (ev < 0 && cw == 0 && elect_one()) {
#pragma unroll 1
          for (int i = 0; i < 6; i++) {
            __nanosleep(i == 0 ? (c >> 1) * (kFillNs / 4) : kFillNs);
            tma_store2d(i < 2 ? &p.ost : &p.hst, sb + kFill, i < 2 ? (8 + c) * 64 : (c * 2 - 1 + (i >> 1)) * 64, r * 128 + (i & 1) * 64);
            bulk_commit();
          }
          uint32_t peer;
          asm volatile("ld.shared::cluster.b32 %0, [%1];" : "=r"(peer) : "r"(map_cta(sb + kRole, rank ^ 1)) : "memory");
          if (peer != (bid ^ 8)) __trap();
          TS(90);
        }
        nb_sync(kNbSelf + cw, 32);
      }
    }
  } else {
    if (tid == 0) TSS(2);
    cluster_arrive();
    float bias = 0.f;
    float sx = 0.f, mx = 0.f;
    asm volatile("setmaxnreg.inc.sync.aligned.u32 232;");
    if (tid == 0) TSS(4);
    int task;
    asm volatile("mov.u32 %0, %1;" : "=r"(task) : "r"(8 - wg));

#pragma unroll 1
    for (task = __shfl_sync(~0u, task, 0);; task++) {
      if (task == 1 + wg || task == 9 - wg) {
        const int t = fresh_tid();
        uint2 scale;
        do asm volatile("ld.volatile.shared.v2.b32 {%0, %1}, [%2];" : "=r"(scale.x), "=r"(scale.y) : "r"(sb + kScale) : "memory");
        while (scale.y == 0);
        __syncwarp();
        bias = bias_at(low_peak(lds128(sb + (task > 5 ? kRing : kStage + wg * 32768) + (t & 126) * 64 + (t & 14) * 8 + (t & 1) * 8192)) *
                       __uint_as_float(task > 5 ? scale.y : scale.x));
        if (t == 128 && task > 5) TS(95);
      }
      if (wg == 0 && (task == 1 || task == 4)) {
        float acc[2][96];
        const int t = fresh_tid() & 127;
        const uint32_t frag = sb + kOwn + ((t >> 5) * 16 + (t & 15)) * 128, frag_x = ((t >> 4) & 1) ^ (t & 7);
        TSG(2);
        if (task == 4) mbar_wait(sb + kBars + 8 * kResBar, 0);
        auto residual = [&](int m) {
#pragma unroll
          for (int i = 0; i < 8; i++) {
            uint32_t v[4];
            ldsm4(frag + (i >> 2) * 16384 + m * 8192 + ((frag_x ^ (i * 2 & 6)) << 4), v);
#pragma unroll
            for (int e = 0; e < 4; e++) {
              float* d = &acc[m][8 * i + 2 * e];
              asm("shl.b32 %0, %1, 16;" : "=f"(d[0]) : "r"(v[e]));
              asm("and.b32 %0, %1, 0xFFFF0000;" : "=f"(d[1]) : "r"(v[e]));
            }
          }
        };
        residual(1);
        if (task == 1) {
          residual(0);
        } else {
#pragma unroll
          for (int i = 0; i < 64; i++) acc[0][i] = 0.f;
        }
        __syncwarp();
        if ((t & 31) == 0) mbar_arrive(sb + kBars + 8 * kResFreeBar);
        TSG(4);
        if ((tid & 127) == 0) TS(task == 1 ? 6 : 14);
        if (task == 4) {
          mainloop<128, kTail>(sc, acc, sb, 3, 16, 56, -2, true, false, false, 0, __shfl_sync(~0u, lds32(sb + kPlan), 0), &p.out, c * 128, (r >> 1) * 128, warp, outp);
          if ((tid & 127) == 0) TSK(15);
          if (fresh_tid() == 0) {
            if (bid == 0) __stcg(sc->epoch, lds32(sb + kEpoch));
            TSK(19);
          }
          break;
        }
        mainloop<128, -1>(sc, acc, sb, 1, 0, 15, kPauseG2, false, true, false, 0);
        const int t2 = fresh_tid() & 127;
        const uint32_t frag2 = sb + kStage + ((t2 >> 5) * 16 + (t2 & 15)) * 128, frag2_x = ((t2 >> 4) & 1) ^ (t2 & 7);
        const uint32_t empty = map_cta(sb + kBars + 8 * (ring_base(1) + 5), t2 & 1);
        mbar_wait(sb + kBars + 8 * kStgBar, 0);
        mbar_wait(sb + kBars + 8 * ring_base(1), 1);
#pragma unroll
        for (int m = 0; m < 2; m++) {
          const uint32_t a = desc_lo(sb + kRing, 16);
          wg_fence();
#pragma unroll
          for (int k = 0; k < 4; k++) wgmma_n128(acc[m], desc_kept(a, sb) + (m * 512 + k * 2), desc_kept(a, sb) + (kToB + k * 128));
          wg_commit();
          if (m) nb_arrive(kNbOrder + 1, 256);
          wg_wait<1>();
          if (!m) mbar_arrive_cluster_if(empty + 8 * 4, (t2 & 31) < 2);
        }
#pragma unroll
        for (int b = 0; b < 4; b++) {
          if (b == 1) {
            wg_wait<0>();
            if (t2 == 0) TSK(7);
          }
          if (b < 2) {
#pragma unroll
            for (int i = 0; i < 64; i++) asm volatile("" : "+f"(acc[b][i])::"memory");
          }
          stage_quarter(&acc[b & 1][32 * (b >> 1)], frag2, frag2_x, b);
          if (b & 1) {
            fence_async_smem();
            __syncwarp();
            if (elect_one()) {
              mbar_arrive(sb + kBars + 8 * (kHalfBar + (b >> 1)));
#pragma unroll
              for (int m = 0; m < 2; m++)
                if (b == 1) tma_store2d(&p.h16, sb + kStage + m * 8192 + warp * 2048, c * 128, r * 128 + m * 64 + warp * 16);
            }
            __syncwarp();
          }
        }
        if (t2 == 0) TS(8);
        sx = mx = 0.f;
        continue;
      }
      float acc[2][96];
      if (task == 8 + wg) {
        wg_fence();
#pragma unroll
        for (int m = 0; m < 2; m++) wgmma_n192_any(acc[m], desc(64 + m), desc(64 + m));
        wg_commit();
        wg_wait<0>();
#pragma unroll
        for (int i = 0; i < 96; i++) asm volatile("" : "+f"(acc[0][i]), "+f"(acc[1][i])::"memory");
      } else {
        const uint32_t z = fresh_tid() >> 10;
#pragma unroll
        for (int i = 0; i < 96; i++) {
#pragma unroll
          for (int m = 0; m < 2; m++) {
            if ((2 * i + m) % kInitMix == kInitMix - 1) asm("fma.rn.f32 %0, %1, %2, %3;" : "=f"(acc[m][i]) : "f"(__uint_as_float(z)), "f"(2 * i + m + 2.f), "f"(bias));
            else asm("{\n.reg .b32 t;\nlop3.b32 t, %1, %2, %3, 0xEA;\nmov.b32 %0, t;\n}\n" : "=f"(acc[m][i]) : "r"(z), "r"(2 * i + m + 1), "r"(__float_as_uint(bias)));
          }
        }
      }
      if (task > 5) {
      if (wg) {
        if (task == 7) cluster_wait();
        if (tid == 128 && task == 7) { TSS(5); TSK(69); }
        const int t = fresh_tid() & 127, lr = c * 16 + (t >> 3);
        uint32_t pf = t < 64 ? (bid * 16 + (t >> 2)) * kD + (t & 3) * 64 : (r * 48 + t - 64) * kD + c * 64;
        const uint32_t src = sb + kRing + lr * 128 + (((t ^ lr) & 7) << 4), empty = map_cta(sb + kBars + 8 * 4, t & 1), zero = fresh_tid() >> 10;
#pragma unroll 1
        for (int j = task == 7 ? 0 : kSplit; j < (task == 7 ? kSplit : 16); j++) {
          mbar_wait(sb + kBars + 8 * (j & 3), (j >> 2) & 1);
          if (j < 2 && t == 0) TS(102 + j);
          const uint4 v = lds128(src + (j >> 1 == c ? kOwn + (j & 1) * 16384 : (j & 3) * 40960));
          __syncwarp();
          mbar_arrive_cluster_if(empty + 8 * (j & 3) + (v.x & zero), (t & 31) < 2);
          if ((j == 0 || j == 3 || j == 6) && t < 112) { pf += t < 64 ? 256 : 256 * 3 * kD; prefetch_l2(plus(t < 64 ? xp : wqkvp, pf)); }
          const uint32_t u[4] = {v.x, v.y, v.z, v.w};
#pragma unroll
          for (int e = 0; e < 4; e++) {
            const float d0 = bf_lo(u[e]), d1 = bf_hi(u[e]);
            sx += d0 + d1;
            mx = fmaf(d1, d1, fmaf(d0, d0, mx));
          }
        }
        if (task == 7) {
          if (t == 0) TS(96);
          continue;
        }
#pragma unroll
        for (int o = 4; o > 0; o >>= 1) { sx += __shfl_xor_sync(~0u, sx, o); mx += __shfl_xor_sync(~0u, mx, o); }
        const float mean = sx * (1.f / kD);
        float rstd;
        asm("rsqrt.approx.ftz.f32 %0, %1;" : "=f"(rstd) : "f"(fmaxf(mx * (1.f / kD) - mean * mean, 0.f) + 1e-5f));
        const uint32_t ep = lds32(sb + kEpoch);
        const int t2 = fresh_tid();
        if ((t2 & 7) == 0) st_b128(SC_AT(stat1, bid * 16 + (t2 >> 3 & 15)), __float_as_uint(rstd), __float_as_uint(-mean), ep, ep);
        if (t == 0) TS(16);
      }
      if (tid == 0) TSS(6);
      mainloop<192, -1>(sc, acc, sb, 0, wg * 16, wg ? 16 - kAhead : 16, wg ? kPauseG1 : -2, false, wg == 0, false, wg,
                        wg ? min((c + 2) & 7, 6) : c);
      int t = fresh_tid() & 127, lane = t & 31, g = lane >> 2, q = lane & 3;
      const int w = warp & 3;
      const uint32_t stg = sb + kStage + wg * 32768;
      auto tail = [&](int m, int k0, int k1) {
        wg_fence();
#pragma unroll
        for (int k = k0; k < k1; k++) {
          const uint64_t a = desc_kept(desc_lo(sb + kRing, 16), sb) + (4 - kAhead + (k >> 2)) * (40960 >> 4);
          wgmma_n192(acc[m], a + (m * 512 + (k & 3) * 2), a + (kToB + (k & 3) * 128));
        }
      };
      auto release = [&](int j, bool cond) { mbar_arrive_cluster_if(map_cta(sb + kBars + 8 * (4 + (j & 3)), lane & 1), cond); };
      if (wg) {
#pragma unroll
        for (int j = 32 - kAhead; j < 32; j++) {
          TST(2 * (j & 1));
          mbar_wait(sb + kBars + 8 * (j & 3), 1);
          TST(2 * (j & 1) + 1);
          tail(1, 4 * (j - 32 + kAhead), 4 * (j - 31 + kAhead));
          wg_commit();
          if (j == 32 - kAhead) {
            wg_wait<1>();
            release(j - 1, lane < 4);
            mbar_wait(sb + kBars + 8 * kResFreeBar, 0);
          }
        }
      } else {
        nb_arrive(kNbOrder + 1, 256);
        wg_wait<0>();
        release(15, lane < 2);
        if (t == 0) TSK(1);
      }
      TST(4);
      mbar_wait(sb + kBars + 8 * (kAuxBar + wg), 0);
      mbar_wait(sb + kBars + 8 * kStatBar, 0);
      {
        uint32_t am[4];
#pragma unroll
        for (int i = 0; i < 4; i++) {
          const float m1 = __uint_as_float(lds32(sb + kStat + (w * 16 + g) * 8 + 4 + (i >> 1) * 512 + (i & 1) * 64));
          const float m2 = bf_rest(m1), lo = q & 1 ? m2 : m1;
          am[i] = bf_upper(lo, q == 3 ? -bias : q == 2 ? bf_rest(m2) : lo);
        }
        const uint64_t db = (uint64_t)desc_lo(sb + kAug + wg * 4096, 1024) | (0x40000000ull << 32);
        TST(5);
        wg_fence();
        wgmma_n192_rs(acc[1], am[2], am[3], 0u, db);
        wg_commit();
        TST(6);
        wg_fence();
        wgmma_n192_rs(acc[0], am[0], am[1], 0u, db);
        wg_commit();
        if (wg) {
          tail(0, 0, 4 * kAhead);
          wg_commit();
          wg_wait<2>();
        } else {
          wg_wait<1>();
        }
        TST(8);
#pragma unroll
        for (int i = 0; i < 96; i++) asm volatile("" : "+f"(acc[1][i])::"memory");
      }
      t = fresh_tid() & 127, lane = t & 31;
      const uint32_t ep = lds32(sb + kEpoch);
      uint32_t pk[2][48];
      auto fold = [&](int pp, int jn, int hf) {
        const uint32_t v = pack_bf16(acc[pp][4 * jn + 2 * hf], acc[pp][4 * jn + 2 * hf + 1]);
        pk[pp][2 * jn + hf] = jn >= 16 ? movm(v) : v;
      };
      if (t == 96) TS(115 + wg);
#pragma unroll
      for (int jn = 8; jn < 24; jn++) fold(1, jn, 1);
      if (w < 3) {
#pragma unroll
        for (int i = 0; i < 4; i++)
          sts128(stg + (w + 5) * 2048 + i * 512 + lane * 16, make_uint4(pk[1][17 + 8 * i], pk[1][19 + 8 * i], pk[1][21 + 8 * i], pk[1][23 + 8 * i]));
      } else if (r < 14) {
        uint4* gh = SC_AT(halo, (wg * 128 + bid) * 192 + lane);
#pragma unroll
        for (int i = 0; i < 6; i++) st_b128(gh + i * 32, pk[1][17 + 6 * i], i < 5 ? pk[1][(19 + 6 * i) % 48] : ep, i < 5 ? pk[1][(21 + 6 * i) % 48] : ep, ep);
        if (wg == 0) {
#pragma unroll 1
          for (int i = 0; i < 6; i++, gh += 32) st_b128(gh + 128 * 192, 0, 0, 0, ep - 1);
        }
      }
      if (w == 3) nb_arrive(kNbHalo, 64);
      if (wg) nb_arrive(kNbOrder, 256);
      TST(9);
      if (t == 96) TS(111 + wg);
#pragma unroll
      for (int jn = 23; jn >= 0; jn--) {
        fold(1, jn, 0);
        if (jn < 8) fold(1, jn, 1);
      }
      t = fresh_tid() & 127, lane = t & 31, g = lane >> 2, q = lane & 3;
      const bool sel0 = 2 * q > g, sel1 = 2 * q + 1 > g, no_prev = (r < 2 && w == 0);
      const uint4 ones = lds128(sb + kOnes);
      const uint32_t lowmask = (sel0 ? 0x0000FFFFu : 0u) | (sel1 ? 0xFFFF0000u : 0u) | ones.y;
      float rs[4][2], rk[4][2];
#pragma unroll
      for (int i = 0; i < 4; i++) {
        const uint32_t a = sb + kStat + w * 128 + (i >> 1) * 512 + (i & 1) * 64;
        const float rq = __uint_as_float(lds32(a + g * 8)) * (0.17677669529663687f * 1.4426950408889634f);
        rk[i][0] = __uint_as_float(lds32(a + q * 16 - (sel0 ? 64 : 0)));
        rk[i][1] = __uint_as_float(lds32(a + q * 16 + 8 - (sel1 ? 64 : 0)));
        rs[i][0] = rk[i][0] * rq;
        rs[i][1] = rk[i][1] * rq;
      }
      {
        uint32_t all = ~0u;
#pragma unroll
        for (int i = 0; i < 48; i++) if (i < 16 || !(i & 1)) all &= pk[1][i];
        if (all == kPoison) sts32(sb + kZero + 8, 0);
      }
      TST(10);
      wg_wait<0>();
      TST(11);
#pragma unroll
      for (int j = 32 - kAhead; j < 32; j++) release(j, lane < 4 * wg && (w != 0 || j < 31));
#pragma unroll
      for (int i = 0; i < 96; i++) asm volatile("" : "+f"(acc[0][i])::"memory");
      if (t == 0 && wg) TSK(21);
#pragma unroll
      for (int jn = 8; jn < 24; jn++) fold(0, jn, 1);
#pragma unroll
      for (int i = 0; i < 4; i++)
        sts128(stg + (w + 1) * 2048 + i * 512 + lane * 16, make_uint4(pk[0][17 + 8 * i], pk[0][19 + 8 * i], pk[0][21 + 8 * i], pk[0][23 + 8 * i]));
#pragma unroll
      for (int jn = 23; jn >= 0; jn--) {
        fold(0, jn, 0);
        if (jn < 8) fold(0, jn, 1);
      }
      if (t == 0) TS(113 + wg);
      nb_sync(kNbWg + wg, 128);
      uint32_t hal[2][16];
      auto load_halo = [&](int m) {
#pragma unroll
        for (int i = 0; i < 4; i++) {
          const uint4 v = lds128(stg + w * 2048 + m * 8192 + i * 512 + lane * 16);
          uint32_t* h = &hal[m][i * 4];
          h[0] = v.x; h[1] = v.y; h[2] = v.z; h[3] = v.w;
        }
      };
      load_halo(1);
      if (w == 0) {
        nb_sync(kNbHalo + 1, 64);
        release(31, lane < 4 * wg);
      }
      load_halo(0);
      __syncwarp();
      if (t == 0) TS(2 + wg * 20);
      {
        uint32_t all = lowmask;
#pragma unroll
        for (int i = 0; i < 32; i++) if (i < 16 || !(i & 1)) all &= pk[0][i];
#pragma unroll
        for (int i = 0; i < 8; i++) all &= __float_as_uint(rs[i >> 1][i & 1]);
        if (all == kPoison) sts32(sb + kZero + 8, 0);
      }
      nb_sync(kNbWin, 256);
      if (t == 0) TS(9 + wg * 20);
      const uint32_t zero = lds32(sb + kZero);
      float s0[4][4], s1[4][4], s2[4][4];
#pragma unroll
      for (int k = 0; k < 4; k++) {
        pk[k >> 1][8 * (k & 1)] |= zero;
#pragma unroll
        for (int e = 0; e < 4; e++) s0[k][e] = s1[k][e] = s2[k][e] = 0.f;
      }
#pragma unroll
      for (int ks = 0; ks < 2; ks++)
#pragma unroll
        for (int k = 0; k < 4; k++) {
          const uint32_t* qf = &pk[k >> 1][8 * (k & 1) + 4 * ks];
          const uint32_t* kf = &pk[k >> 1][16 + 8 * (k & 1) + 4 * ks];
          const uint32_t* hf = &hal[k >> 1][4 * (k & 1) + 2 * ks];
          mma16816(s0[k], qf[0], qf[1], qf[2], qf[3], hf[0], hf[1]);
          mma16816(s1[k], qf[0], qf[1], qf[2], qf[3], kf[0], kf[2]);
          mma16816(s2[k], qf[0], qf[1], qf[2], qf[3], kf[1], kf[3]);
        }
      float ea[4][2], eb[4][2], ma[4], mb[4];
#pragma unroll
      for (int k = 0; k < 4; k++) {
        const float *ra = rs[k & 2], *rb = rs[(k & 2) + 1];
        if (no_prev && k < 2) s0[k][0] = s0[k][1] = -INFINITY;
        ea[k][0] = (sel0 ? s0[k][0] : s1[k][0]) * ra[0]; ea[k][1] = (sel1 ? s0[k][1] : s1[k][1]) * ra[1];
        eb[k][0] = (sel0 ? s1[k][2] : s2[k][2]) * rb[0]; eb[k][1] = (sel1 ? s1[k][3] : s2[k][3]) * rb[1];
        ma[k] = fmaxf(ea[k][0], ea[k][1]); mb[k] = fmaxf(eb[k][0], eb[k][1]);
      }
#pragma unroll
      for (int o = 1; o < 4; o <<= 1)
#pragma unroll
        for (int k = 0; k < 4; k++) {
          ma[k] = fmaxf(ma[k], __shfl_xor_sync(~0u, ma[k], o));
          mb[k] = fmaxf(mb[k], __shfl_xor_sync(~0u, mb[k], o));
        }
      float ov[4][4][4], ls[4][4];
      uint32_t all = 0;
#pragma unroll
      for (int k = 0; k < 4; k++) {
        const float *ra = rk[k & 2], *rb = rk[(k & 2) + 1];
        ea[k][0] = ex2(ea[k][0] - ma[k]); ea[k][1] = ex2(ea[k][1] - ma[k]);
        eb[k][0] = ex2(eb[k][0] - mb[k]); eb[k][1] = ex2(eb[k][1] - mb[k]);
        const uint32_t pa = pack_bf16(ea[k][0] * ra[0], ea[k][1] * ra[1]), pb = pack_bf16(eb[k][0] * rb[0], eb[k][1] * rb[1]);
        const uint32_t* vf = &pk[k >> 1][32 + 8 * (k & 1)];
        const uint32_t* hf = &hal[k >> 1][8 + 4 * (k & 1)];
#pragma unroll
        for (int d2 = 0; d2 < 2; d2++) {
#pragma unroll
          for (int e = 0; e < 4; e++) ov[k][d2][e] = ov[k][2 + d2][e] = 0.f;
          mma1688(ov[k][d2], hf[2 * d2], hf[2 * d2 + 1], pa & lowmask);
          mma1688(ov[k][2 + d2], vf[4 * d2], vf[4 * d2 + 2], pb & lowmask);
        }
#pragma unroll
        for (int d2 = 0; d2 < 2; d2++) {
          mma1688(ov[k][d2], vf[4 * d2], vf[4 * d2 + 2], pa & ~lowmask);
          mma1688(ov[k][2 + d2], vf[4 * d2 + 1], vf[4 * d2 + 3], pb & ~lowmask);
        }
        ls[k][0] = ls[k][1] = ls[k][2] = ls[k][3] = 0.f;
        mma16816(ls[k], ones.x, ones.y, ones.z, ones.w, pack_bf16(ea[k][0], ea[k][1]), pack_bf16(eb[k][0], eb[k][1]));
        if (k >= kDone) all |= pa & pb;
      }
#pragma unroll
      for (int k = 0; k < 4; k++) {
        if (k == kDone) {
          if (all == 0xFFFFFFFFu) sts32(sb + kZero + 8, 0);
          nb_arrive(kNbWin + 1, 256);
          all = 0;
        }
        all |= (__float_as_uint(ov[k][0][0]) & __float_as_uint(ov[k][1][0]) & __float_as_uint(ov[k][2][0])) &
               (__float_as_uint(ov[k][3][0]) & __float_as_uint(ls[k][0]));
      }
      const uint32_t nil = lds32(sb + kZero);
      const uint32_t frag = stg + (w * 16 + (lane & 15)) * 128, frag_x = (lane >> 4) ^ (lane & 7);
      uint32_t after = all;
#pragma unroll
      for (int k = 0; k < 4; k++) {
        uint32_t h[2][4];
#pragma unroll
        for (int hf = 0; hf < 2; hf++) {
          const float i0 = rcp(__uint_as_float(__float_as_uint(ls[k][2 * hf]) | (after & nil)));
          const float i1 = rcp(__uint_as_float(__float_as_uint(ls[k][2 * hf + 1]) | (after & nil)));
#pragma unroll
          for (int e = 0; e < 4; e++) h[e >> 1][2 * (e & 1) + hf] = pack_bf16(ov[k][2 * hf + (e >> 1)][2 * (e & 1)] * i0, ov[k][2 * hf + (e >> 1)][2 * (e & 1) + 1] * i1);
          after = h[0][hf];
        }
#pragma unroll
        for (int d2 = 0; d2 < 2; d2++) stsm4_t(frag + (k >> 1) * 8192 + ((frag_x ^ ((k & 1) * 4 + d2 * 2)) << 4), h[d2][0], h[d2][1], h[d2][2], h[d2][3]);
      }
      fence_async_smem();
      if (wg) {
        __syncwarp();
        if (elect_one()) {
          tma_store2d(&p.o16, stg + w * 2048, (8 + c) * 64, r * 128 + w * 16);
          tma_store2d(&p.o16, stg + 8192 + w * 2048, (8 + c) * 64, r * 128 + 64 + w * 16);
          bulk_commit();
          bulk_wait_read();
          mbar_arrive(sb + kBars + 8 * kSentBar);
        }
        __syncwarp();
      } else {
        nb_arrive(kNbPub, 160);
      }
      if (t == 0) TS(3 + wg * 20);
      task = wg;
      sx = mx = bias = 0.f;
      continue;
      }

      {
#pragma unroll 1
        for (int part = task != 2; part < 2; part++) {
          if ((tid & 127) == 0) TS(6 + 2 * task + wg * 20);
          if (task + part == 5) {
            mainloop<128, 0>(sc, acc, sb, 3, 0, 16, -2, false, true, false, 1);
            continue;
          }
          const int j0 = task == 3 ? 48 - wg * 16 : part == 0 ? 2 - 2 * wg : 18 - 14 * wg;
          mainloop<192, 0>(sc, acc, sb, 2, j0, task != 2 ? 16 : part == 0 ? 2 : 14, -2, false, true, part == 0, wg);
          if (part == 0 && wg == 0) {
            const int t = fresh_tid() & 127;
            const uint32_t ep = lds32(sb + kEpoch);
            {
              float s = 0.f, ss = 0.f;
#pragma unroll 1
              for (int i = 0; i < 16; i++) {
                const uint4 v = lds128(sb + kStage + t * 128 + (i >> 3) * 16384 + (((i ^ t) & 7) << 4));
                const uint32_t u[4] = {v.x, v.y, v.z, v.w};
#pragma unroll
                for (int e = 0; e < 4; e++) {
                  const float d0 = bf_lo(u[e]), d1 = bf_hi(u[e]);
                  s = (s + d0) + d1;
                  ss = fmaf(d1, d1, fmaf(d0, d0, ss));
                }
              }
              st_b128(SC_AT(stat2, c * kS + r * 128 + t), __float_as_uint(s), __float_as_uint(ss), ep, ep);
            }
            __nanosleep(kStatNs);
            float2 sum = make_float2(0.f, 0.f);
#pragma unroll 1
            for (int i = 0; i < 2; i++) {
              uint3 a[4];
              load_tagged<4, true>(a, SC_AT(stat2, i * 4 * kS + r * 128 + t), kS, ep);
              sum.x += (__uint_as_float(a[0].x) + __uint_as_float(a[1].x)) + (__uint_as_float(a[2].x) + __uint_as_float(a[3].x));
              sum.y += (__uint_as_float(a[0].y) + __uint_as_float(a[1].y)) + (__uint_as_float(a[2].y) + __uint_as_float(a[3].y));
            }
            const float mean = sum.x * (1.f / kD);
            sts64f(sb + kStat + t * 8, make_float2(fmaxf(sum.y * (1.f / kD) - mean * mean, 0.f) + 1e-5f, -mean));
            __syncwarp();
            if (elect_one()) {
              bulk_commit();
              bulk_wait_read();
              mbar_arrive(sb + kBars + 8 * kStatBar);
            }
            __syncwarp();
            if (t == 0) TS(37);
          }
        }
      }
      const int t = fresh_tid() & 127, w = warp & 3, lane = t & 31, g = lane >> 2, q = lane & 3;
      const uint32_t stg = sb + kStage + wg * 32768;
      uint32_t csv = sb + kCs + wg * 768 + q * 8;
      uint32_t statv = sb + kStat + (w * 16 + g) * 8;
      const uint32_t frag = stg + (w * 16 + (lane & 15)) * 128;
      const uint32_t frag_x = (lane >> 4) ^ (lane & 7);
      const uint32_t priv = stg + (t & 96) * 64 + lane * 16;
      if (t == 0) TSK(7 + 2 * task + wg * 20);

      if (task == 4) {
        mbar_wait(sb + kBars + 8 * (kAuxBar + 1), 1);
        mbar_wait(sb + kBars + 8 * kResFreeBar, 1);
        mbar_wait(sb + kBars + 8 * (kStgBar + 1), 0);
      }
      asm volatile("" : "+r"(csv), "+r"(statv)::"memory");

      {
#pragma unroll
        for (int i = 0; i < 96; i++) asm volatile("sub.f32 %0, %0, %1;" : "+f"(acc[0][i]) : "f"(bias));
#define NEXT(i) asm volatile("sub.f32 %0, %1, %2;" : "=f"(acc[0][i]) : "f"(acc[1][i]), "f"(bias))
#pragma unroll 1
        for (int pp = 0; pp < 2; pp++) {
          TSG(pp);
          RowConst rc[2];
#pragma unroll
          for (int hf = 0; hf < 2; hf++) {
            const float2 st = lds64f_const(statv + pp * 512 + hf * 64);
            float rstd;
            asm("rsqrt.approx.ftz.f32 %0, %1;" : "=f"(rstd) : "f"(st.x));
            rc[hf] = {st.y, 0.7978845608f * rstd, 0.0356774081f * rstd * rstd * rstd, 0.5f * rstd * rstd};
          }
#pragma unroll
          for (int j2 = 0; j2 < 4; j2++) {
            uint32_t hv[4];
#pragma unroll
            for (int jj = 0; jj < 2; jj++) {
              const int jn = 2 * j2 + jj;
              const float2 cg = lds64f_const(csv + jn * 32), cu = lds64f_const(csv + 256 + jn * 32);
#pragma unroll
              for (int hf = 0; hf < 2; hf++) {
                const float nm = rc[hf].nmean;
                const float g0 = fmaf(nm, cg.x, acc[0][4 * jn + 2 * hf]), g1 = fmaf(nm, cg.y, acc[0][4 * jn + 2 * hf + 1]);
                const float u0 = fmaf(nm, cu.x, acc[0][32 + 4 * jn + 2 * hf]), u1 = fmaf(nm, cu.y, acc[0][33 + 4 * jn + 2 * hf]);
                hv[2 * jj + hf] = pack_bf16(g0 * u0 * gate_scale(g0, rc[hf]), g1 * u1 * gate_scale(g1, rc[hf]));
              }
            }
            stsm4(frag + 16384 + pp * 8192 + ((frag_x ^ (j2 * 2)) << 4), hv[0], hv[1], hv[2], hv[3]);
          }
          if (task < 4) {
            if (task == 2) {
#pragma unroll
              for (int j2 = 0; j2 < 4; j2++) {
                uint32_t hv[4];
#pragma unroll
                for (int jj = 0; jj < 2; jj++) {
                  const int jn = 16 + 2 * j2 + jj;
                  const float2 cs = lds64f_const(csv + jn * 32);
#pragma unroll
                  for (int hf = 0; hf < 2; hf++) {
                    const float nm = rc[hf].nmean;
                    const float t0 = fmaf(nm, cs.x, acc[0][4 * jn + 2 * hf]), t1 = fmaf(nm, cs.y, acc[0][4 * jn + 2 * hf + 1]);
                    hv[2 * jj + hf] = pack_bf16(t0 * gate_scale(t0, rc[hf]), t1 * gate_scale(t1, rc[hf]));
                  }
                }
                sts128(priv + pp * 8192 + j2 * 512, make_uint4(hv[0], hv[1], hv[2], hv[3]));
              }
            } else {
              uint4 park[4];
#pragma unroll
              for (int j2 = 0; j2 < 4; j2++) park[j2] = lds128(priv + pp * 8192 + j2 * 512);
              __syncwarp();
#pragma unroll
              for (int j2 = 0; j2 < 4; j2++) {
                const uint32_t pv[4] = {park[j2].x, park[j2].y, park[j2].z, park[j2].w};
                uint32_t hv[4];
#pragma unroll
                for (int jj = 0; jj < 2; jj++) {
                  const int jn = 16 + 2 * j2 + jj;
                  const float2 cs = lds64f_const(csv + jn * 32);
#pragma unroll
                  for (int hf = 0; hf < 2; hf++) {
                    const float nm = rc[hf].nmean;
                    const float t0 = fmaf(nm, cs.x, acc[0][4 * jn + 2 * hf]), t1 = fmaf(nm, cs.y, acc[0][4 * jn + 2 * hf + 1]);
                    asm("mul.rn.bf16x2 %0, %1, %2;" : "=r"(hv[2 * jj + hf]) : "r"(pack_bf16(t0, t1)), "r"(pv[2 * jj + hf]));
                  }
                }
                stsm4(frag + pp * 8192 + ((frag_x ^ (j2 * 2)) << 4), hv[0], hv[1], hv[2], hv[3]);
              }
            }
            if (pp == 1) break;
#pragma unroll
            for (int i = 64; i < 96; i++) NEXT(i);
          }
          if (pp == 1) break;
#pragma unroll
          for (int i = 0; i < 64; i++) NEXT(i);
        }
      }
      const int t3 = fresh_tid() & 127;
      uint4* part = SC_AT(part, bid * 1024 + (t3 & 96) * 8 + (t3 & 31));
      if (task == 2 && wg) {
#pragma unroll
        for (int k = 0; k < 8; k++) st_b128(part + k * 32, kPoison, kPoison, kPoison, kPoison);
      }
      fence_async_smem();
      nb_arrive(kNbPub + wg, 160);
      if (t == 0) TS(task == 4 ? 57 : 56 + task + wg * 2);
      if (task == 4) {
        mbar_wait(sb + kBars + 8 * kPartBar, 0);
#pragma unroll 1
        for (int b = 1, spins = 0; b >= 0;) {
          uint4 v[4];
          uint32_t top = 0;
#pragma unroll
          for (int k = 0; k < 4; k++) {
            v[k] = ld_b128(part + (128 + k * 32));
            top = max(max(top, v[k].x), max(v[k].y, max(v[k].z, v[k].w)));
          }
          if (__any_sync(~0u, top == kPoison)) {
            if (++spins > 100000) __trap();
            __nanosleep(kPartNs);
            continue;
          }
#pragma unroll
          for (int k = 0; k < 4; k++) {
            uint32_t h[4];
            ldsm4(frag + 16384 + b * 8192 + ((frag_x ^ (k * 2)) << 4), h);
            asm("add.rn.bf16x2 %0, %0, %1;" : "+r"(v[k].x) : "r"(h[0]));
            asm("add.rn.bf16x2 %0, %0, %1;" : "+r"(v[k].y) : "r"(h[1]));
            asm("add.rn.bf16x2 %0, %0, %1;" : "+r"(v[k].z) : "r"(h[2]));
            asm("add.rn.bf16x2 %0, %0, %1;" : "+r"(v[k].w) : "r"(h[3]));
            sts128(stg + (t3 & 96) * 128 + (t3 & 31) * 16 + b * 2048 + k * 512, v[k]);
          }
          b--;
          part -= 128;
        }
        if (t == 0) TSK(56);
        nb_arrive(kNbPart, 256);
        break;
      }
      sx = mx = 0.f;
    }
  }
}

typedef CUresult (*EncodeTiledFn)(CUtensorMap*, CUtensorMapDataType, cuuint32_t, void*, const cuuint64_t*, const cuuint64_t*,
                                  const cuuint32_t*, const cuuint32_t*, CUtensorMapInterleave, CUtensorMapSwizzle,
                                  CUtensorMapL2promotion, CUtensorMapFloatOOBfill);

void encode(EncodeTiledFn fn, CUtensorMap* m, const void* base, int rank, cuuint64_t d0, cuuint64_t d1, cuuint64_t d2,
            cuuint64_t s1, cuuint64_t s2, cuuint32_t b2, cuuint32_t b1 = 64) {
  const cuuint64_t dims[3] = {d0, d1, d2}, strides[2] = {s1, s2};
  const cuuint32_t box[3] = {64, b1, b2}, es[3] = {1, 1, 1};
  fn(m, CU_TENSOR_MAP_DATA_TYPE_BFLOAT16, rank, const_cast<void*>(base), dims, strides, box, es, CU_TENSOR_MAP_INTERLEAVE_NONE,
     CU_TENSOR_MAP_SWIZZLE_128B, CU_TENSOR_MAP_L2_PROMOTION_L2_128B, CU_TENSOR_MAP_FLOAT_OOB_FILL_NONE);
}

}

extern "C" void kernel_launch(void* const* d_in, const int* in_sizes, int n_in, void* d_out, int out_size) {
  void* fnp = nullptr;
  cudaDriverEntryPointQueryResult qr;
  cudaGetDriverEntryPoint("cuTensorMapEncodeTiled", &fnp, cudaEnableDefault, &qr);
  EncodeTiledFn fn = (EncodeTiledFn)fnp;
  void *o, *h, *hh;
  cudaGetSymbolAddress(&o, g_o);
  cudaGetSymbolAddress(&h, g_h);
  cudaGetSymbolAddress(&hh, g_hh);

  Params p;
  Scratch* sc;
  cudaGetSymbolAddress((void**)&sc, g_scratch);
  encode(fn, &p.x, d_in[0], 3, kD, kS / 2, 2, 4 * kD, 2 * kD, 1, 128);
  encode(fn, &p.out, d_out, 3, kD, kS / 2, 2, 4 * kD, 2 * kD, 1, 16);
  encode(fn, &p.wqkv, d_in[1], 2, 3 * kD, kD, 1, 6 * kD, 0, 1);
  encode(fn, &p.wo, d_in[2], 2, kD, kD, 1, 2 * kD, 0, 1);
  encode(fn, &p.wd, d_in[6], 2, kD, kF, 1, 2 * kD, 0, 1);
  encode(fn, &p.wg, d_in[4], 2, kF, kD, 1, 2 * kF, 0, 1);
  encode(fn, &p.wu, d_in[5], 2, kF, kD, 1, 2 * kF, 0, 1);
  encode(fn, &p.o, o, 2, kD, kS, 1, 2 * kD, 0, 1, 128);
  encode(fn, &p.h, h, 2, kD, kS, 1, 2 * kD, 0, 1, 128);
  encode(fn, &p.hh, hh, 2, kF, kS, 1, 2 * kF, 0, 1, 128);
  encode(fn, &p.ost, o, 2, kD, kS, 1, 2 * kD, 0, 1);
  encode(fn, &p.o16, o, 2, kD, kS, 1, 2 * kD, 0, 1, 16);
  encode(fn, &p.h16, h, 2, kD, kS, 1, 2 * kD, 0, 1, 16);
  encode(fn, &p.hst, h, 2, kD, kS, 1, 2 * kD, 0, 1);
  encode(fn, &p.hhst, hh, 2, kF, kS, 1, 2 * kF, 0, 1);
  for (int c = 0; c < 8; c++) {
    for (int j = 0; j < 32; j++) p.g1[c][j] = g1_block(j, c) | (j >= 16 && (j < 20 || g1_block(j, c) >> 1 == c) ? kInPlace : 0);
    for (int j = 0; j < 16; j++) p.g2[c][j] = g2_block(j, c);
    for (int j = 0; j < 64; j++)
      p.g3[c][j] = g3_block(j, c) | ((0x000F000F003C000Full >> j & 1) && j != 28 + c ? kInPlace : 0) | g3_tile(j) << 5;
  }
  for (int i = 0; i < 56; i++)
    p.g4[i] = g4_block(i) | (i >= kFirstShared && i % 3 == 0 && i < kFirstShared + 3 * kMost ? kShared : 0) | (i % 24 == 0 ? kNextWave : 0);
  p.wop = (const uint4*)d_in[2];
  p.wgp = (const uint4*)d_in[4];
  p.wup = (const uint4*)d_in[5];

  int dev = 0, sms = 0;
  cudaGetDevice(&dev);
  cudaDeviceGetAttribute(&sms, cudaDevAttrMultiProcessorCount, dev);
  auto* kernel = sms == 132 ? fused_block_kernel<true> : fused_block_kernel<false>;
  cudaFuncSetAttribute(kernel, cudaFuncAttributeMaxDynamicSharedMemorySize, kSmemBytes);
  kernel<<<132, kThreads, kSmemBytes, cudaStreamPerThread>>>(sc, (const __nv_bfloat16*)d_in[0], (const __nv_bfloat16*)d_in[1],
                                                                  (__nv_bfloat16*)d_out, p);
}
```

```cpp
#include <cuda_runtime.h>
#include <cuda_bf16.h>
#include <cuda.h>
#include <stddef.h>
#include <stdint.h>

namespace {

constexpr int kS = 2048, kD = 1024, kF = 3584;
constexpr int kThreads = 384;

constexpr int kRing = 0;
constexpr int kStage = 163840;
constexpr int kAug = kStage + 16384;
constexpr int kOwn = kStage + 32768;
constexpr int kFill = kStage + 24576;
constexpr int kCs = kStage + 65536;
constexpr int kStat = kCs + 1536;
constexpr int kBars = kStat + 1024;
constexpr int kSmemBytes = kBars + 512;
constexpr int kResBar = 38;
constexpr int kAuxBar = 39;
constexpr int kStgBar = 41;
constexpr int kResFreeBar = 43;
constexpr int kStatBar = 44;
constexpr int kPartBar = 45;
constexpr int kWaveBar = 46;
constexpr int kHalfBar = 49;
constexpr int kSentBar = 51;
constexpr int kLandBar = 52;
constexpr int kNumBars = 58;
static_assert(kNumBars == 4 + 3 * 18, "barrier initialisation is split 4 + 3 x 18");
__host__ __device__ constexpr int bar_count(int i) {
  const int ph = i < 8 ? 0 : i < 18 ? 1 : i < 26 ? 2 : 3, base = ph * 9 - (ph & 1);
  return i < 38 ? (i - base < 4 + (ph & 1) + (ph == 3) ? 2 : ph == 0 ? 16 : 8) : i == kResFreeBar || i == kStatBar || (i >= kHalfBar && i < kLandBar) ? 4 : 1;
}
__host__ __device__ constexpr uint64_t bar_shifts(int first) {
  uint64_t m = 0;
  for (int i = 17; i >= 0; i--) {
    const int n = bar_count(first + i);
    m = m << 3 | (n == 16 ? 4 : n == 8 ? 3 : n >> 1);
  }
  return m;
}
constexpr int kScale = kBars + 464;
constexpr int kPlan = kBars + 472;
constexpr int kOnes = kBars + 480;
constexpr int kZero = kBars + 496;
constexpr int kRole = kBars + 508;
constexpr int kEpoch = kBars + 500;
__device__ __forceinline__ int ring_base(int ph) { return ph * 9 - (ph & 1); }
constexpr int kWide = 25;
constexpr int kFirstShared = 15;
constexpr int kNbOrder = 1;
constexpr int kNbWg = 3;
constexpr int kNbPub = 5;
constexpr int kNbWin = 7;
constexpr int kNbSelf = 13;
constexpr int kNbPart = 11;
constexpr int kNbHalo = 9;

constexpr int kFlO = 0;
constexpr int kFlPace = 1;
constexpr int kFlHH = 3;
constexpr int kFlRow = 32;
constexpr int kNumFlags = 16 * kFlRow;

constexpr int kPauseG1 = 7;
constexpr int kPauseG2 = 1;
constexpr int kAhead = 2;
constexpr int kTail = 4;
constexpr int kShare = 5;
constexpr int kPartAt = 2;
constexpr int kMost = 8;
constexpr int kBudget = 328;
constexpr int kRemain = 65500;
constexpr int kStepNs = 167;
constexpr int kDone = 3;
constexpr int kQuietAt = 48;
constexpr int kPfStep = 8;
constexpr int kBackoffNs = 200;
constexpr int kPaceNs = 300;
constexpr int kPartNs = 500;
constexpr int kFillNs = 500;
constexpr int kHaloNs = 150;
constexpr int kGateONs = 150;
constexpr int kGateHNs = 150;
constexpr int kHoldNs = 1200;
constexpr float kBias1 = 512.f, kBias3 = 32768.f;
constexpr int kSplit = 13;
constexpr int kSampleNs = 1000;
constexpr int kStatNs = 1500;

struct Scratch {
  uint32_t flags[kNumFlags];
  uint32_t epoch[32];
  uint4 stat1[kS];
  uint4 stat2[8 * kS];
  uint4 cs[7 * 8 * 96];
  uint2 finish[128];
  uint2 plan[16];
  uint4 halo[2 * 16 * 8 * 6 * 32];
  uint4 part[128 * 8 * 128];
};
struct Params {
  CUtensorMap x, wqkv, o, wo, h, wg, wu, hh, wd, out;
  CUtensorMap ost, hst, hhst;
  CUtensorMap o16, h16;
  const uint4 *wop, *wgp, *wup;
  uint8_t g1[8][32], g2[8][16], g3[8][64], g4[56];
};

__device__ __align__(256) __nv_bfloat16 g_o[kS * kD];
__device__ __align__(256) __nv_bfloat16 g_h[kS * kD];
__device__ __align__(256) __nv_bfloat16 g_hh[kS * kF];
__device__ __align__(256) Scratch g_scratch;

template <bool BY_SM>
__device__ __forceinline__ int role_id() {
  uint32_t sm;
  asm("mov.u32 %0, %%smid;" : "=r"(sm));
  const int tpc = (BY_SM ? sm : blockIdx.x) >> 1, rank = blockIdx.x & 1;
  if ((tpc | 1) == 61) return 8 + 2 * tpc + rank;
  const int u = tpc - 32, s7 = (u * 37) >> 8;
  const int g = tpc < 32 ? tpc & 7 : tpc < 60 ? 1 + u - 7 * s7 : 0, s = tpc < 32 ? tpc >> 3 : tpc < 60 ? 4 + s7 : tpc - 58;
  return (g * 2 + rank) * 8 + s;
}
#define TS(i) do { } while (0)
#define TSK(i) do { } while (0)
#define TSS(i) do { } while (0)
#define TST(i)
#define TSG(i)

__device__ __forceinline__ uint32_t smem_u32(const void* p) { return (uint32_t)__cvta_generic_to_shared(p); }
template <class T>
__device__ __forceinline__ T* plus(T* p, uint32_t n) {
  uint64_t r;
  asm("{\n.reg .b32 lo, hi;\nmov.b64 {lo, hi}, %1;\nadd.cc.u32 lo, lo, %2;\naddc.u32 hi, hi, 0;\nmov.b64 %0, {lo, hi};\n}\n"
      : "=l"(r) : "l"(p), "r"(n * (uint32_t)sizeof(T)));
  return (T*)r;
}
#define SC_AT(member, n) ((decltype(+sc->member))((char*)plus((decltype(+sc->member))sc, n) + offsetof(Scratch, member)))
__device__ __forceinline__ void mbar_init(uint32_t bar, uint32_t cnt) {
  asm volatile("mbarrier.init.shared::cta.b64 [%0], %1;" ::"r"(bar), "r"(cnt));
}
__device__ __forceinline__ void mbar_expect_tx(uint32_t bar, uint32_t bytes) {
  asm volatile("mbarrier.arrive.expect_tx.shared::cta.b64 _, [%0], %1;" ::"r"(bar), "r"(bytes) : "memory");
}
__device__ __forceinline__ uint32_t map_cta(uint32_t addr, uint32_t cta) {
  uint32_t r;
  asm("mapa.shared::cluster.u32 %0, %1, %2;" : "=r"(r) : "r"(addr), "r"(cta));
  return r;
}
__device__ __forceinline__ void mbar_arrive_cluster_if(uint32_t bar, bool cond) {
  asm volatile("{\n.reg .pred p;\nsetp.ne.u32 p, %1, 0;\n@p mbarrier.arrive.shared::cluster.b64 _, [%0];\n}\n"
               ::"r"(bar), "r"((uint32_t)cond) : "memory");
}
__device__ __forceinline__ void mbar_wait(uint32_t bar, uint32_t parity) {
  asm volatile("{\n.reg .pred p;\nLAB_WAIT:\nmbarrier.try_wait.parity.shared::cta.b64 p, [%0], %1;\n@!p bra LAB_WAIT;\n}\n"
               ::"r"(bar), "r"(parity) : "memory");
  return;
  asm volatile("{\n.reg .pred p;\n.reg .u32 c;\nmov.u32 c, 0;\n"
               "LAB_WAIT:\nmbarrier.try_wait.parity.shared::cta.b64 p, [%0], %1;\n@p bra LAB_DONE;\n"
               "add.u32 c, c, 1;\nsetp.lt.u32 p, c, 2000000;\n@p bra LAB_WAIT;\ntrap;\nLAB_DONE:\n}\n"
               ::"r"(bar), "r"(parity) : "memory");
}
__device__ __forceinline__ void mbar_arrive(uint32_t bar) {
  asm volatile("mbarrier.arrive.shared::cta.b64 _, [%0];" ::"r"(bar) : "memory");
}
__device__ __forceinline__ void flag_signal(uint32_t* flag) {
  asm volatile("red.release.gpu.global.add.u32 [%0], 1;" ::"l"(flag) : "memory");
}
__device__ __forceinline__ void st_b128(uint4* p, uint32_t a, uint32_t b, uint32_t c, uint32_t d) {
  asm volatile("{\n.reg .b128 t;\n.reg .b64 lo, hi;\nmov.b64 lo, {%1,%2};\nmov.b64 hi, {%3,%4};\nmov.b128 t, {lo, hi};\n"
               "st.relaxed.gpu.global.b128 [%0], t;\n}\n" ::"l"(p), "r"(a), "r"(b), "r"(c), "r"(d) : "memory");
}
__device__ __forceinline__ uint4 ld_b128(const uint4* p) {
  uint4 v;
  asm volatile("{\n.reg .b128 t;\n.reg .b64 lo, hi;\nld.relaxed.gpu.global.b128 t, [%4];\nmov.b128 {lo, hi}, t;\n"
               "mov.b64 {%0,%1}, lo;\nmov.b64 {%2,%3}, hi;\n}\n" : "=r"(v.x), "=r"(v.y), "=r"(v.z), "=r"(v.w) : "l"(p) : "memory");
  return v;
}
__device__ __forceinline__ uint32_t ld_epoch(Scratch* sc) {
  uint32_t v;
  asm volatile("ld.relaxed.gpu.global.u32 %0, [%1];" : "=r"(v) : "l"(sc->epoch) : "memory");
  return v + 1;
}
__device__ __forceinline__ void flag_wait(uint32_t* flag, uint32_t target) {
  asm volatile("{\n.reg .pred p;\n.reg .u32 c, v;\nmov.u32 c, 0;\n"
               "LAB_WAIT:\nld.relaxed.gpu.global.u32 v, [%0];\nsub.u32 v, v, %1;\nsetp.ge.s32 p, v, 0;\n@p bra LAB_DONE;\n"
               "add.u32 c, c, 1;\nsetp.lt.u32 p, c, 4000000;\n@p bra LAB_WAIT;\ntrap;\nLAB_DONE:\n}\n"
               ::"l"(flag), "r"(target) : "memory");
}
__device__ __forceinline__ void send_word(uint2* p, uint32_t v, uint32_t tag) {
  asm volatile("{\n.reg .b64 t;\nmov.b64 t, {%1, %2};\nst.relaxed.gpu.global.b64 [%0], t;\n}\n" ::"l"(p), "r"(v), "r"(tag) : "memory");
}
__device__ __forceinline__ uint32_t await_word(const uint2* p, uint32_t tag) {
  uint32_t v;
  asm volatile("{\n.reg .pred p;\n.reg .u32 c, g;\n.reg .b64 t;\nmov.u32 c, 0;\n"
               "LAB_WAIT:\nld.relaxed.gpu.global.b64 t, [%1];\nmov.b64 {%0, g}, t;\nsetp.eq.u32 p, g, %2;\n@p bra LAB_DONE;\n"
               "add.u32 c, c, 1;\nsetp.lt.u32 p, c, 4000000;\n@p bra LAB_WAIT;\ntrap;\nLAB_DONE:\n}\n"
               : "=r"(v) : "l"(p), "r"(tag) : "memory");
  return v;
}
__device__ __forceinline__ uint32_t global_ns() {
  uint32_t v;
  asm volatile("mov.u32 %0, %%globaltimer_lo;" : "=r"(v));
  return v;
}
__device__ __forceinline__ int fresh_tid() {
  int v;
  asm volatile("mov.u32 %0, %%tid.x;" : "=r"(v));
  return v;
}
constexpr uint32_t kPoison = 0xFFFFFFFFu;
__device__ __forceinline__ bool elect_one() {
  uint32_t p;
  asm volatile("{\n.reg .pred P;\nelect.sync _|P, 0xffffffff;\nselp.u32 %0, 1, 0, P;\n}\n" : "=r"(p));
  return p != 0;
}
__device__ __forceinline__ void fence_async() { asm volatile("fence.acquire.gpu;\nfence.proxy.async.global;" ::: "memory"); }
__device__ __forceinline__ void fence_async_smem() { asm volatile("fence.proxy.async.shared::cta;" ::: "memory"); }
__device__ __forceinline__ void nb_sync(int id, int n) { asm volatile("bar.sync %0, %1;" ::"r"(id), "r"(n) : "memory"); }
__device__ __forceinline__ void nb_arrive(int id, int n) { asm volatile("bar.arrive %0, %1;" ::"r"(id), "r"(n) : "memory"); }

__device__ __forceinline__ void tma2d(uint32_t dst, const CUtensorMap* m, int c0, int c1, uint32_t bar) {
  asm volatile("cp.async.bulk.tensor.2d.shared::cluster.global.mbarrier::complete_tx::bytes [%0], [%1, {%3, %4}], [%2];"
               ::"r"(dst), "l"(m), "r"(bar), "r"(c0), "r"(c1) : "memory");
}
__device__ __forceinline__ void tma2d_mc(uint32_t dst, const CUtensorMap* m, int c0, int c1, uint32_t bar) {
  asm volatile("cp.async.bulk.tensor.2d.shared::cluster.global.mbarrier::complete_tx::bytes.multicast::cluster"
               " [%0], [%1, {%3, %4}], [%2], %5;"
               ::"r"(dst), "l"(m), "r"(bar), "r"(c0), "r"(c1), "h"((uint16_t)3) : "memory");
}
__device__ __forceinline__ void tma3d(uint32_t dst, const CUtensorMap* m, int c0, int c1, int c2, uint32_t bar) {
  asm volatile("cp.async.bulk.tensor.3d.shared::cluster.global.mbarrier::complete_tx::bytes [%0], [%1, {%3, %4, %5}], [%2];"
               ::"r"(dst), "l"(m), "r"(bar), "r"(c0), "r"(c1), "r"(c2) : "memory");
}
__device__ __forceinline__ void tma_store2d(const CUtensorMap* m, uint32_t src, int c0, int c1) {
  asm volatile("cp.async.bulk.tensor.2d.global.shared::cta.bulk_group [%0, {%2, %3}], [%1];"
               ::"l"(m), "r"(src), "r"(c0), "r"(c1) : "memory");
}
__device__ __forceinline__ void tma_store3d(const CUtensorMap* m, uint32_t src, int c0, int c1, int c2) {
  asm volatile("cp.async.bulk.tensor.3d.global.shared::cta.bulk_group [%0, {%2, %3, %4}], [%1];"
               ::"l"(m), "r"(src), "r"(c0), "r"(c1), "r"(c2) : "memory");
}
__device__ __forceinline__ void tma_prefetch2d(const CUtensorMap* m, int c0, int c1) {
  asm volatile("cp.async.bulk.prefetch.tensor.2d.L2.global [%0, {%1, %2}];" ::"l"(m), "r"(c0), "r"(c1) : "memory");
}
__device__ __forceinline__ void prefetch_map(const CUtensorMap* m) { asm volatile("prefetch.tensormap [%0];" ::"l"(m) : "memory"); }
__device__ __forceinline__ void bulk_commit() { asm volatile("cp.async.bulk.commit_group;" ::: "memory"); }
__device__ __forceinline__ void bulk_wait_all() { asm volatile("cp.async.bulk.wait_group 0;" ::: "memory"); }
__device__ __forceinline__ void bulk_wait_read() { asm volatile("cp.async.bulk.wait_group.read 0;" ::: "memory"); }
__device__ __forceinline__ void prefetch_l2(const void* p) { asm volatile("prefetch.global.L2 [%0];" ::"l"(p)); }
__device__ __forceinline__ void cluster_arrive() { asm volatile("barrier.cluster.arrive.relaxed.aligned;" ::: "memory"); }
__device__ __forceinline__ void cluster_wait() { asm volatile("barrier.cluster.wait.aligned;" ::: "memory"); }

__device__ __forceinline__ void wg_fence() { asm volatile("wgmma.fence.sync.aligned;" ::: "memory"); }
__device__ __forceinline__ void wg_commit() { asm volatile("wgmma.commit_group.sync.aligned;" ::: "memory"); }
template <int N> __device__ __forceinline__ void wg_wait() { asm volatile("wgmma.wait_group.sync.aligned %0;" ::"n"(N) : "memory"); }
__device__ __forceinline__ uint32_t desc_lo(uint32_t addr, uint32_t lbo) { return ((addr & 0x3FFFF) >> 4) | ((lbo >> 4) << 16); }
__device__ __forceinline__ uint64_t desc(uint32_t lo) { return (uint64_t)lo | (0x40000040ull << 32); }
__device__ __forceinline__ uint64_t desc_kept(uint32_t lo, uint32_t sb) { return (uint64_t)lo | (uint64_t)(0x40000040u | sb >> 31) << 32; }
constexpr int kToB = (16384 >> 4) + ((8192 - 16) >> 4 << 16);

__device__ __forceinline__ void wgmma_n128(float (&d)[96], uint64_t da, uint64_t db, int add = 1) {
  asm volatile(
      "{\n.reg .pred p;\nsetp.ne.b32 p, %66, 0;\n"
      "wgmma.mma_async.sync.aligned.m64n128k16.f32.bf16.bf16 {"
      "%0, %1, %2, %3, %4, %5, %6, %7, %8, %9, %10, %11, %12, %13, %14, %15, "
      "%16, %17, %18, %19, %20, %21, %22, %23, %24, %25, %26, %27, %28, %29, %30, %31, "
      "%32, %33, %34, %35, %36, %37, %38, %39, %40, %41, %42, %43, %44, %45, %46, %47, "
      "%48, %49, %50, %51, %52, %53, %54, %55, %56, %57, %58, %59, %60, %61, %62, %63}, "
      "%64, %65, p, 1, 1, 0, 1;\n}\n"
      :
        "+f"(d[0]), "+f"(d[1]), "+f"(d[2]), "+f"(d[3]), "+f"(d[4]), "+f"(d[5]), "+f"(d[6]), "+f"(d[7]),
        "+f"(d[8]), "+f"(d[9]), "+f"(d[10]), "+f"(d[11]), "+f"(d[12]), "+f"(d[13]), "+f"(d[14]), "+f"(d[15]),
        "+f"(d[16]), "+f"(d[17]), "+f"(d[18]), "+f"(d[19]), "+f"(d[20]), "+f"(d[21]), "+f"(d[22]), "+f"(d[23]),
        "+f"(d[24]), "+f"(d[25]), "+f"(d[26]), "+f"(d[27]), "+f"(d[28]), "+f"(d[29]), "+f"(d[30]), "+f"(d[31]),
        "+f"(d[32]), "+f"(d[33]), "+f"(d[34]), "+f"(d[35]), "+f"(d[36]), "+f"(d[37]), "+f"(d[38]), "+f"(d[39]),
        "+f"(d[40]), "+f"(d[41]), "+f"(d[42]), "+f"(d[43]), "+f"(d[44]), "+f"(d[45]), "+f"(d[46]), "+f"(d[47]),
        "+f"(d[48]), "+f"(d[49]), "+f"(d[50]), "+f"(d[51]), "+f"(d[52]), "+f"(d[53]), "+f"(d[54]), "+f"(d[55]),
        "+f"(d[56]), "+f"(d[57]), "+f"(d[58]), "+f"(d[59]), "+f"(d[60]), "+f"(d[61]), "+f"(d[62]), "+f"(d[63])
      : "l"(da), "l"(db), "r"(add));
}

__device__ __forceinline__ void wgmma_n192(float (&d)[96], uint64_t da, uint64_t db, int add = 1) {
  asm volatile(
      "{\n.reg .pred p;\nsetp.ne.b32 p, %98, 0;\n"
      "wgmma.mma_async.sync.aligned.m64n192k16.f32.bf16.bf16 {"
      "%0, %1, %2, %3, %4, %5, %6, %7, %8, %9, %10, %11, %12, %13, %14, %15, "
      "%16, %17, %18, %19, %20, %21, %22, %23, %24, %25, %26, %27, %28, %29, %30, %31, "
      "%32, %33, %34, %35, %36, %37, %38, %39, %40, %41, %42, %43, %44, %45, %46, %47, "
      "%48, %49, %50, %51, %52, %53, %54, %55, %56, %57, %58, %59, %60, %61, %62, %63, "
      "%64, %65, %66, %67, %68, %69, %70, %71, %72, %73, %74, %75, %76, %77, %78, %79, "
      "%80, %81, %82, %83, %84, %85, %86, %87, %88, %89, %90, %91, %92, %93, %94, %95}, "
      "%96, %97, p, 1, 1, 0, 1;\n}\n"
      :
        "+f"(d[0]), "+f"(d[1]), "+f"(d[2]), "+f"(d[3]), "+f"(d[4]), "+f"(d[5]), "+f"(d[6]), "+f"(d[7]),
        "+f"(d[8]), "+f"(d[9]), "+f"(d[10]), "+f"(d[11]), "+f"(d[12]), "+f"(d[13]), "+f"(d[14]), "+f"(d[15]),
        "+f"(d[16]), "+f"(d[17]), "+f"(d[18]), "+f"(d[19]), "+f"(d[20]), "+f"(d[21]), "+f"(d[22]), "+f"(d[23]),
        "+f"(d[24]), "+f"(d[25]), "+f"(d[26]), "+f"(d[27]), "+f"(d[28]), "+f"(d[29]), "+f"(d[30]), "+f"(d[31]),
        "+f"(d[32]), "+f"(d[33]), "+f"(d[34]), "+f"(d[35]), "+f"(d[36]), "+f"(d[37]), "+f"(d[38]), "+f"(d[39]),
        "+f"(d[40]), "+f"(d[41]), "+f"(d[42]), "+f"(d[43]), "+f"(d[44]), "+f"(d[45]), "+f"(d[46]), "+f"(d[47]),
        "+f"(d[48]), "+f"(d[49]), "+f"(d[50]), "+f"(d[51]), "+f"(d[52]), "+f"(d[53]), "+f"(d[54]), "+f"(d[55]),
        "+f"(d[56]), "+f"(d[57]), "+f"(d[58]), "+f"(d[59]), "+f"(d[60]), "+f"(d[61]), "+f"(d[62]), "+f"(d[63]),
        "+f"(d[64]), "+f"(d[65]), "+f"(d[66]), "+f"(d[67]), "+f"(d[68]), "+f"(d[69]), "+f"(d[70]), "+f"(d[71]),
        "+f"(d[72]), "+f"(d[73]), "+f"(d[74]), "+f"(d[75]), "+f"(d[76]), "+f"(d[77]), "+f"(d[78]), "+f"(d[79]),
        "+f"(d[80]), "+f"(d[81]), "+f"(d[82]), "+f"(d[83]), "+f"(d[84]), "+f"(d[85]), "+f"(d[86]), "+f"(d[87]),
        "+f"(d[88]), "+f"(d[89]), "+f"(d[90]), "+f"(d[91]), "+f"(d[92]), "+f"(d[93]), "+f"(d[94]), "+f"(d[95])
      : "l"(da), "l"(db), "r"(add));
}

__device__ __forceinline__ void wgmma_n192_any(float (&d)[96], uint64_t da, uint64_t db) {
  asm volatile(
      "wgmma.mma_async.sync.aligned.m64n192k16.f32.bf16.bf16 {"
      "%0, %1, %2, %3, %4, %5, %6, %7, %8, %9, %10, %11, %12, %13, %14, %15, "
      "%16, %17, %18, %19, %20, %21, %22, %23, %24, %25, %26, %27, %28, %29, %30, %31, "
      "%32, %33, %34, %35, %36, %37, %38, %39, %40, %41, %42, %43, %44, %45, %46, %47, "
      "%48, %49, %50, %51, %52, %53, %54, %55, %56, %57, %58, %59, %60, %61, %62, %63, "
      "%64, %65, %66, %67, %68, %69, %70, %71, %72, %73, %74, %75, %76, %77, %78, %79, "
      "%80, %81, %82, %83, %84, %85, %86, %87, %88, %89, %90, %91, %92, %93, %94, %95}, "
      "%96, %97, 0, 1, 1, 0, 1;\n"
      :
        "=f"(d[0]), "=f"(d[1]), "=f"(d[2]), "=f"(d[3]), "=f"(d[4]), "=f"(d[5]), "=f"(d[6]), "=f"(d[7]),
        "=f"(d[8]), "=f"(d[9]), "=f"(d[10]), "=f"(d[11]), "=f"(d[12]), "=f"(d[13]), "=f"(d[14]), "=f"(d[15]),
        "=f"(d[16]), "=f"(d[17]), "=f"(d[18]), "=f"(d[19]), "=f"(d[20]), "=f"(d[21]), "=f"(d[22]), "=f"(d[23]),
        "=f"(d[24]), "=f"(d[25]), "=f"(d[26]), "=f"(d[27]), "=f"(d[28]), "=f"(d[29]), "=f"(d[30]), "=f"(d[31]),
        "=f"(d[32]), "=f"(d[33]), "=f"(d[34]), "=f"(d[35]), "=f"(d[36]), "=f"(d[37]), "=f"(d[38]), "=f"(d[39]),
        "=f"(d[40]), "=f"(d[41]), "=f"(d[42]), "=f"(d[43]), "=f"(d[44]), "=f"(d[45]), "=f"(d[46]), "=f"(d[47]),
        "=f"(d[48]), "=f"(d[49]), "=f"(d[50]), "=f"(d[51]), "=f"(d[52]), "=f"(d[53]), "=f"(d[54]), "=f"(d[55]),
        "=f"(d[56]), "=f"(d[57]), "=f"(d[58]), "=f"(d[59]), "=f"(d[60]), "=f"(d[61]), "=f"(d[62]), "=f"(d[63]),
        "=f"(d[64]), "=f"(d[65]), "=f"(d[66]), "=f"(d[67]), "=f"(d[68]), "=f"(d[69]), "=f"(d[70]), "=f"(d[71]),
        "=f"(d[72]), "=f"(d[73]), "=f"(d[74]), "=f"(d[75]), "=f"(d[76]), "=f"(d[77]), "=f"(d[78]), "=f"(d[79]),
        "=f"(d[80]), "=f"(d[81]), "=f"(d[82]), "=f"(d[83]), "=f"(d[84]), "=f"(d[85]), "=f"(d[86]), "=f"(d[87]),
        "=f"(d[88]), "=f"(d[89]), "=f"(d[90]), "=f"(d[91]), "=f"(d[92]), "=f"(d[93]), "=f"(d[94]), "=f"(d[95])
      : "l"(da), "l"(db));
}

__device__ __forceinline__ void wgmma_n192_rs(float (&d)[96], uint32_t a0, uint32_t a1, uint32_t a23, uint64_t db) {
  asm volatile(
      "wgmma.mma_async.sync.aligned.m64n192k16.f32.bf16.bf16 {"
      "%0, %1, %2, %3, %4, %5, %6, %7, %8, %9, %10, %11, %12, %13, %14, %15, "
      "%16, %17, %18, %19, %20, %21, %22, %23, %24, %25, %26, %27, %28, %29, %30, %31, "
      "%32, %33, %34, %35, %36, %37, %38, %39, %40, %41, %42, %43, %44, %45, %46, %47, "
      "%48, %49, %50, %51, %52, %53, %54, %55, %56, %57, %58, %59, %60, %61, %62, %63, "
      "%64, %65, %66, %67, %68, %69, %70, %71, %72, %73, %74, %75, %76, %77, %78, %79, "
      "%80, %81, %82, %83, %84, %85, %86, %87, %88, %89, %90, %91, %92, %93, %94, %95}, "
      "{%96, %97, %98, %98}, %99, 1, 1, 1, 1;\n"
      :
        "+f"(d[0]), "+f"(d[1]), "+f"(d[2]), "+f"(d[3]), "+f"(d[4]), "+f"(d[5]), "+f"(d[6]), "+f"(d[7]),
        "+f"(d[8]), "+f"(d[9]), "+f"(d[10]), "+f"(d[11]), "+f"(d[12]), "+f"(d[13]), "+f"(d[14]), "+f"(d[15]),
        "+f"(d[16]), "+f"(d[17]), "+f"(d[18]), "+f"(d[19]), "+f"(d[20]), "+f"(d[21]), "+f"(d[22]), "+f"(d[23]),
        "+f"(d[24]), "+f"(d[25]), "+f"(d[26]), "+f"(d[27]), "+f"(d[28]), "+f"(d[29]), "+f"(d[30]), "+f"(d[31]),
        "+f"(d[32]), "+f"(d[33]), "+f"(d[34]), "+f"(d[35]), "+f"(d[36]), "+f"(d[37]), "+f"(d[38]), "+f"(d[39]),
        "+f"(d[40]), "+f"(d[41]), "+f"(d[42]), "+f"(d[43]), "+f"(d[44]), "+f"(d[45]), "+f"(d[46]), "+f"(d[47]),
        "+f"(d[48]), "+f"(d[49]), "+f"(d[50]), "+f"(d[51]), "+f"(d[52]), "+f"(d[53]), "+f"(d[54]), "+f"(d[55]),
        "+f"(d[56]), "+f"(d[57]), "+f"(d[58]), "+f"(d[59]), "+f"(d[60]), "+f"(d[61]), "+f"(d[62]), "+f"(d[63]),
        "+f"(d[64]), "+f"(d[65]), "+f"(d[66]), "+f"(d[67]), "+f"(d[68]), "+f"(d[69]), "+f"(d[70]), "+f"(d[71]),
        "+f"(d[72]), "+f"(d[73]), "+f"(d[74]), "+f"(d[75]), "+f"(d[76]), "+f"(d[77]), "+f"(d[78]), "+f"(d[79]),
        "+f"(d[80]), "+f"(d[81]), "+f"(d[82]), "+f"(d[83]), "+f"(d[84]), "+f"(d[85]), "+f"(d[86]), "+f"(d[87]),
        "+f"(d[88]), "+f"(d[89]), "+f"(d[90]), "+f"(d[91]), "+f"(d[92]), "+f"(d[93]), "+f"(d[94]), "+f"(d[95])
      : "r"(a0), "r"(a1), "r"(a23), "l"(db));
}

__device__ __forceinline__ uint32_t pack_bf16(float lo, float hi) {
  uint32_t r;
  asm("cvt.rn.bf16x2.f32 %0, %1, %2;" : "=r"(r) : "f"(hi), "f"(lo));
  return r;
}
__device__ __forceinline__ float bf_lo(uint32_t v) { return __uint_as_float(v << 16); }
__device__ __forceinline__ float bf_hi(uint32_t v) { return __uint_as_float(v & 0xFFFF0000u); }
__device__ __forceinline__ float ex2(float x) { float r; asm("ex2.approx.ftz.f32 %0, %1;" : "=f"(r) : "f"(x)); return r; }
__device__ __forceinline__ float rcp(float x) { float r; asm("rcp.approx.ftz.f32 %0, %1;" : "=f"(r) : "f"(x)); return r; }
__device__ __forceinline__ uint32_t movm(uint32_t a) {
  uint32_t d;
  asm volatile("movmatrix.sync.aligned.m8n8.trans.b16 %0, %1;" : "=r"(d) : "r"(a));
  return d;
}
__device__ __forceinline__ void mma16816(float (&c)[4], uint32_t a0, uint32_t a1, uint32_t a2, uint32_t a3, uint32_t b0, uint32_t b1) {
  asm volatile("mma.sync.aligned.m16n8k16.row.col.f32.bf16.bf16.f32 {%0,%1,%2,%3}, {%4,%5,%6,%7}, {%8,%9}, {%0,%1,%2,%3};"
               : "+f"(c[0]), "+f"(c[1]), "+f"(c[2]), "+f"(c[3]) : "r"(a0), "r"(a1), "r"(a2), "r"(a3), "r"(b0), "r"(b1));
}
__device__ __forceinline__ void mma1688(float (&c)[4], uint32_t a0, uint32_t a1, uint32_t b0) {
  asm volatile("mma.sync.aligned.m16n8k8.row.col.f32.bf16.bf16.f32 {%0,%1,%2,%3}, {%4,%5}, {%6}, {%0,%1,%2,%3};"
               : "+f"(c[0]), "+f"(c[1]), "+f"(c[2]), "+f"(c[3]) : "r"(a0), "r"(a1), "r"(b0));
}
__device__ __forceinline__ void stsm4(uint32_t addr, uint32_t a, uint32_t b, uint32_t c, uint32_t d) {
  asm volatile("stmatrix.sync.aligned.m8n8.x4.shared.b16 [%0], {%1,%2,%3,%4};" ::"r"(addr), "r"(a), "r"(b), "r"(c), "r"(d) : "memory");
}
__device__ __forceinline__ void stsm4_t(uint32_t addr, uint32_t a, uint32_t b, uint32_t c, uint32_t d) {
  asm volatile("stmatrix.sync.aligned.m8n8.x4.trans.shared.b16 [%0], {%1,%2,%3,%4};" ::"r"(addr), "r"(a), "r"(b), "r"(c), "r"(d) : "memory");
}
__device__ __forceinline__ void ldsm4(uint32_t addr, uint32_t (&v)[4]) {
  asm volatile("ldmatrix.sync.aligned.m8n8.x4.shared.b16 {%0,%1,%2,%3}, [%4];"
               : "=r"(v[0]), "=r"(v[1]), "=r"(v[2]), "=r"(v[3]) : "r"(addr) : "memory");
}
__device__ __forceinline__ void sts128(uint32_t addr, uint4 v) {
  asm volatile("st.shared.v4.b32 [%0], {%1,%2,%3,%4};" ::"r"(addr), "r"(v.x), "r"(v.y), "r"(v.z), "r"(v.w) : "memory");
}
__device__ __forceinline__ uint4 lds128(uint32_t addr) {
  uint4 v;
  asm volatile("ld.shared.v4.b32 {%0,%1,%2,%3}, [%4];" : "=r"(v.x), "=r"(v.y), "=r"(v.z), "=r"(v.w) : "r"(addr) : "memory");
  return v;
}
__device__ __forceinline__ void sts64(uint32_t addr, uint32_t a, uint32_t b) {
  asm volatile("st.shared.v2.b32 [%0], {%1,%2};" ::"r"(addr), "r"(a), "r"(b) : "memory");
}
__device__ __forceinline__ void sts32(uint32_t addr, uint32_t a) { asm volatile("st.shared.b32 [%0], %1;" ::"r"(addr), "r"(a) : "memory"); }
__device__ __forceinline__ uint32_t lds32(uint32_t addr) {
  uint32_t v;
  asm volatile("ld.shared.b32 %0, [%1];" : "=r"(v) : "r"(addr) : "memory");
  return v;
}
__device__ __forceinline__ float2 lds64f_const(uint32_t addr) {
  float2 v;
  asm("ld.shared.v2.f32 {%0,%1}, [%2];" : "=f"(v.x), "=f"(v.y) : "r"(addr));
  return v;
}
template <int N, bool PAIR>
__device__ __forceinline__ void load_tagged(uint3 (&out)[N], const uint4* src, int stride, uint32_t tag, const uint4* last = nullptr) {
  uint32_t bad;
  int spins = 0;
  do {
    if (spins != 0) __nanosleep(kBackoffNs);
    if (++spins > 2000000) __trap();
    bad = 0;
#pragma unroll
    for (int i = 0; i < N; i++) {
      const uint4 v = ld_b128(N == 5 && i == 4 ? last : src + i * stride);
      out[i] = make_uint3(v.x, v.y, v.z);
      bad |= (v.w ^ tag) | (PAIR ? v.z ^ tag : 0);
    }
  } while (N == 4 ? __any_sync(~0u, bad != 0) : bad != 0);
}
__device__ __forceinline__ void sts64f(uint32_t addr, float2 v) { sts64(addr, __float_as_uint(v.x), __float_as_uint(v.y)); }
__device__ __forceinline__ float bf_rest(float v) { return v - __uint_as_float(__float_as_uint(v) & 0xFFFF0000u); }
__device__ __forceinline__ uint32_t bf_upper(float lo, float hi) { return __byte_perm(__float_as_uint(lo), __float_as_uint(hi), 0x7632); }
__device__ __forceinline__ float low_peak(uint4 v) {
  asm("max.xorsign.abs.bf16x2 %0, %0, %1;" : "+r"(v.x) : "r"(v.y));
  asm("max.xorsign.abs.bf16x2 %0, %0, %1;" : "+r"(v.z) : "r"(v.w));
  asm("max.xorsign.abs.bf16x2 %0, %0, %1;" : "+r"(v.x) : "r"(v.z));
  asm("max.xorsign.abs.bf16x2 %0, %0, %1;" : "+r"(v.x) : "r"(v.x << 16));
  return __uint_as_float(__reduce_min_sync(~0u, v.x & 0x7FFF0000u));
}
__device__ __forceinline__ float bias_at(float v) { return __uint_as_float((__float_as_uint(fminf(v, 1e37f)) & 0x7F800000u) | 0x00400000u); }
struct RowConst {
  float nmean, k0, k1, half;
};
__device__ __forceinline__ float gate_scale(float t, const RowConst& k) {
  float th;
  asm("tanh.approx.f32 %0, %1;" : "=f"(th) : "f"(t * fmaf(t * t, k.k1, k.k0)));
  return fmaf(th, k.half, k.half);
}

template <int N>
__device__ __forceinline__ void mma_k16(float (&acc)[2][96], uint32_t a, uint32_t b, int kk, int add = 1) {
#pragma unroll
  for (int m = 0; m < 2; m++) {
    const uint64_t da = desc(a) + (m * 512 + kk * 2), db = desc(b) + kk * 128;
    if (N == 128) wgmma_n128(acc[m], da, db); else wgmma_n192(acc[m], da, db, add);
  }
}

__device__ __forceinline__ void stage_quarter(const float* acc, uint32_t frag, uint32_t frag_x, int b, const uint4* add = nullptr) {
#pragma unroll
  for (int j = 0; j < 4; j++) {
    const float* v = acc + 8 * j;
    uint32_t h[4] = {pack_bf16(v[0], v[1]), pack_bf16(v[2], v[3]), pack_bf16(v[4], v[5]), pack_bf16(v[6], v[7])};
    if (add) {
      const uint32_t a[4] = {add[j].x, add[j].y, add[j].z, add[j].w};
#pragma unroll
      for (int e = 0; e < 4; e++) asm("add.rn.bf16x2 %0, %0, %1;" : "+r"(h[e]) : "r"(a[e]));
    }
    stsm4(frag + b * 8192 + ((frag_x ^ (j * 2)) << 4), h[0], h[1], h[2], h[3]);
  }
}

inline int g1_block(int j, int c) { return j < 16 ? j : ((j + 12) & 15) ^ (c == 5 && j >= 28 ? 2 : 0); }
inline int g2_block(int j, int c) { return j < 8 ? j : j == 8 ? 8 + c : j - (j - 9 < c); }
inline int g3_tile(int j) { return j < 4 ? j >> 1 : j < 18 ? 0 : j >> 4; }
inline int g3_block(int j, int c) {
  const int i = j < 32 ? (j < 16 ? 0xDCBA976543218080ull : 0x7654321BA9FEDCFEull) >> 4 * (j & 15) : j + (~j >> 2 & 4), o = i & 7;
  return 2 * (j < 32 && (o == c || o == 0) ? c - o : o) + (i >> 3 & 1);
}
__device__ __forceinline__ bool g3_is_up(int tile, int a) { return a == 1 || (a == 2 && tile >= 2); }
__device__ __forceinline__ int g3_atom(int tile, int a, int c) { return c * 7 + (tile & 1) * 3 + (a == 2 ? 1 : tile == 4 ? 6 : tile & 2); }
inline int g4_block(int i) {
  const int n = i * 43 >> 7, j = i - 3 * n, m = j ? n : n + (16 - kFirstShared / 3);
  return i < 48 ? 7 * (m & 7) + 3 * (m >> 3 & 1) + j : 7 * i - 330;
}

constexpr int kInPlace = 16, kShared = 64, kNextWave = 128;

template <int N, int TAIL>
__device__ __forceinline__ void mainloop(Scratch* sc, float (&acc)[2][96], uint32_t sb, int ph, int j0, int nsteps, int pause_at, bool last,
                                         bool hand_over, bool local, int wg, int own = -1, const CUtensorMap* out = nullptr, int out_col = 0,
                                         int out_row = 0, int warp = 0, __nv_bfloat16* outp = nullptr) {
  constexpr int NSLOT = N == 128 ? 5 : 4, SLOT = N == 128 ? 32768 : 40960;
  const int lane = fresh_tid() & 31;
  const uint32_t full = sb + kBars + 8 * ring_base(ph);
  const uint32_t empty = map_cta(full + 8 * (NSLOT + (ph == 3)), lane & 1);
  const uint32_t ring = desc_lo(sb + kRing, 16);
  int bi = j0 % NSLOT, par = (j0 / NSLOT) & 1;
  const int release_end = lane < (N == 192 && !hand_over ? 4 : 2) ? (last ? nsteps - 1 - NSLOT : nsteps) : 0;
  uint32_t rel = empty;
  const uint32_t special = ph == 0 && wg == 0 ? 3 : pause_at < 0 ? 1 : 1 | 2 << pause_at;
  int i = 0;
#pragma unroll 1
  for (;;) {
  const int end = TAIL <= 0 ? nsteps : !own ? nsteps - TAIL - 1 : i ? i + 2 : kFirstShared;
#pragma unroll 1
  do {
    uint32_t a = ring + bi * (SLOT >> 4), b = a + kToB;
    if (TAIL > 0 ? i == 0 : special >> i & 1) {
      if (i == 0) nb_sync(kNbOrder + wg, ph == 0 && wg == 0 ? 160 : 256);
      else if (ph == 0 && wg == 0) cluster_wait();
      else if (ph < 2) nb_sync(kNbWin + 1, 256);
    }
    if (N == 192 && local) {
      a = ring + ((kStage + i * 16384) >> 4);
      b = ring + bi * (32768 >> 4) + desc_lo(32768, 8192) - desc_lo(0, 16);
    }
    if (ph == 0 && i >> 1 == own) a = ring + ((kOwn + (i & 1) * 16384) >> 4);
    if (ph == 1 && i == 8) a = ring + ((kStage + 32768) >> 4);
    mbar_wait(full + 8 * bi, par);
    if (N == 192 && local) mbar_wait(sb + kBars + 8 * (kHalfBar + i), 0);
    const bool release = (uint32_t)(i - 1) < (uint32_t)release_end;
    wg_fence();
    mma_k16<N>(acc, a, b, 0, ph == 0 ? i | wg : 1);
    mma_k16<N>(acc, a, b, 1);
    wg_commit();
    wg_wait<1>();
    mbar_arrive_cluster_if(rel, release);
    wg_fence();
    mma_k16<N>(acc, a, b, 2);
    mma_k16<N>(acc, a, b, 3);
    wg_commit();
    rel = empty + 8 * bi;
    if (++bi == NSLOT + (TAIL > 0 && i >= kWide - 16)) { bi = 0; par ^= 1; }
    if (ph < 2 && i == pause_at) nb_arrive(kNbWin, 256);
  } while (++i < end);
  if (TAIL <= 0 || own-- == 0) break;
  const uint32_t a = ring + bi * (SLOT >> 4);
  mbar_wait(full + 8 * bi, par);
  wg_fence();
#pragma unroll
  for (int k = 0; k < 4; k++) wgmma_n128(acc[1], desc(a) + (512 + k * 2), desc(a + kToB) + k * 128);
  wg_commit();
  wg_wait<1>();
  mbar_arrive_cluster_if(rel, lane < 2);
  rel = empty + 8 * bi;
  if (++bi == NSLOT + 1) { bi = 0; par ^= 1; }
  i++;
  }
  if (TAIL < 0) return;
  if (TAIL > 0) {
    uint32_t at[TAIL + 2];
    bi = par = 0;
    const int t = fresh_tid() & 127;
    uint32_t frag = sb + kStage + ((t >> 5) * 16 + (t & 15)) * 128, frag_x = ((t >> 4) & 1) ^ (t & 7);
    const uint32_t back = sb + kStage + (t >> 5) * 2048 + ((t >> 3) & 3) * 128, back_x = ((t ^ (t >> 3 & 3)) & 7) << 4;
    outp = plus(outp, (2 * (out_row + (t >> 5) * 16 + ((t >> 3) & 3)) + (blockIdx.x & 1)) * kD + out_col + (t & 7) * 8);
    auto rows = [&](int m, int i0, int i1) {
      wg_fence();
#pragma unroll
      for (int i = 4 * i0; i < 4 * i1; i++)
        wgmma_n128(acc[m], desc_kept(ring, sb) + (at[i >> 2] + m * 512 + (i & 3) * 2), desc_kept(ring, sb) + (at[i >> 2] + kToB + (i & 3) * 128));
      wg_commit();
    };
    auto last_rows = [&](int i0, int i1) { rows(1, i0, i1); };
    uint4 part[8];
#pragma unroll
    for (int i = 0; i <= TAIL; i++) {
      at[i] = bi * (SLOT >> 4);
      mbar_wait(full + 8 * bi, par);
      if (++bi == NSLOT) { bi = 0; par ^= 1; }
      rows(0, i, i + 1);
      if (i == kPartAt) nb_sync(kNbPart, 256);
      if (i == kPartAt || i == kPartAt + 1) {
#pragma unroll
        for (int k = 4 * (i - kPartAt); k < 4 * (i - kPartAt + 1); k++) part[k] = lds128(sb + kStage + 32768 + (t >> 5) * 4096 + (t & 31) * 16 + k * 512);
      }
    }
    last_rows(0, 2);
#pragma unroll
    for (int b = 0; b < 4; b++) {
      if (b == 0) wg_wait<1>();
      if (b == 1) last_rows(3, 4);
      if (b == 2) wg_wait<0>();
      if (!(b & 1)) {
#pragma unroll
        for (int i = 0; i < 64; i++) asm volatile("" : "+f"(acc[b >> 1][i])::"memory");
        if (t == 0) TSS(b);
      }
      stage_quarter(&acc[b >> 1][32 * (b & 1)], frag, frag_x, b, b < 2 ? &part[4 * b] : nullptr);
      if (b == 3) {
        __syncwarp();
        uint4 v[4];
#pragma unroll
        for (int i = 0; i < 4; i++) v[i] = lds128(back + b * 8192 + i * 512 + ((i & 1) ? back_x ^ 64 : back_x));
#pragma unroll
        for (int i = 0; i < 4; i++) __stcs((uint4*)(outp + ((b >> 1) * 128 + i * 8) * kD + (b & 1) * 64), v[i]);
        if (t == 0) TSS(4 + b);
        continue;
      }
      if (b < 2) last_rows(2 + 2 * b, 3 + 2 * b);
      fence_async_smem();
      __syncwarp();
      if (elect_one()) tma_store3d(out, sb + kStage + b * 8192 + warp * 2048, out_col + (b & 1) * 64, out_row + (b >> 1) * 64 + warp * 16, blockIdx.x & 1);
      __syncwarp();
      if (t == 0) TSS(4 + b);
    }
    if (elect_one()) {
      bulk_commit();
      bulk_wait_read();
    }
    if (t == 0) TSS(1);
    return;
  }
  if (hand_over) nb_arrive(kNbOrder + (wg ^ 1), 256);
  if (N == 192 && !local) {
    mbar_wait(sb + kBars + 8 * (kAuxBar + wg), j0 < 32);
    if (j0 < 32) mbar_wait(sb + kBars + 8 * kStatBar, 1);
    mbar_wait(sb + kBars + 8 * (kStgBar + wg), ((j0 >> 5) ^ wg ^ 1) & 1);
  }
  wg_wait<0>();
  mbar_arrive_cluster_if(rel, release_end == nsteps);
#pragma unroll
  for (int i = 0; i < N / 2; i++) asm volatile("" : "+f"(acc[0][i]), "+f"(acc[1][i])::"memory");
}

template <int PH>
struct Ring {
  static constexpr int NSLOT = 4 + (PH & 1), SLOT = PH & 1 ? 32768 : 40960;
  uint32_t full, dst0;
  int j = PH == 0 ? 4 : 0, bi = 0, par = PH == 0 ? 0 : 1;
  __device__ __forceinline__ Ring(uint32_t sb, uint32_t ofs) : full(sb + kBars + 8 * (PH * 9 - (PH & 1))), dst0(sb + kRing + ofs) {}
  __device__ __forceinline__ uint32_t bar() const { return full + 8 * bi; }
  __device__ __forceinline__ uint32_t dst() const { return dst0 + bi * SLOT; }
  __device__ __forceinline__ void acquire_first() const {
    const bool first = j < NSLOT;
    mbar_wait(full + (first ? 8 * min(j, 3) - 32 : 8 * (NSLOT + (PH == 3) + bi)), PH == 2 && first ? 0 : par);
  }
  __device__ __forceinline__ void acquire() const { mbar_wait(full + 8 * (NSLOT + (PH == 3) + bi), par); }
  __device__ __forceinline__ void next() {
    j++;
    if (++bi == NSLOT + (PH == 3 && j > kWide)) { bi = 0; par ^= 1; }
  }
};

__device__ __forceinline__ void check_blocks(const Params& p, Scratch* sc, uint32_t sb, int r, int c, bool g3, uint32_t& par) {
  const int lane = fresh_tid() & 31, nslot = g3 ? 4 : 5, slot_bytes = g3 ? 40960 : 32768;
  const uint32_t mine = (lane >> 2) * 132 + (lane & 3) * 32, ring_end = sb + kRing + kStage + mine;
  const uint32_t to_full = 8 * (kLandBar - (g3 ? ring_base(2) : ring_base(1)));
  uint32_t src = sb + kRing + mine + (g3 ? 0 : 4 * 32768);
  int bi = g3 ? 0 : 4, spins = 0;
#pragma unroll 1
  for (int i = g3 ? 2 : 9; i < 16;) {
    const uint32_t land = sb + kBars + 8 * (kLandBar + bi);
    mbar_wait(land, (par >> bi) & 1);
    uint32_t v[16];
#pragma unroll
    for (int k = 0; k < 16; k++) v[k] = lds32(src + k * 1024);
#pragma unroll
    for (int k = 0; k < 5; k++) v[k] = max(max(v[3 * k + 1], v[3 * k + 2]), k ? v[3 * k] : max(v[0], v[15]));
    const bool again = __any_sync(~0u, max(max(max(v[0], v[1]), v[2]), max(v[3], v[4])) == kPoison);
    asm volatile("{\n.reg .pred p;\nsetp.eq.u32 p, %1, 0;\n@p mbarrier.arrive.shared::cta.b64 _, [%0];\n}\n"
                 ::"r"(land - to_full), "r"(lane + again) : "memory");
    par ^= 1u << bi;
    if (again) {
      if (++spins > 100000) __trap();
      if (elect_one()) {
        mbar_expect_tx(land, 16384);
        tma2d(src - mine, g3 ? &p.h : &p.o, ((g3 ? p.g3[c][i + 2] : p.g2[c][i]) & 15) * 64, r * 128, land);
      }
      nb_sync(kNbSelf + 1, 32);
      continue;
    }
    if (lane == 0 && (i == 2 || i == 3 || (!g3 && (i == 9 || i == 12)))) TS(i < 4 ? 88 + 2 * i : i == 9 ? 120 : 122);
    i++;
    if (++bi == nslot) bi = 0;
    src += slot_bytes;
    if (src == ring_end) src -= kStage;
  }
}

__device__ __forceinline__ void colsum_cta(const Params& p, Scratch* sc, uint32_t sb, int warp, int bid) {
  constexpr int kSlots = 4, kSlot = 49152;
  constexpr int kRows = kMost * 16384, kIn = (kCs - kRows) / 8192;
  const int lane = threadIdx.x & 31, c0 = (bid - 128) * 2;
  const uint32_t full = sb + kBars, empty = full + 8 * kSlots;
  const uint32_t event = full + 64, rfull = full + 128, rempty = full + 256;
  if (threadIdx.x == 0) {
#pragma unroll 1
    for (int i = 0; i < 48; i++) mbar_init(full + 8 * i, i & (i < 16 ? 4 : 32) ? 8 : 1);
    asm volatile("fence.mbarrier_init.release.cluster;" ::: "memory");
  }
  __syncthreads();
  const uint32_t ep = ld_epoch(sc);
  if (warp == 8) {
    if (elect_one()) {
#pragma unroll 1
      for (int n = 0; n < 112 + kSlots; n++) {
        const int u = n >> 4, c = c0 + ((n >> 3) & 1), k0 = (n & 7) * 128, slot = n & (kSlots - 1);
        if (n == kQuietAt) flag_wait(sc->flags + kFlPace, ep);
        const uint32_t bar = full + 8 * slot;
        mbar_wait(empty + 8 * slot, ((n / kSlots) & 1) ^ 1);
        if (n == 108) mbar_arrive(event);
        if (u == 7) continue;
        mbar_expect_tx(bar, u == 6 ? 32768 : 49152);
#pragma unroll
        for (int a = 0; a < 3; a++) {
          if (a == 2 && u == 6) break;
          const CUtensorMap* m = u < 2 ? &p.wqkv : g3_is_up(u - 2, a) ? &p.wu : &p.wg;
          const int col = (u < 2 ? a * 16 + u * 8 + c : g3_atom(u - 2, a, c)) * 64;
          tma2d(sb + slot * kSlot + a * 8192, m, col, k0, bar);
          tma2d(sb + slot * kSlot + a * 8192 + 24576, m, col, k0 + 64, bar);
        }
      }
      mbar_wait(event + 8, 0);
      asm volatile("fence.proxy.async.global;" ::: "memory");
      int slot = 0, par = 1, w = 0;
#pragma unroll 1
      for (int job = 0; job < 32; job++) {
        const int k = lds32(sb + kPlan + (job >> 4) * 4) >> (job & 14) * 2 & 15;
        if (job == 16) {
          mbar_wait(rempty + 8 * (slot ? slot - 1 : kIn - 1), par ^ (slot != 0));
          w = 0;
        }
#pragma unroll 1
        for (int i = 0; i < k; i++) {
          const uint32_t bar = rfull + 8 * slot;
          mbar_wait(bar + 128, par);
          mbar_expect_tx(bar, w < kMost ? 24576 : 8192);
          tma2d(sb + kRows + slot * 8192, &p.hhst, i * (7 * 64), (job & 15) * 128, bar);
          if (w < kMost) {
#pragma unroll
            for (int a = 0; a < 2; a++)
              tma2d(sb + w * 16384 + a * 8192, &p.wd, ((c0 + (job >> 4)) * 2 + a) * 64, w * (7 * 64), bar);
            w++;
          }
          if (++slot == kIn) { slot = 0; par ^= 1; }
        }
      }
    }
  } else if (warp < 8) {
    uint32_t src[3];
#pragma unroll
    for (int j = 0; j < 3; j++) src[j] = sb + ((warp * 3 + j) >> 3) * 8192 + lane * 128 + ((((warp * 3 + j) & 7) ^ (lane & 7)) << 4);
    const uint32_t ones = 0x3F803F80u;
#pragma unroll 1
    for (int s = 0; s < 112; s++) {
      float a[3][2][4] = {};
#pragma unroll 1
      for (;; s++) {
      const int slot = s & (kSlots - 1);
      mbar_wait(full + 8 * slot, (s / kSlots) & 1);
      uint32_t b[3][4][4];
#pragma unroll
      for (int j = 0; j < 3; j++)
#pragma unroll
        for (int k = 0; k < 4; k++)
          asm volatile("ldmatrix.sync.aligned.m8n8.x4.trans.shared.b16 {%0,%1,%2,%3}, [%4];"
                       : "=r"(b[j][k][0]), "=r"(b[j][k][1]), "=r"(b[j][k][2]), "=r"(b[j][k][3])
                       : "r"(src[j] + slot * kSlot + (k >> 1) * 24576 + (k & 1) * 4096) : "memory");
      __syncwarp();
      if (lane == 0) mbar_arrive(empty + 8 * slot);
#pragma unroll
      for (int k = 0; k < 4; k++)
#pragma unroll
        for (int j = 0; j < 3; j++) {
          mma16816(a[j][0], ones, ones, ones, ones, b[j][k][0], b[j][k][1]);
          mma16816(a[j][1], ones, ones, ones, ones, b[j][k][2], b[j][k][3]);
        }
      if ((s & 7) == 7) break;
      }
      {
        if (lane < 12) {
          const int j = lane >> 2;
          const float x = j == 0 ? a[0][0][0] + a[0][1][0] : j == 1 ? a[1][0][0] + a[1][1][0] : a[2][0][0] + a[2][1][0];
          const float y = j == 0 ? a[0][0][1] + a[0][1][1] : j == 1 ? a[1][0][1] + a[1][1][1] : a[2][0][1] + a[2][1][1];
          const float x1 = bf_rest(x), y1 = bf_rest(y);
          const bool split = s < 32;
          st_b128(SC_AT(cs, ((s >> 4) * 8 + c0 + ((s >> 3) & 1)) * 96 + warp * 12 + lane), split ? bf_upper(x, y) : __float_as_uint(x),
                  split ? bf_upper(x1, y1) : __float_as_uint(y), bf_upper(bf_rest(x1), bf_rest(y1)), ep);
        }
        if (threadIdx.x == 0 && (s & 8)) TSK(s >> 4);
      }
    }
    const int wg = warp >> 2;
    mbar_wait(event + 8, 0);
#pragma unroll 1
    for (int job = wg, first = 0; job < 32; job += 2) {
      const int k = __shfl_sync(~0u, lds32(sb + kPlan + (job >> 4) * 4), 0) >> (job & 14) * 2 & 15;
      if (k == 0) continue;
      float acc[96];
#pragma unroll
      for (int i = 0; i < 64; i++) asm volatile("" : "=f"(acc[i]));
      static_assert(kIn == 12, "");
      int slot = first + wg * k, par = slot * 171 >> 11, i = 0;
      slot -= par * kIn;
      first += 2 * k;
      uint32_t done = 0;
      if (job) nb_sync(kNbOrder + wg, 256);
#pragma unroll 1
      do {
        mbar_wait(rfull + 8 * slot, par & 1);
        wg_fence();
#pragma unroll
        for (int kk = 0; kk < 4; kk++)
          wgmma_n128(acc, desc(desc_lo(sb + kRows, 16) + slot * 512) + kk * 2, desc(desc_lo(sb, 8192) + i * 1024) + kk * 128, kk | i);
        wg_commit();
        wg_wait<1>();
        if (lane < 2 && i) mbar_arrive(done);
        done = rempty + 8 * slot;
        if (++slot == kIn) { slot = 0; par++; }
      } while (++i < k);
      nb_arrive(kNbOrder + (wg ^ 1), 256);
      uint4* dst = SC_AT(part, ((job & 15) * 8 + c0 + (job >> 4)) * 1024 + (warp & 3) * 256 + lane);
      wg_wait<0>();
#pragma unroll
      for (int i = 0; i < 64; i++) asm volatile("" : "+f"(acc[i])::"memory");
      if (lane < 2) mbar_arrive(done);
#pragma unroll
      for (int i = 0; i < 8; i++) {
        const float* v = &acc[8 * i];
        asm volatile("st.relaxed.gpu.global.v4.b32 [%0], {%1, %2, %3, %4};"
                     ::"l"(dst + i * 32),
                     "r"(pack_bf16(v[0], v[1])), "r"(pack_bf16(v[2], v[3])), "r"(pack_bf16(v[4], v[5])), "r"(pack_bf16(v[6], v[7])) : "memory");
      }
    }
    if (threadIdx.x == 128) TSK(7);
  } else if (warp == 10) {
    mbar_wait(event, 0);
    flag_wait(sc->flags + kFlHH + (lane & 15) * kFlRow, ep * 8);
    int late = await_word(sc->finish + (uint32_t)((lane & 15) * 8 + c0 + (lane >> 4)), ep);
    __syncwarp();
    late -= __shfl_sync(~0u, late, 0);
    late = max(late, __shfl_xor_sync(~0u, late, 1));
    late = max(min(late - (__reduce_add_sync(~0u, late) >> 5) + kShare * kStepNs, 4096), -4096);
    int k;
#pragma unroll 1
    do {
      k = min(max((late * (8192 / kStepNs) >> 13) + 1, (lane & 14) == 0), kMost);
      late -= kStepNs / 4;
    } while (__reduce_add_sync(~0u, k ? max(2 * k, k + 4) : 0) > kBudget);
    k <<= (lane & 14) * 2;
#pragma unroll
    for (int o = 2; o < 16; o <<= 1) k |= __shfl_xor_sync(~0u, k, o);
    asm volatile("fence.acquire.gpu;" ::: "memory");
    send_word(sc->plan + (uint32_t)(c0 + (lane >> 4)), k, ep);
    sts32(sb + kPlan + (lane >> 4) * 4, k);
    __syncwarp();
    if (lane == 0) mbar_arrive(event + 8);
  }
}

#define PROF_BEGIN
template <bool BY_SM>
__global__ void __cluster_dims__(2, 1, 1) __launch_bounds__(kThreads, 1) fused_block_kernel(Scratch* sc, const __nv_bfloat16* xp, const __nv_bfloat16* wqkvp, __nv_bfloat16* outp,
                                                                   const __grid_constant__ Params p) {
  extern __shared__ __align__(1024) uint8_t smem_raw[];
  if (threadIdx.x < 56) {
    const int l = threadIdx.x & 31, b = blockIdx.x & 127;
    if (threadIdx.x < 32) prefetch_l2(xp + (b * 16 + (l & 15)) * kD + (l >> 4) * 64);
    else prefetch_l2(wqkvp + b * (3 * kD) + (l >> 3) * kD + (l & 7) * 64);
  }
  const uint32_t sb = smem_u32(smem_raw);
  const int bid = role_id<BY_SM>();
  const int r = bid >> 3, c = bid & 7, rank = blockIdx.x & 1;
  auto first_fill = [&](int j) {
    const uint32_t fb = sb + kBars + 8 * j, dst = sb + kRing + j * 40960;
    mbar_expect_tx(fb, 40960);
    tma3d(j >> 1 == c ? sb + kOwn + (j & 1) * 16384 : dst, &p.x, j * 64, (r >> 1) * 128, rank, fb);
#pragma unroll
    for (int a = 0; a < 3; a++) tma2d(dst + 16384 + a * 8192, &p.wqkv, a * kD + c * 64, j * 64, fb);
    mbar_arrive(fb);
  };
  const int tid = threadIdx.x, warp = __shfl_sync(~0u, tid >> 5, 0), wg = warp >> 2;
  if (bid >= 128) {
    if (tid == 0) PROF_BEGIN;
    colsum_cta(p, sc, sb, warp, bid);
    return;
  }
  if (wg == 2) {
    if (warp == 8 && elect_one()) {
#pragma unroll
      for (int j = 0; j < 4; j++) mbar_init(sb + kBars + 8 * j, 2);
      asm volatile("fence.mbarrier_init.release.cluster;" ::: "memory");
      first_fill(0);
      TSS(0);
    }
    __syncwarp();
    if (warp == 8) nb_arrive(kNbOrder, 160);
    asm volatile("setmaxnreg.dec.sync.aligned.u32 40;");
    if (warp == 8) {
      cluster_arrive();
      if (elect_one()) {
#pragma unroll 1
        for (int j = 1; j < 4; j++) first_fill(j);
        TSS(1);
      }
      __syncwarp();
    } else {
      if (elect_one()) {
        uint64_t shifts = warp == 9 ? bar_shifts(4) : warp == 10 ? bar_shifts(22) : bar_shifts(40);
#pragma unroll 1
        for (int i = 0; i < 18; i++, shifts >>= 3) mbar_init(sb + kBars + 8 * (18 * warp - 158 + i), 1u << (shifts & 7));
        if (warp == 10) asm volatile("mbarrier.arrive.shared::cta.b64 _, [%0], 2;" ::"r"(sb + kBars + 8 * 31) : "memory");
        sts32(sb + kZero, 0);
        sts32(sb + kScale + 4, 0);
        sts32(sb + kRole, bid);
        sts128(sb + kOnes, make_uint4(0x3F803F80u, 0, 0, 0x3F803F80u));
        asm volatile("fence.mbarrier_init.release.cluster;" ::: "memory");
      }
      __syncwarp();
      cluster_arrive();
    }
    cluster_wait();
    const uint32_t ep = ld_epoch(sc);
    if (tid == 320) sts32(sb + kEpoch, ep);
    if (tid == 320) PROF_BEGIN;
    const int pw = warp & 3;
    if (pw == 0) {
      if (elect_one()) {
        const int row = r * 128;
        const uint32_t land = sb + kBars + 8 * kLandBar;
#pragma unroll 1
        for (Ring<0> q(sb, 0); q.j < 32; q.next()) {
          q.acquire();
          const int kb = p.g1[c][q.j];
          if (kb & kInPlace) { mbar_arrive(q.bar()); continue; }
          mbar_expect_tx(q.bar(), 16384);
          tma3d(kb >> 1 == c ? sb + kOwn + (kb & 1) * 16384 : q.dst(), &p.x, kb * 64, (r >> 1) * 128, rank, q.bar());
        }
        prefetch_map(&p.o);
        prefetch_map(&p.o16);
        flag_wait(sc->flags + kFlO + r * kFlRow, ep * 8);
        fence_async();
        TS(40);
#pragma unroll 1
        for (Ring<1> q(sb, 0); q.j < 16; q.next()) {
          q.acquire_first();
          if (q.j == 8) {
            prefetch_map(&p.wg);
            prefetch_map(&p.wu);
            prefetch_map(&p.h);
            prefetch_map(&p.h16);
            mbar_wait(sb + kBars + 8 * kSentBar, 0);
            mbar_arrive(q.bar());
            mbar_arrive(sb + kBars + 8 * (kStgBar + 1));
            if (bid == 0) __stcg(sc->flags + kFlPace, ep);
            __nanosleep(kGateONs);
            continue;
          }
          const uint32_t bar = q.j < 8 ? q.bar() : land + 8 * q.bi;
          if (q.j == 9) TS(41);
          mbar_expect_tx(bar, 16384);
          tma2d(q.dst(), &p.o, p.g2[c][q.j] * 64, row, bar);
        }
#pragma unroll 1
        for (Ring<2> q(sb, 0); q.j < 64; q.next()) {
          q.acquire_first();
          const int kb = p.g3[c][q.j];
          if (kb & kInPlace) { mbar_arrive(q.bar()); continue; }
          if (q.j == 4) { __nanosleep(kGateHNs); TS(42); }
          const uint32_t bar = q.j < 18 ? land + 8 * q.bi : q.bar();
          mbar_expect_tx(bar, 16384);
          tma2d(q.dst(), &p.h, (kb & 15) * 64, row, bar);
        }
        prefetch_map(&p.hh);
        prefetch_map(&p.out);
        Ring<3> q(sb, 0);
#pragma unroll 1
        for (; q.j < 16; q.next()) {
          q.acquire_first();
          if (q.j == 0) { mbar_arrive(q.bar()); continue; }
          mbar_expect_tx(q.bar(), 16384);
          tma2d(q.dst(), &p.h, ((q.j + 9) & 15) * 64, row, q.bar());
        }
        uint32_t wave = sb + kBars + 8 * kWaveBar;
        int share = 0;
#pragma unroll 1
        for (; q.j < 72; q.next()) {
          const int kb = p.g4[q.j - 16];
          if (kb & kNextWave) {
            mbar_wait(wave, 0);
            fence_async();
            wave += 8;
            if (q.j == 16) share = lds32(sb + kPlan);
          }
          q.acquire();
          const bool half = (kb & kShared) && --share >= 0;
          mbar_expect_tx(q.bar(), half ? 8192 : 16384);
          tma2d(q.dst() + half * 8192, half ? &p.hhst : &p.hh, (kb & 63) * 64, row + half * 64, q.bar());
        }
      }
    } else if (pw == 1) {
      if (elect_one()) {
        const int rp = r >> 1;
#pragma unroll 1
        for (Ring<0> q(sb, 16384); q.j < 32; q.next()) {
          q.acquire();
          mbar_expect_tx(q.bar(), 24576);
          const int col = ((q.j >> 4) * 8 + c) * 64, k0 = (p.g1[c][q.j] & 15) * 64;
          tma2d_mc(q.dst() + rank * 8192, &p.wqkv, rank * kD + col, k0, q.bar());
          if ((q.j & 1) == rank) tma2d_mc(q.dst() + 16384, &p.wqkv, 2 * kD + col, k0, q.bar());
          if (q.j == max(r, 4))
            for (int a = 0; a < 3; a++) tma_prefetch2d(&p.wqkv, a * kD + (8 + c) * 64, ((r + 12) & 15) * 64);
          if (q.j >> 1 == rp + 8) tma_prefetch2d(&p.wo, (c * 2 + rank) * 64, (q.j & 15) * 64);
        }
        if (r < 6) tma_prefetch2d(rp == 1 ? &p.wu : &p.wg, (c * 7 + 3 + (rp >> 1)) * 64, (c * 2 + rank) * 64);
#pragma unroll 1
        for (Ring<1> q(sb, 16384 + rank * 8192); q.j < 16; q.next()) {
          q.acquire_first();
          mbar_expect_tx(q.bar(), 16384);
          tma2d_mc(q.dst(), &p.wo, (c * 2 + rank) * 64, p.g2[c][q.j] * 64, q.bar());
        }
        const CUtensorMap* mine = rank ? &p.wu : &p.wg;
#pragma unroll 1
        for (Ring<2> q(sb, 16384); q.j < 64; q.next()) {
          const int kb = p.g3[c][q.j], tile = kb >> 5, f0 = c * 7 + (tile & 1) * 3, fp = f0 + (tile & 2);
          const int k0 = (kb & 15) * 64;
          q.acquire_first();
          mbar_expect_tx(q.bar(), 24576);
          const uint32_t dst = q.j < 4 ? sb + kRing + (q.j + 1) * 32768 : q.dst();
          tma2d_mc(dst + rank * 8192, mine, fp * 64, k0, q.bar());
          if ((q.j & 1) == rank) tma2d_mc(dst + 16384, tile & 2 ? &p.wu : &p.wg, (f0 + 1) * 64, k0, q.bar());
          const int d = q.j - kPfStep - (c & 1) * 5 - (r >> 2);
          if (d == 0 || d == 11 || d == 22) {
            const int f = c * 7 + (d == 0 ? 2 : d == 11 ? 5 : 6);
            tma_prefetch2d(&p.wg, f * 64, r * 64);
            tma_prefetch2d(&p.wu, f * 64, r * 64);
            if (d != 22) tma_prefetch2d(&p.wu, (f - 1) * 64, r * 64);
            else tma_prefetch2d(&p.wd, (c * 2 + rank) * 64, rp * (7 * 64));
          }
          if (q.j >> 1 == rp + 24) tma_prefetch2d(&p.wd, (c * 2 + rank) * 64, (p.g4[q.j & 15] & 63) * 64);
        }
        Ring<3> q(sb, 16384 + rank * 8192);
#pragma unroll 1
        for (; q.j < 16; q.next()) {
          q.acquire_first();
          mbar_expect_tx(q.bar(), 16384);
          tma2d_mc(q.dst(), mine, (c * 7 + 6) * 64, ((q.j + 9) & 15) * 64, q.bar());
          if (q.j >> 1 == rp) tma_prefetch2d(&p.wd, (c * 2 + rank) * 64, (p.g4[q.j + 16] & 63) * 64);
        }
#pragma unroll 1
        for (; q.j < 72; q.next()) {
          q.acquire();
          mbar_expect_tx(q.bar(), 16384);
          tma2d_mc(q.dst(), &p.wd, (c * 2 + rank) * 64, (p.g4[q.j - 16] & 63) * 64, q.bar());
          if ((q.j & 15) >> 1 == rp && q.j < 40) tma_prefetch2d(&p.wd, (c * 2 + rank) * 64, (p.g4[q.j + 16] & 63) * 64);
        }
      }
    } else {
      const int cw = pw - 2;
      const uint32_t stg = sb + kStage + cw * 32768, rb = sb + kBars + 8 * kResBar;
      uint32_t land_par = 0;
      sts64(sb + kPlan, global_ns(), clock());
      if (cw == 0) {
#pragma unroll 1
        for (int i = 0; i < 16; i++) sts128(sb + kFill + i * 512 + (tid & 31) * 16, make_uint4(kPoison, kPoison, kPoison, kPoison));
        __nanosleep(kSampleNs);
        const uint32_t l15 = tid & 15;
        const uint4 os = __ldg(plus(p.wop, (tid & 31) * 128 + c * 16 + l15));
        const uint4 gs = __ldg(plus(tid & 16 ? p.wup : p.wgp, l15 * 451 + c * 56));
        const uint4 ws = __ldg(plus((const uint4*)wqkvp, (tid & 7) * 385 + (tid & 24) * 16 + (8 + c) * 8));
        sts64(sb + kScale, __float_as_uint(low_peak(os) * kBias3 * low_peak(gs)), __float_as_uint(low_peak(ws) * kBias1) | 1);
        if (tid == 320) TS(93);
      }
#pragma unroll 1
      for (int ev = -1; ev < 4; ev++) {
        const bool quads = cw == 0 && ev == 1;
        if (ev >= cw && !quads) nb_sync(kNbPub + cw, 160);
        if (ev >= cw && elect_one()) {
          if (quads) {
            mbar_wait(sb + kBars + 8 * (kHalfBar + 1), 0);
#pragma unroll 1
            for (int i = 0; i < 2; i++) {
              __nanosleep(i ? kPaceNs : kHoldNs);
              tma_store2d(&p.hst, stg + 16384 + i * 8192, c * 128 + 64, r * 128 + i * 64);
              TS(100 + i);
            }
            bulk_commit();
            bulk_wait_read();
            mbar_arrive(sb + kBars + 8 * kStgBar);
          } else {
            if (ev == 1) {
              const uint32_t now = global_ns();
              const float left = (float)(now - lds32(sb + kPlan)) * (float)kRemain * rcp((float)((uint32_t)clock() - lds32(sb + kPlan + 4)));
              send_word(sc->finish + (uint32_t)bid, now + (uint32_t)left, ep);
            }
            const int it = ev - 2 + cw, f0 = c * 7 + (1 - cw) * 3, fp = it == 2 ? c * 7 + 6 : f0 + 2 * it;
            const bool is_o = ev == 0;
            const CUtensorMap* m = is_o ? &p.ost : &p.hhst;
            const int b0 = is_o ? c : f0 + 1, b1 = fp;
#pragma unroll 1
            for (int i = is_o || it == 1 ? 0 : 2; i < (is_o ? 2 : 4); i++) {
              tma_store2d(m, stg + i * 8192, (i < 2 ? b0 : b1) * 64, r * 128 + (i & 1) * 64);
              if (!is_o) {
                bulk_commit();
                bulk_wait_read();
                __nanosleep(kPaceNs);
              }
            }
            bulk_commit();
            bulk_wait_all();
            mbar_arrive(sb + kBars + 8 * (kStgBar + cw));
            if (ev == 3 + cw) {
#pragma unroll
              for (int i = 0; i < 2; i++) asm volatile("mbarrier.arrive.shared::cluster.b64 _, [%0], 4;" ::"r"(map_cta(sb + kBars + 8 * 37, i)) : "memory");
            }
            flag_signal(SC_AT(flags, kFlHH + ev * 2 - 3 + cw + r * kFlRow));
            TS(44 + cw * 8 + ev);
            if (ev == 2 && cw) {
              sts32(sb + kPlan, await_word(sc->plan + (uint32_t)c, ep) >> (r >> 1) * 4 & 15);
              mbar_expect_tx(rb, 16384);
#pragma unroll 1
              for (int i = 0; i < 2; i++) tma2d(stg + 8192 + i * 16384, &p.hst, c * 128 + i * 64, r * 128 + 64, rb);
            }
          }
        }
        nb_sync(kNbSelf + cw, 32);
        if (ev >= 2 && ev + cw >= 3 && elect_one()) {
          const int wv = cw == 0 ? 3 : ev == 2 ? 0 : 4;
#pragma unroll 1
          for (int i = wv; i <= max(wv, 2); i++) flag_wait(SC_AT(flags, kFlHH + i + r * kFlRow), ep * 8);
          fence_async();
          mbar_arrive(sb + kBars + 8 * (kWaveBar + (wv >> 1)));
          if (wv == 4) {
            mbar_expect_tx(sb + kBars + 8 * kPartBar, 16384);
#pragma unroll 1
            for (int i = 0; i < 2; i++) tma2d(stg + 16384 + i * 8192, &p.hst, c * 128 + i * 64, r * 128, sb + kBars + 8 * kPartBar);
          }
        }
        nb_sync(kNbSelf + cw, 32);
#pragma unroll 1
        for (int sub = 0; ev < 3 && (ev != 0 || cw == 1); sub++) {
          nb_sync(kNbSelf + cw, 32);
          if (ev == 0) check_blocks(p, sc, sb, r, c, sub, land_par);
          const int u = ev < 0 ? cw : 2 * ev + 1 + cw, lane = fresh_tid() & 31;
          if (u == 1 && !sub) {
            uint3 st[5];
            load_tagged<5, true>(st, SC_AT(stat1, r * 128 + lane), 32, ep, SC_AT(stat1, (r < 2 ? r : r - 2) * 128 + (lane & 7)) + 120);
#pragma unroll
            for (int i = 0; i < 4; i++) sts64(sb + kStat + (i * 32 + lane) * 8, st[i].x, st[i].y);
            sts64(sb + kStat - 64 + (lane & 7) * 8, st[4].x, st[4].y);
            nb_sync(kNbSelf + cw, 32);
            if (lane < 4) mbar_arrive(sb + kBars + 8 * kStatBar);
            if (lane == 0) TS(17);
          }
          if (u == 1) {
            const uint4* gh = SC_AT(halo, (sub * 128 + bid) * 192 + lane) - 16 * 192;
            uint4 hv[6] = {};
            nb_sync(kNbHalo, 64);
            uint32_t ns = sub ? kHaloNs : 2 * kBackoffNs;
#pragma unroll 1
            for (int spins = 0; r >= 2; spins++) {
              if (ns) __nanosleep(ns);
              ns = sub ? 0 : kBackoffNs;
              if (spins > 2000000) __trap();
#pragma unroll
              for (int i = 0; i < 6; i++) hv[i] = ld_b128(gh + i * 32);
              uint32_t bad = (hv[5].y ^ ep) | (hv[5].z ^ ep);
#pragma unroll
              for (int i = 0; i < 6; i++) bad |= hv[i].w ^ ep;
              if (!__any_sync(~0u, bad != 0)) break;
            }
            const uint32_t dst = sb + kStage + sub * 32768 + lane * 16;
            sts128(dst, make_uint4(hv[0].x, hv[0].y, hv[0].z, hv[1].x));
            sts128(dst + 512, make_uint4(hv[1].y, hv[1].z, hv[2].x, hv[2].y));
            sts128(dst + 1024, make_uint4(hv[2].z, hv[3].x, hv[3].y, hv[3].z));
            sts128(dst + 1536, make_uint4(hv[4].x, hv[4].y, hv[4].z, hv[5].x));
            nb_arrive(kNbHalo + 1, 64);
            if (lane == 0) TS(123 + sub);
          }
          if (sub) break;
          uint3 v[3];
          load_tagged<3, false>(v, SC_AT(cs, c * 96 + u * 768 + lane), 32, ep);
          if (u < 2) {
#pragma unroll
            for (int i = 0; i < 3; i++)
#pragma unroll
              for (int k = 0; k < 8; k++)
                sts32(sb + kAug + cw * 4096 + i * 1024 + k * 128 + ((lane * 4) ^ (k * 16)), k == 7 ? 0x3F803F80u : k == 4 || k == 6 ? v[i].z : k & 1 && k != 5 ? v[i].y : v[i].x);
            fence_async_smem();
          } else {
#pragma unroll
            for (int i = 0; i < 3; i++) sts64(sb + kCs + cw * 768 + (i * 32 + lane) * 8, v[i].x, v[i].y);
          }
          nb_sync(kNbSelf + cw, 32);
          if (lane == 0) { mbar_arrive(sb + kBars + 8 * (kAuxBar + cw)); TS(104 + u); }
        }
        nb_sync(kNbSelf + cw, 32);
        if (ev < 0 && cw == 0 && elect_one()) {
#pragma unroll 1
          for (int i = 0; i < 6; i++) {
            __nanosleep(i == 0 ? (c >> 1) * (kFillNs / 4) : kFillNs);
            tma_store2d(i < 2 ? &p.ost : &p.hst, sb + kFill, i < 2 ? (8 + c) * 64 : (c * 2 - 1 + (i >> 1)) * 64, r * 128 + (i & 1) * 64);
            bulk_commit();
          }
          uint32_t peer;
          asm volatile("ld.shared::cluster.b32 %0, [%1];" : "=r"(peer) : "r"(map_cta(sb + kRole, rank ^ 1)) : "memory");
          if (peer != (bid ^ 8)) __trap();
          TS(90);
        }
        nb_sync(kNbSelf + cw, 32);
      }
    }
  } else {
    if (tid == 0) TSS(2);
    cluster_arrive();
    float bias = 0.f;
    float sx = 0.f, mx = 0.f;
    asm volatile("setmaxnreg.inc.sync.aligned.u32 232;");
    if (tid == 0) TSS(4);
    int task;
    asm volatile("mov.u32 %0, %1;" : "=r"(task) : "r"(8 - wg));

#pragma unroll 1
    for (task = __shfl_sync(~0u, task, 0);; task++) {
      if (task == 1 + wg || task == 9 - wg) {
        const int t = fresh_tid();
        uint2 scale;
        do asm volatile("ld.volatile.shared.v2.b32 {%0, %1}, [%2];" : "=r"(scale.x), "=r"(scale.y) : "r"(sb + kScale) : "memory");
        while (scale.y == 0);
        __syncwarp();
        bias = bias_at(low_peak(lds128(sb + (task > 5 ? kRing : kStage + wg * 32768) + (t & 126) * 64 + (t & 14) * 8 + (t & 1) * 8192)) *
                       __uint_as_float(task > 5 ? scale.y : scale.x));
        if (t == 128 && task > 5) TS(95);
      }
      if (wg == 0 && (task == 1 || task == 4)) {
        float acc[2][96];
        const int t = fresh_tid() & 127;
        const uint32_t frag = sb + kOwn + ((t >> 5) * 16 + (t & 15)) * 128, frag_x = ((t >> 4) & 1) ^ (t & 7);
        TSG(2);
        if (task == 4) mbar_wait(sb + kBars + 8 * kResBar, 0);
        auto residual = [&](int m) {
#pragma unroll
          for (int i = 0; i < 8; i++) {
            uint32_t v[4];
            ldsm4(frag + (i >> 2) * 16384 + m * 8192 + ((frag_x ^ (i * 2 & 6)) << 4), v);
#pragma unroll
            for (int e = 0; e < 4; e++) {
              float* d = &acc[m][8 * i + 2 * e];
              asm("shl.b32 %0, %1, 16;" : "=f"(d[0]) : "r"(v[e]));
              asm("and.b32 %0, %1, 0xFFFF0000;" : "=f"(d[1]) : "r"(v[e]));
            }
          }
        };
        residual(1);
        if (task == 1) {
          residual(0);
        } else {
#pragma unroll
          for (int i = 0; i < 64; i++) acc[0][i] = 0.f;
        }
        __syncwarp();
        if ((t & 31) == 0) mbar_arrive(sb + kBars + 8 * kResFreeBar);
        TSG(4);
        if ((tid & 127) == 0) TS(task == 1 ? 6 : 14);
        if (task == 4) {
          mainloop<128, kTail>(sc, acc, sb, 3, 16, 56, -2, true, false, false, 0, __shfl_sync(~0u, lds32(sb + kPlan), 0), &p.out, c * 128, (r >> 1) * 128, warp, outp);
          if ((tid & 127) == 0) TSK(15);
          if (fresh_tid() == 0) {
            if (bid == 0) __stcg(sc->epoch, lds32(sb + kEpoch));
            TSK(19);
          }
          break;
        }
        mainloop<128, -1>(sc, acc, sb, 1, 0, 15, kPauseG2, false, true, false, 0);
        const int t2 = fresh_tid() & 127;
        const uint32_t frag2 = sb + kStage + ((t2 >> 5) * 16 + (t2 & 15)) * 128, frag2_x = ((t2 >> 4) & 1) ^ (t2 & 7);
        const uint32_t empty = map_cta(sb + kBars + 8 * (ring_base(1) + 5), t2 & 1);
        mbar_wait(sb + kBars + 8 * kStgBar, 0);
        mbar_wait(sb + kBars + 8 * ring_base(1), 1);
#pragma unroll
        for (int m = 0; m < 2; m++) {
          const uint32_t a = desc_lo(sb + kRing, 16);
          wg_fence();
#pragma unroll
          for (int k = 0; k < 4; k++) wgmma_n128(acc[m], desc_kept(a, sb) + (m * 512 + k * 2), desc_kept(a, sb) + (kToB + k * 128));
          wg_commit();
          if (m) nb_arrive(kNbOrder + 1, 256);
          wg_wait<1>();
          if (!m) mbar_arrive_cluster_if(empty + 8 * 4, (t2 & 31) < 2);
        }
#pragma unroll
        for (int b = 0; b < 4; b++) {
          if (b == 1) {
            wg_wait<0>();
            if (t2 == 0) TSK(7);
          }
          if (b < 2) {
#pragma unroll
            for (int i = 0; i < 64; i++) asm volatile("" : "+f"(acc[b][i])::"memory");
          }
          stage_quarter(&acc[b & 1][32 * (b >> 1)], frag2, frag2_x, b);
          if (b & 1) {
            fence_async_smem();
            __syncwarp();
            if (elect_one()) {
              mbar_arrive(sb + kBars + 8 * (kHalfBar + (b >> 1)));
#pragma unroll
              for (int m = 0; m < 2; m++)
                if (b == 1) tma_store2d(&p.h16, sb + kStage + m * 8192 + warp * 2048, c * 128, r * 128 + m * 64 + warp * 16);
            }
            __syncwarp();
          }
        }
        if (t2 == 0) TS(8);
        sx = mx = 0.f;
        continue;
      }
      float acc[2][96];
      if (task == 8 + wg) {
        wg_fence();
#pragma unroll
        for (int m = 0; m < 2; m++) wgmma_n192_any(acc[m], desc(64 + m), desc(64 + m));
        wg_commit();
        wg_wait<0>();
#pragma unroll
        for (int i = 0; i < 96; i++) asm volatile("" : "+f"(acc[0][i]), "+f"(acc[1][i])::"memory");
      } else {
        const uint32_t z = fresh_tid() >> 10;
#pragma unroll
        for (int i = 0; i < 96; i++) {
#pragma unroll
          for (int m = 0; m < 2; m++)
            asm("{\n.reg .b32 t;\nlop3.b32 t, %1, %2, %3, 0xEA;\nmov.b32 %0, t;\n}\n" : "=f"(acc[m][i]) : "r"(z), "r"(2 * i + m + 1), "r"(__float_as_uint(bias)));
        }
      }
      if (task > 5) {
      if (wg) {
        if (task == 7) cluster_wait();
        if (tid == 128 && task == 7) { TSS(5); TSK(69); }
        const int t = fresh_tid() & 127, lr = c * 16 + (t >> 3);
        uint32_t pf = t < 64 ? (bid * 16 + (t >> 2)) * kD + (t & 3) * 64 : (r * 48 + t - 64) * kD + c * 64;
        const uint32_t src = sb + kRing + lr * 128 + (((t ^ lr) & 7) << 4), empty = map_cta(sb + kBars + 8 * 4, t & 1), zero = fresh_tid() >> 10;
#pragma unroll 1
        for (int j = task == 7 ? 0 : kSplit; j < (task == 7 ? kSplit : 16); j++) {
          mbar_wait(sb + kBars + 8 * (j & 3), (j >> 2) & 1);
          if (j < 2 && t == 0) TS(102 + j);
          const uint4 v = lds128(src + (j >> 1 == c ? kOwn + (j & 1) * 16384 : (j & 3) * 40960));
          __syncwarp();
          mbar_arrive_cluster_if(empty + 8 * (j & 3) + (v.x & zero), (t & 31) < 2);
          if ((j == 0 || j == 3 || j == 6) && t < 112) { pf += t < 64 ? 256 : 256 * 3 * kD; prefetch_l2(plus(t < 64 ? xp : wqkvp, pf)); }
          const uint32_t u[4] = {v.x, v.y, v.z, v.w};
#pragma unroll
          for (int e = 0; e < 4; e++) {
            const float d0 = bf_lo(u[e]), d1 = bf_hi(u[e]);
            sx += d0 + d1;
            mx = fmaf(d1, d1, fmaf(d0, d0, mx));
          }
        }
        if (task == 7) {
          if (t == 0) TS(96);
          continue;
        }
#pragma unroll
        for (int o = 4; o > 0; o >>= 1) { sx += __shfl_xor_sync(~0u, sx, o); mx += __shfl_xor_sync(~0u, mx, o); }
        const float mean = sx * (1.f / kD);
        float rstd;
        asm("rsqrt.approx.ftz.f32 %0, %1;" : "=f"(rstd) : "f"(fmaxf(mx * (1.f / kD) - mean * mean, 0.f) + 1e-5f));
        const uint32_t ep = lds32(sb + kEpoch);
        const int t2 = fresh_tid();
        if ((t2 & 7) == 0) st_b128(SC_AT(stat1, bid * 16 + (t2 >> 3 & 15)), __float_as_uint(rstd), __float_as_uint(-mean), ep, ep);
        if (t == 0) TS(16);
      }
      if (tid == 0) TSS(6);
      mainloop<192, -1>(sc, acc, sb, 0, wg * 16, wg ? 16 - kAhead : 16, wg ? kPauseG1 : -2, false, wg == 0, false, wg,
                        wg ? min((c + 2) & 7, 6) : c);
      int t = fresh_tid() & 127, lane = t & 31, g = lane >> 2, q = lane & 3;
      const int w = warp & 3;
      const uint32_t stg = sb + kStage + wg * 32768;
      auto tail = [&](int m, int k0, int k1) {
        wg_fence();
#pragma unroll
        for (int k = k0; k < k1; k++) {
          const uint64_t a = desc_kept(desc_lo(sb + kRing, 16), sb) + (4 - kAhead + (k >> 2)) * (40960 >> 4);
          wgmma_n192(acc[m], a + (m * 512 + (k & 3) * 2), a + (kToB + (k & 3) * 128));
        }
      };
      auto release = [&](int j, bool cond) { mbar_arrive_cluster_if(map_cta(sb + kBars + 8 * (4 + (j & 3)), lane & 1), cond); };
      if (wg) {
#pragma unroll
        for (int j = 32 - kAhead; j < 32; j++) {
          TST(2 * (j & 1));
          mbar_wait(sb + kBars + 8 * (j & 3), 1);
          TST(2 * (j & 1) + 1);
          tail(1, 4 * (j - 32 + kAhead), 4 * (j - 31 + kAhead));
          wg_commit();
          if (j == 32 - kAhead) {
            wg_wait<1>();
            release(j - 1, lane < 4);
            mbar_wait(sb + kBars + 8 * kResFreeBar, 0);
          }
        }
      } else {
        nb_arrive(kNbOrder + 1, 256);
        wg_wait<0>();
        release(15, lane < 2);
        if (t == 0) TSK(1);
      }
      TST(4);
      mbar_wait(sb + kBars + 8 * (kAuxBar + wg), 0);
      mbar_wait(sb + kBars + 8 * kStatBar, 0);
      {
        uint32_t am[4];
#pragma unroll
        for (int i = 0; i < 4; i++) {
          const float m1 = __uint_as_float(lds32(sb + kStat + (w * 16 + g) * 8 + 4 + (i >> 1) * 512 + (i & 1) * 64));
          const float m2 = bf_rest(m1), lo = q & 1 ? m2 : m1;
          am[i] = bf_upper(lo, q == 3 ? -bias : q == 2 ? bf_rest(m2) : lo);
        }
        const uint64_t db = (uint64_t)desc_lo(sb + kAug + wg * 4096, 1024) | (0x40000000ull << 32);
        TST(5);
        wg_fence();
        wgmma_n192_rs(acc[1], am[2], am[3], 0u, db);
        wg_commit();
        TST(6);
        wg_fence();
        wgmma_n192_rs(acc[0], am[0], am[1], 0u, db);
        wg_commit();
        if (wg) {
          tail(0, 0, 4 * kAhead);
          wg_commit();
          wg_wait<2>();
        } else {
          wg_wait<1>();
        }
        TST(8);
#pragma unroll
        for (int i = 0; i < 96; i++) asm volatile("" : "+f"(acc[1][i])::"memory");
      }
      t = fresh_tid() & 127, lane = t & 31;
      const uint32_t ep = lds32(sb + kEpoch);
      uint32_t pk[2][48];
      auto fold = [&](int pp, int jn, int hf) {
        const uint32_t v = pack_bf16(acc[pp][4 * jn + 2 * hf], acc[pp][4 * jn + 2 * hf + 1]);
        pk[pp][2 * jn + hf] = jn >= 16 ? movm(v) : v;
      };
      if (t == 96) TS(115 + wg);
#pragma unroll
      for (int jn = 8; jn < 24; jn++) fold(1, jn, 1);
      if (w < 3) {
#pragma unroll
        for (int i = 0; i < 4; i++)
          sts128(stg + (w + 5) * 2048 + i * 512 + lane * 16, make_uint4(pk[1][17 + 8 * i], pk[1][19 + 8 * i], pk[1][21 + 8 * i], pk[1][23 + 8 * i]));
      } else if (r < 14) {
        uint4* gh = SC_AT(halo, (wg * 128 + bid) * 192 + lane);
#pragma unroll
        for (int i = 0; i < 6; i++) st_b128(gh + i * 32, pk[1][17 + 6 * i], i < 5 ? pk[1][(19 + 6 * i) % 48] : ep, i < 5 ? pk[1][(21 + 6 * i) % 48] : ep, ep);
        if (wg == 0) {
#pragma unroll 1
          for (int i = 0; i < 6; i++, gh += 32) st_b128(gh + 128 * 192, 0, 0, 0, ep - 1);
        }
      }
      if (w == 3) nb_arrive(kNbHalo, 64);
      if (wg) nb_arrive(kNbOrder, 256);
      TST(9);
      if (t == 96) TS(111 + wg);
#pragma unroll
      for (int jn = 23; jn >= 0; jn--) {
        fold(1, jn, 0);
        if (jn < 8) fold(1, jn, 1);
      }
      t = fresh_tid() & 127, lane = t & 31, g = lane >> 2, q = lane & 3;
      const bool sel0 = 2 * q > g, sel1 = 2 * q + 1 > g, no_prev = (r < 2 && w == 0);
      const uint4 ones = lds128(sb + kOnes);
      const uint32_t lowmask = (sel0 ? 0x0000FFFFu : 0u) | (sel1 ? 0xFFFF0000u : 0u) | ones.y;
      float rs[4][2], rk[4][2];
#pragma unroll
      for (int i = 0; i < 4; i++) {
        const uint32_t a = sb + kStat + w * 128 + (i >> 1) * 512 + (i & 1) * 64;
        const float rq = __uint_as_float(lds32(a + g * 8)) * (0.17677669529663687f * 1.4426950408889634f);
        rk[i][0] = __uint_as_float(lds32(a + q * 16 - (sel0 ? 64 : 0)));
        rk[i][1] = __uint_as_float(lds32(a + q * 16 + 8 - (sel1 ? 64 : 0)));
        rs[i][0] = rk[i][0] * rq;
        rs[i][1] = rk[i][1] * rq;
      }
      {
        uint32_t all = ~0u;
#pragma unroll
        for (int i = 0; i < 48; i++) if (i < 16 || !(i & 1)) all &= pk[1][i];
        if (all == kPoison) sts32(sb + kZero + 8, 0);
      }
      TST(10);
      wg_wait<0>();
      TST(11);
#pragma unroll
      for (int j = 32 - kAhead; j < 32; j++) release(j, lane < 4 * wg && (w != 0 || j < 31));
#pragma unroll
      for (int i = 0; i < 96; i++) asm volatile("" : "+f"(acc[0][i])::"memory");
      if (t == 0 && wg) TSK(21);
#pragma unroll
      for (int jn = 8; jn < 24; jn++) fold(0, jn, 1);
#pragma unroll
      for (int i = 0; i < 4; i++)
        sts128(stg + (w + 1) * 2048 + i * 512 + lane * 16, make_uint4(pk[0][17 + 8 * i], pk[0][19 + 8 * i], pk[0][21 + 8 * i], pk[0][23 + 8 * i]));
#pragma unroll
      for (int jn = 23; jn >= 0; jn--) {
        fold(0, jn, 0);
        if (jn < 8) fold(0, jn, 1);
      }
      if (t == 0) TS(113 + wg);
      nb_sync(kNbWg + wg, 128);
      uint32_t hal[2][16];
      auto load_halo = [&](int m) {
#pragma unroll
        for (int i = 0; i < 4; i++) {
          const uint4 v = lds128(stg + w * 2048 + m * 8192 + i * 512 + lane * 16);
          uint32_t* h = &hal[m][i * 4];
          h[0] = v.x; h[1] = v.y; h[2] = v.z; h[3] = v.w;
        }
      };
      load_halo(1);
      if (w == 0) {
        nb_sync(kNbHalo + 1, 64);
        release(31, lane < 4 * wg);
      }
      load_halo(0);
      __syncwarp();
      if (t == 0) TS(2 + wg * 20);
      {
        uint32_t all = lowmask;
#pragma unroll
        for (int i = 0; i < 32; i++) if (i < 16 || !(i & 1)) all &= pk[0][i];
#pragma unroll
        for (int i = 0; i < 8; i++) all &= __float_as_uint(rs[i >> 1][i & 1]);
        if (all == kPoison) sts32(sb + kZero + 8, 0);
      }
      nb_sync(kNbWin, 256);
      if (t == 0) TS(9 + wg * 20);
      const uint32_t zero = lds32(sb + kZero);
      float s0[4][4], s1[4][4], s2[4][4];
#pragma unroll
      for (int k = 0; k < 4; k++) {
        pk[k >> 1][8 * (k & 1)] |= zero;
#pragma unroll
        for (int e = 0; e < 4; e++) s0[k][e] = s1[k][e] = s2[k][e] = 0.f;
      }
#pragma unroll
      for (int ks = 0; ks < 2; ks++)
#pragma unroll
        for (int k = 0; k < 4; k++) {
          const uint32_t* qf = &pk[k >> 1][8 * (k & 1) + 4 * ks];
          const uint32_t* kf = &pk[k >> 1][16 + 8 * (k & 1) + 4 * ks];
          const uint32_t* hf = &hal[k >> 1][4 * (k & 1) + 2 * ks];
          mma16816(s0[k], qf[0], qf[1], qf[2], qf[3], hf[0], hf[1]);
          mma16816(s1[k], qf[0], qf[1], qf[2], qf[3], kf[0], kf[2]);
          mma16816(s2[k], qf[0], qf[1], qf[2], qf[3], kf[1], kf[3]);
        }
      float ea[4][2], eb[4][2], ma[4], mb[4];
#pragma unroll
      for (int k = 0; k < 4; k++) {
        const float *ra = rs[k & 2], *rb = rs[(k & 2) + 1];
        if (no_prev && k < 2) s0[k][0] = s0[k][1] = -INFINITY;
        ea[k][0] = (sel0 ? s0[k][0] : s1[k][0]) * ra[0]; ea[k][1] = (sel1 ? s0[k][1] : s1[k][1]) * ra[1];
        eb[k][0] = (sel0 ? s1[k][2] : s2[k][2]) * rb[0]; eb[k][1] = (sel1 ? s1[k][3] : s2[k][3]) * rb[1];
        ma[k] = fmaxf(ea[k][0], ea[k][1]); mb[k] = fmaxf(eb[k][0], eb[k][1]);
      }
#pragma unroll
      for (int o = 1; o < 4; o <<= 1)
#pragma unroll
        for (int k = 0; k < 4; k++) {
          ma[k] = fmaxf(ma[k], __shfl_xor_sync(~0u, ma[k], o));
          mb[k] = fmaxf(mb[k], __shfl_xor_sync(~0u, mb[k], o));
        }
      float ov[4][4][4], ls[4][4];
      uint32_t all = 0;
#pragma unroll
      for (int k = 0; k < 4; k++) {
        const float *ra = rk[k & 2], *rb = rk[(k & 2) + 1];
        ea[k][0] = ex2(ea[k][0] - ma[k]); ea[k][1] = ex2(ea[k][1] - ma[k]);
        eb[k][0] = ex2(eb[k][0] - mb[k]); eb[k][1] = ex2(eb[k][1] - mb[k]);
        const uint32_t pa = pack_bf16(ea[k][0] * ra[0], ea[k][1] * ra[1]), pb = pack_bf16(eb[k][0] * rb[0], eb[k][1] * rb[1]);
        const uint32_t* vf = &pk[k >> 1][32 + 8 * (k & 1)];
        const uint32_t* hf = &hal[k >> 1][8 + 4 * (k & 1)];
#pragma unroll
        for (int d2 = 0; d2 < 2; d2++) {
#pragma unroll
          for (int e = 0; e < 4; e++) ov[k][d2][e] = ov[k][2 + d2][e] = 0.f;
          mma1688(ov[k][d2], hf[2 * d2], hf[2 * d2 + 1], pa & lowmask);
          mma1688(ov[k][2 + d2], vf[4 * d2], vf[4 * d2 + 2], pb & lowmask);
        }
#pragma unroll
        for (int d2 = 0; d2 < 2; d2++) {
          mma1688(ov[k][d2], vf[4 * d2], vf[4 * d2 + 2], pa & ~lowmask);
          mma1688(ov[k][2 + d2], vf[4 * d2 + 1], vf[4 * d2 + 3], pb & ~lowmask);
        }
        ls[k][0] = ls[k][1] = ls[k][2] = ls[k][3] = 0.f;
        mma16816(ls[k], ones.x, ones.y, ones.z, ones.w, pack_bf16(ea[k][0], ea[k][1]), pack_bf16(eb[k][0], eb[k][1]));
        if (k >= kDone) all |= pa & pb;
      }
#pragma unroll
      for (int k = 0; k < 4; k++) {
        if (k == kDone) {
          if (all == 0xFFFFFFFFu) sts32(sb + kZero + 8, 0);
          nb_arrive(kNbWin + 1, 256);
          all = 0;
        }
        all |= (__float_as_uint(ov[k][0][0]) & __float_as_uint(ov[k][1][0]) & __float_as_uint(ov[k][2][0])) &
               (__float_as_uint(ov[k][3][0]) & __float_as_uint(ls[k][0]));
      }
      const uint32_t nil = lds32(sb + kZero);
      const uint32_t frag = stg + (w * 16 + (lane & 15)) * 128, frag_x = (lane >> 4) ^ (lane & 7);
      uint32_t after = all;
#pragma unroll
      for (int k = 0; k < 4; k++) {
        uint32_t h[2][4];
#pragma unroll
        for (int hf = 0; hf < 2; hf++) {
          const float i0 = rcp(__uint_as_float(__float_as_uint(ls[k][2 * hf]) | (after & nil)));
          const float i1 = rcp(__uint_as_float(__float_as_uint(ls[k][2 * hf + 1]) | (after & nil)));
#pragma unroll
          for (int e = 0; e < 4; e++) h[e >> 1][2 * (e & 1) + hf] = pack_bf16(ov[k][2 * hf + (e >> 1)][2 * (e & 1)] * i0, ov[k][2 * hf + (e >> 1)][2 * (e & 1) + 1] * i1);
          after = h[0][hf];
        }
#pragma unroll
        for (int d2 = 0; d2 < 2; d2++) stsm4_t(frag + (k >> 1) * 8192 + ((frag_x ^ ((k & 1) * 4 + d2 * 2)) << 4), h[d2][0], h[d2][1], h[d2][2], h[d2][3]);
      }
      fence_async_smem();
      if (wg) {
        __syncwarp();
        if (elect_one()) {
          tma_store2d(&p.o16, stg + w * 2048, (8 + c) * 64, r * 128 + w * 16);
          tma_store2d(&p.o16, stg + 8192 + w * 2048, (8 + c) * 64, r * 128 + 64 + w * 16);
          bulk_commit();
          bulk_wait_read();
          mbar_arrive(sb + kBars + 8 * kSentBar);
        }
        __syncwarp();
      } else {
        nb_arrive(kNbPub, 160);
      }
      if (t == 0) TS(3 + wg * 20);
      task = wg;
      sx = mx = bias = 0.f;
      continue;
      }

      {
#pragma unroll 1
        for (int part = task != 2; part < 2; part++) {
          if ((tid & 127) == 0) TS(6 + 2 * task + wg * 20);
          if (task + part == 5) {
            mainloop<128, 0>(sc, acc, sb, 3, 0, 16, -2, false, true, false, 1);
            continue;
          }
          const int j0 = task == 3 ? 48 - wg * 16 : part == 0 ? 2 - 2 * wg : 18 - 14 * wg;
          mainloop<192, 0>(sc, acc, sb, 2, j0, task != 2 ? 16 : part == 0 ? 2 : 14, -2, false, true, part == 0, wg);
          if (part == 0 && wg == 0) {
            const int t = fresh_tid() & 127;
            const uint32_t ep = lds32(sb + kEpoch);
            {
              float s = 0.f, ss = 0.f;
#pragma unroll 1
              for (int i = 0; i < 16; i++) {
                const uint4 v = lds128(sb + kStage + t * 128 + (i >> 3) * 16384 + (((i ^ t) & 7) << 4));
                const uint32_t u[4] = {v.x, v.y, v.z, v.w};
#pragma unroll
                for (int e = 0; e < 4; e++) {
                  const float d0 = bf_lo(u[e]), d1 = bf_hi(u[e]);
                  s = (s + d0) + d1;
                  ss = fmaf(d1, d1, fmaf(d0, d0, ss));
                }
              }
              st_b128(SC_AT(stat2, c * kS + r * 128 + t), __float_as_uint(s), __float_as_uint(ss), ep, ep);
            }
            __nanosleep(kStatNs);
            float2 sum = make_float2(0.f, 0.f);
#pragma unroll 1
            for (int i = 0; i < 2; i++) {
              uint3 a[4];
              load_tagged<4, true>(a, SC_AT(stat2, i * 4 * kS + r * 128 + t), kS, ep);
              sum.x += (__uint_as_float(a[0].x) + __uint_as_float(a[1].x)) + (__uint_as_float(a[2].x) + __uint_as_float(a[3].x));
              sum.y += (__uint_as_float(a[0].y) + __uint_as_float(a[1].y)) + (__uint_as_float(a[2].y) + __uint_as_float(a[3].y));
            }
            const float mean = sum.x * (1.f / kD);
            sts64f(sb + kStat + t * 8, make_float2(fmaxf(sum.y * (1.f / kD) - mean * mean, 0.f) + 1e-5f, -mean));
            __syncwarp();
            if (elect_one()) {
              bulk_commit();
              bulk_wait_read();
              mbar_arrive(sb + kBars + 8 * kStatBar);
            }
            __syncwarp();
            if (t == 0) TS(37);
          }
        }
      }
      const int t = fresh_tid() & 127, w = warp & 3, lane = t & 31, g = lane >> 2, q = lane & 3;
      const uint32_t stg = sb + kStage + wg * 32768;
      uint32_t csv = sb + kCs + wg * 768 + q * 8;
      uint32_t statv = sb + kStat + (w * 16 + g) * 8;
      const uint32_t frag = stg + (w * 16 + (lane & 15)) * 128;
      const uint32_t frag_x = (lane >> 4) ^ (lane & 7);
      const uint32_t priv = stg + (t & 96) * 64 + lane * 16;
      if (t == 0) TSK(7 + 2 * task + wg * 20);

      if (task == 4) {
        mbar_wait(sb + kBars + 8 * (kAuxBar + 1), 1);
        mbar_wait(sb + kBars + 8 * kResFreeBar, 1);
        mbar_wait(sb + kBars + 8 * (kStgBar + 1), 0);
      }
      asm volatile("" : "+r"(csv), "+r"(statv)::"memory");

      {
#pragma unroll
        for (int i = 0; i < 96; i++) asm volatile("sub.f32 %0, %0, %1;" : "+f"(acc[0][i]) : "f"(bias));
#define NEXT(i) asm volatile("sub.f32 %0, %1, %2;" : "=f"(acc[0][i]) : "f"(acc[1][i]), "f"(bias))
#pragma unroll 1
        for (int pp = 0; pp < 2; pp++) {
          TSG(pp);
          RowConst rc[2];
#pragma unroll
          for (int hf = 0; hf < 2; hf++) {
            const float2 st = lds64f_const(statv + pp * 512 + hf * 64);
            float rstd;
            asm("rsqrt.approx.ftz.f32 %0, %1;" : "=f"(rstd) : "f"(st.x));
            rc[hf] = {st.y, 0.7978845608f * rstd, 0.0356774081f * rstd * rstd * rstd, 0.5f * rstd * rstd};
          }
#pragma unroll
          for (int j2 = 0; j2 < 4; j2++) {
            uint32_t hv[4];
#pragma unroll
            for (int jj = 0; jj < 2; jj++) {
              const int jn = 2 * j2 + jj;
              const float2 cg = lds64f_const(csv + jn * 32), cu = lds64f_const(csv + 256 + jn * 32);
#pragma unroll
              for (int hf = 0; hf < 2; hf++) {
                const float nm = rc[hf].nmean;
                const float g0 = fmaf(nm, cg.x, acc[0][4 * jn + 2 * hf]), g1 = fmaf(nm, cg.y, acc[0][4 * jn + 2 * hf + 1]);
                const float u0 = fmaf(nm, cu.x, acc[0][32 + 4 * jn + 2 * hf]), u1 = fmaf(nm, cu.y, acc[0][33 + 4 * jn + 2 * hf]);
                hv[2 * jj + hf] = pack_bf16(g0 * u0 * gate_scale(g0, rc[hf]), g1 * u1 * gate_scale(g1, rc[hf]));
              }
            }
            stsm4(frag + 16384 + pp * 8192 + ((frag_x ^ (j2 * 2)) << 4), hv[0], hv[1], hv[2], hv[3]);
          }
          if (task < 4) {
            if (task == 2) {
#pragma unroll
              for (int j2 = 0; j2 < 4; j2++) {
                uint32_t hv[4];
#pragma unroll
                for (int jj = 0; jj < 2; jj++) {
                  const int jn = 16 + 2 * j2 + jj;
                  const float2 cs = lds64f_const(csv + jn * 32);
#pragma unroll
                  for (int hf = 0; hf < 2; hf++) {
                    const float nm = rc[hf].nmean;
                    const float t0 = fmaf(nm, cs.x, acc[0][4 * jn + 2 * hf]), t1 = fmaf(nm, cs.y, acc[0][4 * jn + 2 * hf + 1]);
                    hv[2 * jj + hf] = pack_bf16(t0 * gate_scale(t0, rc[hf]), t1 * gate_scale(t1, rc[hf]));
                  }
                }
                sts128(priv + pp * 8192 + j2 * 512, make_uint4(hv[0], hv[1], hv[2], hv[3]));
              }
            } else {
              uint4 park[4];
#pragma unroll
              for (int j2 = 0; j2 < 4; j2++) park[j2] = lds128(priv + pp * 8192 + j2 * 512);
              __syncwarp();
#pragma unroll
              for (int j2 = 0; j2 < 4; j2++) {
                const uint32_t pv[4] = {park[j2].x, park[j2].y, park[j2].z, park[j2].w};
                uint32_t hv[4];
#pragma unroll
                for (int jj = 0; jj < 2; jj++) {
                  const int jn = 16 + 2 * j2 + jj;
                  const float2 cs = lds64f_const(csv + jn * 32);
#pragma unroll
                  for (int hf = 0; hf < 2; hf++) {
                    const float nm = rc[hf].nmean;
                    const float t0 = fmaf(nm, cs.x, acc[0][4 * jn + 2 * hf]), t1 = fmaf(nm, cs.y, acc[0][4 * jn + 2 * hf + 1]);
                    asm("mul.rn.bf16x2 %0, %1, %2;" : "=r"(hv[2 * jj + hf]) : "r"(pack_bf16(t0, t1)), "r"(pv[2 * jj + hf]));
                  }
                }
                stsm4(frag + pp * 8192 + ((frag_x ^ (j2 * 2)) << 4), hv[0], hv[1], hv[2], hv[3]);
              }
            }
            if (pp == 1) break;
#pragma unroll
            for (int i = 64; i < 96; i++) NEXT(i);
          }
          if (pp == 1) break;
#pragma unroll
          for (int i = 0; i < 64; i++) NEXT(i);
        }
      }
      const int t3 = fresh_tid() & 127;
      uint4* part = SC_AT(part, bid * 1024 + (t3 & 96) * 8 + (t3 & 31));
      if (task == 2 && wg) {
#pragma unroll
        for (int k = 0; k < 8; k++) st_b128(part + k * 32, kPoison, kPoison, kPoison, kPoison);
      }
      fence_async_smem();
      nb_arrive(kNbPub + wg, 160);
      if (t == 0) TS(task == 4 ? 57 : 56 + task + wg * 2);
      if (task == 4) {
        mbar_wait(sb + kBars + 8 * kPartBar, 0);
        const bool none = lds32(sb + kPlan) == 0;
#pragma unroll 1
        for (int b = 1, spins = 0; b >= 0;) {
          uint4 v[4] = {};
          uint32_t top = 0;
          if (!none) {
#pragma unroll
            for (int k = 0; k < 4; k++) v[k] = ld_b128(part + (128 + k * 32));
          }
#pragma unroll
          for (int k = 0; k < 4; k++) {
            top = max(max(top, v[k].x), max(v[k].y, max(v[k].z, v[k].w)));
          }
          if (__any_sync(~0u, top == kPoison)) {
            if (++spins > 100000) __trap();
            __nanosleep(kPartNs);
            continue;
          }
#pragma unroll
          for (int k = 0; k < 4; k++) {
            uint32_t h[4];
            ldsm4(frag + 16384 + b * 8192 + ((frag_x ^ (k * 2)) << 4), h);
            asm("add.rn.bf16x2 %0, %0, %1;" : "+r"(v[k].x) : "r"(h[0]));
            asm("add.rn.bf16x2 %0, %0, %1;" : "+r"(v[k].y) : "r"(h[1]));
            asm("add.rn.bf16x2 %0, %0, %1;" : "+r"(v[k].z) : "r"(h[2]));
            asm("add.rn.bf16x2 %0, %0, %1;" : "+r"(v[k].w) : "r"(h[3]));
            sts128(stg + (t3 & 96) * 128 + (t3 & 31) * 16 + b * 2048 + k * 512, v[k]);
          }
          b--;
          part -= 128;
        }
        if (t == 0) TSK(56);
        nb_arrive(kNbPart, 256);
        break;
      }
      sx = mx = 0.f;
    }
  }
}

typedef CUresult (*EncodeTiledFn)(CUtensorMap*, CUtensorMapDataType, cuuint32_t, void*, const cuuint64_t*, const cuuint64_t*,
                                  const cuuint32_t*, const cuuint32_t*, CUtensorMapInterleave, CUtensorMapSwizzle,
                                  CUtensorMapL2promotion, CUtensorMapFloatOOBfill);

void encode(EncodeTiledFn fn, CUtensorMap* m, const void* base, int rank, cuuint64_t d0, cuuint64_t d1, cuuint64_t d2,
            cuuint64_t s1, cuuint64_t s2, cuuint32_t b2, cuuint32_t b1 = 64) {
  const cuuint64_t dims[3] = {d0, d1, d2}, strides[2] = {s1, s2};
  const cuuint32_t box[3] = {64, b1, b2}, es[3] = {1, 1, 1};
  fn(m, CU_TENSOR_MAP_DATA_TYPE_BFLOAT16, rank, const_cast<void*>(base), dims, strides, box, es, CU_TENSOR_MAP_INTERLEAVE_NONE,
     CU_TENSOR_MAP_SWIZZLE_128B, CU_TENSOR_MAP_L2_PROMOTION_L2_128B, CU_TENSOR_MAP_FLOAT_OOB_FILL_NONE);
}

}

extern "C" void kernel_launch(void* const* d_in, const int* in_sizes, int n_in, void* d_out, int out_size) {
  void* fnp = nullptr;
  cudaDriverEntryPointQueryResult qr;
  cudaGetDriverEntryPoint("cuTensorMapEncodeTiled", &fnp, cudaEnableDefault, &qr);
  EncodeTiledFn fn = (EncodeTiledFn)fnp;
  void *o, *h, *hh;
  cudaGetSymbolAddress(&o, g_o);
  cudaGetSymbolAddress(&h, g_h);
  cudaGetSymbolAddress(&hh, g_hh);

  Params p;
  Scratch* sc;
  cudaGetSymbolAddress((void**)&sc, g_scratch);
  encode(fn, &p.x, d_in[0], 3, kD, kS / 2, 2, 4 * kD, 2 * kD, 1, 128);
  encode(fn, &p.out, d_out, 3, kD, kS / 2, 2, 4 * kD, 2 * kD, 1, 16);
  encode(fn, &p.wqkv, d_in[1], 2, 3 * kD, kD, 1, 6 * kD, 0, 1);
  encode(fn, &p.wo, d_in[2], 2, kD, kD, 1, 2 * kD, 0, 1);
  encode(fn, &p.wd, d_in[6], 2, kD, kF, 1, 2 * kD, 0, 1);
  encode(fn, &p.wg, d_in[4], 2, kF, kD, 1, 2 * kF, 0, 1);
  encode(fn, &p.wu, d_in[5], 2, kF, kD, 1, 2 * kF, 0, 1);
  encode(fn, &p.o, o, 2, kD, kS, 1, 2 * kD, 0, 1, 128);
  encode(fn, &p.h, h, 2, kD, kS, 1, 2 * kD, 0, 1, 128);
  encode(fn, &p.hh, hh, 2, kF, kS, 1, 2 * kF, 0, 1, 128);
  encode(fn, &p.ost, o, 2, kD, kS, 1, 2 * kD, 0, 1);
  encode(fn, &p.o16, o, 2, kD, kS, 1, 2 * kD, 0, 1, 16);
  encode(fn, &p.h16, h, 2, kD, kS, 1, 2 * kD, 0, 1, 16);
  encode(fn, &p.hst, h, 2, kD, kS, 1, 2 * kD, 0, 1);
  encode(fn, &p.hhst, hh, 2, kF, kS, 1, 2 * kF, 0, 1);
  for (int c = 0; c < 8; c++) {
    for (int j = 0; j < 32; j++) p.g1[c][j] = g1_block(j, c) | (j >= 16 && (j < 20 || g1_block(j, c) >> 1 == c) ? kInPlace : 0);
    for (int j = 0; j < 16; j++) p.g2[c][j] = g2_block(j, c);
    for (int j = 0; j < 64; j++)
      p.g3[c][j] = g3_block(j, c) | ((0x000F000F003C000Full >> j & 1) && j != 28 + c ? kInPlace : 0) | g3_tile(j) << 5;
  }
  for (int i = 0; i < 56; i++)
    p.g4[i] = g4_block(i) | (i >= kFirstShared && i % 3 == 0 && i < kFirstShared + 3 * kMost ? kShared : 0) | (i % 24 == 0 ? kNextWave : 0);
  p.wop = (const uint4*)d_in[2];
  p.wgp = (const uint4*)d_in[4];
  p.wup = (const uint4*)d_in[5];

  int dev = 0, sms = 0;
  cudaGetDevice(&dev);
  cudaDeviceGetAttribute(&sms, cudaDevAttrMultiProcessorCount, dev);
  auto* kernel = sms == 132 ? fused_block_kernel<true> : fused_block_kernel<false>;
  cudaFuncSetAttribute(kernel, cudaFuncAttributeMaxDynamicSharedMemorySize, kSmemBytes);
  kernel<<<132, kThreads, kSmemBytes, cudaStreamPerThread>>>(sc, (const __nv_bfloat16*)d_in[0], (const __nv_bfloat16*)d_in[1],
                                                                  (__nv_bfloat16*)d_out, p);
}
```

```cpp
#include <cuda_runtime.h>
#include <cuda_bf16.h>
#include <cuda.h>
#include <stddef.h>
#include <stdint.h>

namespace {

constexpr int kS = 2048, kD = 1024, kF = 3584;
constexpr int kThreads = 384;

constexpr int kRing = 0;
constexpr int kStage = 163840;
constexpr int kAug = kStage + 16384;
constexpr int kOwn = kStage + 32768;
constexpr int kFill = kStage + 24576;
constexpr int kCs = kStage + 65536;
constexpr int kStat = kCs + 1536;
constexpr int kBars = kStat + 1024;
constexpr int kSmemBytes = kBars + 512;
constexpr int kResBar = 38;
constexpr int kAuxBar = 39;
constexpr int kStgBar = 41;
constexpr int kResFreeBar = 43;
constexpr int kStatBar = 44;
constexpr int kPartBar = 45;
constexpr int kWaveBar = 46;
constexpr int kHalfBar = 49;
constexpr int kSentBar = 51;
constexpr int kLandBar = 52;
constexpr int kNumBars = 58;
static_assert(kNumBars == 4 + 3 * 18, "barrier initialisation is split 4 + 3 x 18");
__host__ __device__ constexpr int bar_count(int i) {
  const int ph = i < 8 ? 0 : i < 18 ? 1 : i < 26 ? 2 : 3, base = ph * 9 - (ph & 1);
  return i < 38 ? (i - base < 4 + (ph & 1) + (ph == 3) ? 2 : ph == 0 ? 16 : 8) : i == kResFreeBar || i == kStatBar || (i >= kHalfBar && i < kLandBar) ? 4 : 1;
}
__host__ __device__ constexpr uint64_t bar_shifts(int first) {
  uint64_t m = 0;
  for (int i = 17; i >= 0; i--) {
    const int n = bar_count(first + i);
    m = m << 3 | (n == 16 ? 4 : n == 8 ? 3 : n >> 1);
  }
  return m;
}
constexpr int kScale = kBars + 464;
constexpr int kPlan = kBars + 472;
constexpr int kOnes = kBars + 480;
constexpr int kZero = kBars + 496;
constexpr int kRole = kBars + 508;
constexpr int kEpoch = kBars + 500;
__device__ __forceinline__ int ring_base(int ph) { return ph * 9 - (ph & 1); }
constexpr int kWide = 25;
constexpr int kFirstShared = 15;
constexpr int kNbOrder = 1;
constexpr int kNbWg = 3;
constexpr int kNbPub = 5;
constexpr int kNbWin = 7;
constexpr int kNbSelf = 13;
constexpr int kNbPart = 11;
constexpr int kNbHalo = 9;

constexpr int kFlO = 0;
constexpr int kFlPace = 1;
constexpr int kFlHH = 3;
constexpr int kFlRow = 32;
constexpr int kNumFlags = 16 * kFlRow;

constexpr int kPauseG1 = 7;
constexpr int kPauseG2 = 1;
constexpr int kAhead = 2;
constexpr int kTail = 4;
constexpr int kShare = 5;
constexpr int kPartAt = 2;
constexpr int kMost = 8;
constexpr int kBudget = 328;
constexpr int kRemain = 65500;
constexpr int kStepNs = 167;
constexpr int kDone = 3;
constexpr int kQuietAt = 48;
constexpr int kPfStep = 8;
constexpr int kBackoffNs = 200;
constexpr int kPaceNs = 300;
constexpr int kPartNs = 500;
constexpr int kFillNs = 500;
constexpr int kHaloNs = 150;
constexpr int kGateONs = 150;
constexpr int kGateHNs = 150;
constexpr int kHoldNs = 1200;
constexpr float kBias1 = 512.f, kBias3 = 32768.f;
constexpr int kSplit = 13;
constexpr int kSampleNs = 1000;
constexpr int kStatNs = 1500;

struct Scratch {
  uint32_t flags[kNumFlags];
  uint32_t epoch[32];
  uint4 stat1[kS];
  uint4 stat2[8 * kS];
  uint4 cs[7 * 8 * 96];
  uint2 finish[128];
  uint2 plan[16];
  uint4 halo[2 * 16 * 8 * 6 * 32];
  uint4 part[128 * 8 * 128];
};
struct Params {
  CUtensorMap x, wqkv, o, wo, h, wg, wu, hh, wd, out;
  CUtensorMap ost, hst, hhst;
  CUtensorMap o16, h16;
  const uint4 *wop, *wgp, *wup;
  uint8_t g1[8][32], g2[8][16], g3[8][64], g4[56];
};

__device__ __align__(256) __nv_bfloat16 g_o[kS * kD];
__device__ __align__(256) __nv_bfloat16 g_h[kS * kD];
__device__ __align__(256) __nv_bfloat16 g_hh[kS * kF];
__device__ __align__(256) Scratch g_scratch;

template <bool BY_SM>
__device__ __forceinline__ int role_id() {
  uint32_t sm;
  asm("mov.u32 %0, %%smid;" : "=r"(sm));
  const int tpc = (BY_SM ? sm : blockIdx.x) >> 1, rank = blockIdx.x & 1;
  if ((tpc | 1) == 61) return 8 + 2 * tpc + rank;
  const int u = tpc - 32, s7 = (u * 37) >> 8;
  const int g = tpc < 32 ? tpc & 7 : tpc < 60 ? 1 + u - 7 * s7 : 0, s = tpc < 32 ? tpc >> 3 : tpc < 60 ? 4 + s7 : tpc - 58;
  return (g * 2 + rank) * 8 + s;
}
#define TS(i) do { } while (0)
#define TSK(i) do { } while (0)
#define TSS(i) do { } while (0)
#define TST(i)
#define TSG(i)

__device__ __forceinline__ uint32_t smem_u32(const void* p) { return (uint32_t)__cvta_generic_to_shared(p); }
template <class T>
__device__ __forceinline__ T* plus(T* p, uint32_t n) {
  uint64_t r;
  asm("{\n.reg .b32 lo, hi;\nmov.b64 {lo, hi}, %1;\nadd.cc.u32 lo, lo, %2;\naddc.u32 hi, hi, 0;\nmov.b64 %0, {lo, hi};\n}\n"
      : "=l"(r) : "l"(p), "r"(n * (uint32_t)sizeof(T)));
  return (T*)r;
}
#define SC_AT(member, n) ((decltype(+sc->member))((char*)plus((decltype(+sc->member))sc, n) + offsetof(Scratch, member)))
__device__ __forceinline__ void mbar_init(uint32_t bar, uint32_t cnt) {
  asm volatile("mbarrier.init.shared::cta.b64 [%0], %1;" ::"r"(bar), "r"(cnt));
}
__device__ __forceinline__ void mbar_expect_tx(uint32_t bar, uint32_t bytes) {
  asm volatile("mbarrier.arrive.expect_tx.shared::cta.b64 _, [%0], %1;" ::"r"(bar), "r"(bytes) : "memory");
}
__device__ __forceinline__ uint32_t map_cta(uint32_t addr, uint32_t cta) {
  uint32_t r;
  asm("mapa.shared::cluster.u32 %0, %1, %2;" : "=r"(r) : "r"(addr), "r"(cta));
  return r;
}
__device__ __forceinline__ void mbar_arrive_cluster_if(uint32_t bar, bool cond) {
  asm volatile("{\n.reg .pred p;\nsetp.ne.u32 p, %1, 0;\n@p mbarrier.arrive.shared::cluster.b64 _, [%0];\n}\n"
               ::"r"(bar), "r"((uint32_t)cond) : "memory");
}
__device__ __forceinline__ void mbar_wait(uint32_t bar, uint32_t parity) {
  asm volatile("{\n.reg .pred p;\nLAB_WAIT:\nmbarrier.try_wait.parity.shared::cta.b64 p, [%0], %1;\n@!p bra LAB_WAIT;\n}\n"
               ::"r"(bar), "r"(parity) : "memory");
  return;
  asm volatile("{\n.reg .pred p;\n.reg .u32 c;\nmov.u32 c, 0;\n"
               "LAB_WAIT:\nmbarrier.try_wait.parity.shared::cta.b64 p, [%0], %1;\n@p bra LAB_DONE;\n"
               "add.u32 c, c, 1;\nsetp.lt.u32 p, c, 2000000;\n@p bra LAB_WAIT;\ntrap;\nLAB_DONE:\n}\n"
               ::"r"(bar), "r"(parity) : "memory");
}
__device__ __forceinline__ void mbar_arrive(uint32_t bar) {
  asm volatile("mbarrier.arrive.shared::cta.b64 _, [%0];" ::"r"(bar) : "memory");
}
__device__ __forceinline__ void flag_signal(uint32_t* flag) {
  asm volatile("red.release.gpu.global.add.u32 [%0], 1;" ::"l"(flag) : "memory");
}
__device__ __forceinline__ void st_b128(uint4* p, uint32_t a, uint32_t b, uint32_t c, uint32_t d) {
  asm volatile("{\n.reg .b128 t;\n.reg .b64 lo, hi;\nmov.b64 lo, {%1,%2};\nmov.b64 hi, {%3,%4};\nmov.b128 t, {lo, hi};\n"
               "st.relaxed.gpu.global.b128 [%0], t;\n}\n" ::"l"(p), "r"(a), "r"(b), "r"(c), "r"(d) : "memory");
}
__device__ __forceinline__ uint4 ld_b128(const uint4* p) {
  uint4 v;
  asm volatile("{\n.reg .b128 t;\n.reg .b64 lo, hi;\nld.relaxed.gpu.global.b128 t, [%4];\nmov.b128 {lo, hi}, t;\n"
               "mov.b64 {%0,%1}, lo;\nmov.b64 {%2,%3}, hi;\n}\n" : "=r"(v.x), "=r"(v.y), "=r"(v.z), "=r"(v.w) : "l"(p) : "memory");
  return v;
}
__device__ __forceinline__ uint32_t ld_epoch(Scratch* sc) {
  uint32_t v;
  asm volatile("ld.relaxed.gpu.global.u32 %0, [%1];" : "=r"(v) : "l"(sc->epoch) : "memory");
  return v + 1;
}
__device__ __forceinline__ void flag_wait(uint32_t* flag, uint32_t target) {
  asm volatile("{\n.reg .pred p;\n.reg .u32 c, v;\nmov.u32 c, 0;\n"
               "LAB_WAIT:\nld.relaxed.gpu.global.u32 v, [%0];\nsub.u32 v, v, %1;\nsetp.ge.s32 p, v, 0;\n@p bra LAB_DONE;\n"
               "add.u32 c, c, 1;\nsetp.lt.u32 p, c, 4000000;\n@p bra LAB_WAIT;\ntrap;\nLAB_DONE:\n}\n"
               ::"l"(flag), "r"(target) : "memory");
}
__device__ __forceinline__ void send_word(uint2* p, uint32_t v, uint32_t tag) {
  asm volatile("{\n.reg .b64 t;\nmov.b64 t, {%1, %2};\nst.relaxed.gpu.global.b64 [%0], t;\n}\n" ::"l"(p), "r"(v), "r"(tag) : "memory");
}
__device__ __forceinline__ uint32_t await_word(const uint2* p, uint32_t tag) {
  uint32_t v;
  asm volatile("{\n.reg .pred p;\n.reg .u32 c, g;\n.reg .b64 t;\nmov.u32 c, 0;\n"
               "LAB_WAIT:\nld.relaxed.gpu.global.b64 t, [%1];\nmov.b64 {%0, g}, t;\nsetp.eq.u32 p, g, %2;\n@p bra LAB_DONE;\n"
               "add.u32 c, c, 1;\nsetp.lt.u32 p, c, 4000000;\n@p bra LAB_WAIT;\ntrap;\nLAB_DONE:\n}\n"
               : "=r"(v) : "l"(p), "r"(tag) : "memory");
  return v;
}
__device__ __forceinline__ uint32_t global_ns() {
  uint32_t v;
  asm volatile("mov.u32 %0, %%globaltimer_lo;" : "=r"(v));
  return v;
}
__device__ __forceinline__ int fresh_tid() {
  int v;
  asm volatile("mov.u32 %0, %%tid.x;" : "=r"(v));
  return v;
}
constexpr uint32_t kPoison = 0xFFFFFFFFu;
__device__ __forceinline__ bool elect_one() {
  uint32_t p;
  asm volatile("{\n.reg .pred P;\nelect.sync _|P, 0xffffffff;\nselp.u32 %0, 1, 0, P;\n}\n" : "=r"(p));
  return p != 0;
}
__device__ __forceinline__ void fence_async() { asm volatile("fence.acquire.gpu;\nfence.proxy.async.global;" ::: "memory"); }
__device__ __forceinline__ void fence_async_smem() { asm volatile("fence.proxy.async.shared::cta;" ::: "memory"); }
__device__ __forceinline__ void nb_sync(int id, int n) { asm volatile("bar.sync %0, %1;" ::"r"(id), "r"(n) : "memory"); }
__device__ __forceinline__ void nb_arrive(int id, int n) { asm volatile("bar.arrive %0, %1;" ::"r"(id), "r"(n) : "memory"); }

__device__ __forceinline__ void tma2d(uint32_t dst, const CUtensorMap* m, int c0, int c1, uint32_t bar) {
  asm volatile("cp.async.bulk.tensor.2d.shared::cluster.global.mbarrier::complete_tx::bytes [%0], [%1, {%3, %4}], [%2];"
               ::"r"(dst), "l"(m), "r"(bar), "r"(c0), "r"(c1) : "memory");
}
__device__ __forceinline__ void tma2d_mc(uint32_t dst, const CUtensorMap* m, int c0, int c1, uint32_t bar) {
  asm volatile("cp.async.bulk.tensor.2d.shared::cluster.global.mbarrier::complete_tx::bytes.multicast::cluster"
               " [%0], [%1, {%3, %4}], [%2], %5;"
               ::"r"(dst), "l"(m), "r"(bar), "r"(c0), "r"(c1), "h"((uint16_t)3) : "memory");
}
__device__ __forceinline__ void tma3d(uint32_t dst, const CUtensorMap* m, int c0, int c1, int c2, uint32_t bar) {
  asm volatile("cp.async.bulk.tensor.3d.shared::cluster.global.mbarrier::complete_tx::bytes [%0], [%1, {%3, %4, %5}], [%2];"
               ::"r"(dst), "l"(m), "r"(bar), "r"(c0), "r"(c1), "r"(c2) : "memory");
}
__device__ __forceinline__ void tma_store2d(const CUtensorMap* m, uint32_t src, int c0, int c1) {
  asm volatile("cp.async.bulk.tensor.2d.global.shared::cta.bulk_group [%0, {%2, %3}], [%1];"
               ::"l"(m), "r"(src), "r"(c0), "r"(c1) : "memory");
}
__device__ __forceinline__ void tma_store3d(const CUtensorMap* m, uint32_t src, int c0, int c1, int c2) {
  asm volatile("cp.async.bulk.tensor.3d.global.shared::cta.bulk_group [%0, {%2, %3, %4}], [%1];"
               ::"l"(m), "r"(src), "r"(c0), "r"(c1), "r"(c2) : "memory");
}
__device__ __forceinline__ void tma_prefetch2d(const CUtensorMap* m, int c0, int c1) {
  asm volatile("cp.async.bulk.prefetch.tensor.2d.L2.global [%0, {%1, %2}];" ::"l"(m), "r"(c0), "r"(c1) : "memory");
}
__device__ __forceinline__ void prefetch_map(const CUtensorMap* m) { asm volatile("prefetch.tensormap [%0];" ::"l"(m) : "memory"); }
__device__ __forceinline__ void bulk_commit() { asm volatile("cp.async.bulk.commit_group;" ::: "memory"); }
__device__ __forceinline__ void bulk_wait_all() { asm volatile("cp.async.bulk.wait_group 0;" ::: "memory"); }
__device__ __forceinline__ void bulk_wait_read() { asm volatile("cp.async.bulk.wait_group.read 0;" ::: "memory"); }
__device__ __forceinline__ void prefetch_l2(const void* p) { asm volatile("prefetch.global.L2 [%0];" ::"l"(p)); }
__device__ __forceinline__ void cluster_arrive() { asm volatile("barrier.cluster.arrive.relaxed.aligned;" ::: "memory"); }
__device__ __forceinline__ void cluster_wait() { asm volatile("barrier.cluster.wait.aligned;" ::: "memory"); }

__device__ __forceinline__ void wg_fence() { asm volatile("wgmma.fence.sync.aligned;" ::: "memory"); }
__device__ __forceinline__ void wg_commit() { asm volatile("wgmma.commit_group.sync.aligned;" ::: "memory"); }
template <int N> __device__ __forceinline__ void wg_wait() { asm volatile("wgmma.wait_group.sync.aligned %0;" ::"n"(N) : "memory"); }
__device__ __forceinline__ uint32_t desc_lo(uint32_t addr, uint32_t lbo) { return ((addr & 0x3FFFF) >> 4) | ((lbo >> 4) << 16); }
__device__ __forceinline__ uint64_t desc(uint32_t lo) { return (uint64_t)lo | (0x40000040ull << 32); }
__device__ __forceinline__ uint64_t desc_kept(uint32_t lo, uint32_t sb) { return (uint64_t)lo | (uint64_t)(0x40000040u | sb >> 31) << 32; }
constexpr int kToB = (16384 >> 4) + ((8192 - 16) >> 4 << 16);

__device__ __forceinline__ void wgmma_n128(float (&d)[96], uint64_t da, uint64_t db, int add = 1) {
  asm volatile(
      "{\n.reg .pred p;\nsetp.ne.b32 p, %66, 0;\n"
      "wgmma.mma_async.sync.aligned.m64n128k16.f32.bf16.bf16 {"
      "%0, %1, %2, %3, %4, %5, %6, %7, %8, %9, %10, %11, %12, %13, %14, %15, "
      "%16, %17, %18, %19, %20, %21, %22, %23, %24, %25, %26, %27, %28, %29, %30, %31, "
      "%32, %33, %34, %35, %36, %37, %38, %39, %40, %41, %42, %43, %44, %45, %46, %47, "
      "%48, %49, %50, %51, %52, %53, %54, %55, %56, %57, %58, %59, %60, %61, %62, %63}, "
      "%64, %65, p, 1, 1, 0, 1;\n}\n"
      :
        "+f"(d[0]), "+f"(d[1]), "+f"(d[2]), "+f"(d[3]), "+f"(d[4]), "+f"(d[5]), "+f"(d[6]), "+f"(d[7]),
        "+f"(d[8]), "+f"(d[9]), "+f"(d[10]), "+f"(d[11]), "+f"(d[12]), "+f"(d[13]), "+f"(d[14]), "+f"(d[15]),
        "+f"(d[16]), "+f"(d[17]), "+f"(d[18]), "+f"(d[19]), "+f"(d[20]), "+f"(d[21]), "+f"(d[22]), "+f"(d[23]),
        "+f"(d[24]), "+f"(d[25]), "+f"(d[26]), "+f"(d[27]), "+f"(d[28]), "+f"(d[29]), "+f"(d[30]), "+f"(d[31]),
        "+f"(d[32]), "+f"(d[33]), "+f"(d[34]), "+f"(d[35]), "+f"(d[36]), "+f"(d[37]), "+f"(d[38]), "+f"(d[39]),
        "+f"(d[40]), "+f"(d[41]), "+f"(d[42]), "+f"(d[43]), "+f"(d[44]), "+f"(d[45]), "+f"(d[46]), "+f"(d[47]),
        "+f"(d[48]), "+f"(d[49]), "+f"(d[50]), "+f"(d[51]), "+f"(d[52]), "+f"(d[53]), "+f"(d[54]), "+f"(d[55]),
        "+f"(d[56]), "+f"(d[57]), "+f"(d[58]), "+f"(d[59]), "+f"(d[60]), "+f"(d[61]), "+f"(d[62]), "+f"(d[63])
      : "l"(da), "l"(db), "r"(add));
}

__device__ __forceinline__ void wgmma_n192(float (&d)[96], uint64_t da, uint64_t db, int add = 1) {
  asm volatile(
      "{\n.reg .pred p;\nsetp.ne.b32 p, %98, 0;\n"
      "wgmma.mma_async.sync.aligned.m64n192k16.f32.bf16.bf16 {"
      "%0, %1, %2, %3, %4, %5, %6, %7, %8, %9, %10, %11, %12, %13, %14, %15, "
      "%16, %17, %18, %19, %20, %21, %22, %23, %24, %25, %26, %27, %28, %29, %30, %31, "
      "%32, %33, %34, %35, %36, %37, %38, %39, %40, %41, %42, %43, %44, %45, %46, %47, "
      "%48, %49, %50, %51, %52, %53, %54, %55, %56, %57, %58, %59, %60, %61, %62, %63, "
      "%64, %65, %66, %67, %68, %69, %70, %71, %72, %73, %74, %75, %76, %77, %78, %79, "
      "%80, %81, %82, %83, %84, %85, %86, %87, %88, %89, %90, %91, %92, %93, %94, %95}, "
      "%96, %97, p, 1, 1, 0, 1;\n}\n"
      :
        "+f"(d[0]), "+f"(d[1]), "+f"(d[2]), "+f"(d[3]), "+f"(d[4]), "+f"(d[5]), "+f"(d[6]), "+f"(d[7]),
        "+f"(d[8]), "+f"(d[9]), "+f"(d[10]), "+f"(d[11]), "+f"(d[12]), "+f"(d[13]), "+f"(d[14]), "+f"(d[15]),
        "+f"(d[16]), "+f"(d[17]), "+f"(d[18]), "+f"(d[19]), "+f"(d[20]), "+f"(d[21]), "+f"(d[22]), "+f"(d[23]),
        "+f"(d[24]), "+f"(d[25]), "+f"(d[26]), "+f"(d[27]), "+f"(d[28]), "+f"(d[29]), "+f"(d[30]), "+f"(d[31]),
        "+f"(d[32]), "+f"(d[33]), "+f"(d[34]), "+f"(d[35]), "+f"(d[36]), "+f"(d[37]), "+f"(d[38]), "+f"(d[39]),
        "+f"(d[40]), "+f"(d[41]), "+f"(d[42]), "+f"(d[43]), "+f"(d[44]), "+f"(d[45]), "+f"(d[46]), "+f"(d[47]),
        "+f"(d[48]), "+f"(d[49]), "+f"(d[50]), "+f"(d[51]), "+f"(d[52]), "+f"(d[53]), "+f"(d[54]), "+f"(d[55]),
        "+f"(d[56]), "+f"(d[57]), "+f"(d[58]), "+f"(d[59]), "+f"(d[60]), "+f"(d[61]), "+f"(d[62]), "+f"(d[63]),
        "+f"(d[64]), "+f"(d[65]), "+f"(d[66]), "+f"(d[67]), "+f"(d[68]), "+f"(d[69]), "+f"(d[70]), "+f"(d[71]),
        "+f"(d[72]), "+f"(d[73]), "+f"(d[74]), "+f"(d[75]), "+f"(d[76]), "+f"(d[77]), "+f"(d[78]), "+f"(d[79]),
        "+f"(d[80]), "+f"(d[81]), "+f"(d[82]), "+f"(d[83]), "+f"(d[84]), "+f"(d[85]), "+f"(d[86]), "+f"(d[87]),
        "+f"(d[88]), "+f"(d[89]), "+f"(d[90]), "+f"(d[91]), "+f"(d[92]), "+f"(d[93]), "+f"(d[94]), "+f"(d[95])
      : "l"(da), "l"(db), "r"(add));
}

__device__ __forceinline__ void wgmma_n192_any(float (&d)[96], uint64_t da, uint64_t db) {
  asm volatile(
      "wgmma.mma_async.sync.aligned.m64n192k16.f32.bf16.bf16 {"
      "%0, %1, %2, %3, %4, %5, %6, %7, %8, %9, %10, %11, %12, %13, %14, %15, "
      "%16, %17, %18, %19, %20, %21, %22, %23, %24, %25, %26, %27, %28, %29, %30, %31, "
      "%32, %33, %34, %35, %36, %37, %38, %39, %40, %41, %42, %43, %44, %45, %46, %47, "
      "%48, %49, %50, %51, %52, %53, %54, %55, %56, %57, %58, %59, %60, %61, %62, %63, "
      "%64, %65, %66, %67, %68, %69, %70, %71, %72, %73, %74, %75, %76, %77, %78, %79, "
      "%80, %81, %82, %83, %84, %85, %86, %87, %88, %89, %90, %91, %92, %93, %94, %95}, "
      "%96, %97, 0, 1, 1, 0, 1;\n"
      :
        "=f"(d[0]), "=f"(d[1]), "=f"(d[2]), "=f"(d[3]), "=f"(d[4]), "=f"(d[5]), "=f"(d[6]), "=f"(d[7]),
        "=f"(d[8]), "=f"(d[9]), "=f"(d[10]), "=f"(d[11]), "=f"(d[12]), "=f"(d[13]), "=f"(d[14]), "=f"(d[15]),
        "=f"(d[16]), "=f"(d[17]), "=f"(d[18]), "=f"(d[19]), "=f"(d[20]), "=f"(d[21]), "=f"(d[22]), "=f"(d[23]),
        "=f"(d[24]), "=f"(d[25]), "=f"(d[26]), "=f"(d[27]), "=f"(d[28]), "=f"(d[29]), "=f"(d[30]), "=f"(d[31]),
        "=f"(d[32]), "=f"(d[33]), "=f"(d[34]), "=f"(d[35]), "=f"(d[36]), "=f"(d[37]), "=f"(d[38]), "=f"(d[39]),
        "=f"(d[40]), "=f"(d[41]), "=f"(d[42]), "=f"(d[43]), "=f"(d[44]), "=f"(d[45]), "=f"(d[46]), "=f"(d[47]),
        "=f"(d[48]), "=f"(d[49]), "=f"(d[50]), "=f"(d[51]), "=f"(d[52]), "=f"(d[53]), "=f"(d[54]), "=f"(d[55]),
        "=f"(d[56]), "=f"(d[57]), "=f"(d[58]), "=f"(d[59]), "=f"(d[60]), "=f"(d[61]), "=f"(d[62]), "=f"(d[63]),
        "=f"(d[64]), "=f"(d[65]), "=f"(d[66]), "=f"(d[67]), "=f"(d[68]), "=f"(d[69]), "=f"(d[70]), "=f"(d[71]),
        "=f"(d[72]), "=f"(d[73]), "=f"(d[74]), "=f"(d[75]), "=f"(d[76]), "=f"(d[77]), "=f"(d[78]), "=f"(d[79]),
        "=f"(d[80]), "=f"(d[81]), "=f"(d[82]), "=f"(d[83]), "=f"(d[84]), "=f"(d[85]), "=f"(d[86]), "=f"(d[87]),
        "=f"(d[88]), "=f"(d[89]), "=f"(d[90]), "=f"(d[91]), "=f"(d[92]), "=f"(d[93]), "=f"(d[94]), "=f"(d[95])
      : "l"(da), "l"(db));
}

__device__ __forceinline__ void wgmma_n192_rs(float (&d)[96], uint32_t a0, uint32_t a1, uint32_t a23, uint64_t db) {
  asm volatile(
      "wgmma.mma_async.sync.aligned.m64n192k16.f32.bf16.bf16 {"
      "%0, %1, %2, %3, %4, %5, %6, %7, %8, %9, %10, %11, %12, %13, %14, %15, "
      "%16, %17, %18, %19, %20, %21, %22, %23, %24, %25, %26, %27, %28, %29, %30, %31, "
      "%32, %33, %34, %35, %36, %37, %38, %39, %40, %41, %42, %43, %44, %45, %46, %47, "
      "%48, %49, %50, %51, %52, %53, %54, %55, %56, %57, %58, %59, %60, %61, %62, %63, "
      "%64, %65, %66, %67, %68, %69, %70, %71, %72, %73, %74, %75, %76, %77, %78, %79, "
      "%80, %81, %82, %83, %84, %85, %86, %87, %88, %89, %90, %91, %92, %93, %94, %95}, "
      "{%96, %97, %98, %98}, %99, 1, 1, 1, 1;\n"
      :
        "+f"(d[0]), "+f"(d[1]), "+f"(d[2]), "+f"(d[3]), "+f"(d[4]), "+f"(d[5]), "+f"(d[6]), "+f"(d[7]),
        "+f"(d[8]), "+f"(d[9]), "+f"(d[10]), "+f"(d[11]), "+f"(d[12]), "+f"(d[13]), "+f"(d[14]), "+f"(d[15]),
        "+f"(d[16]), "+f"(d[17]), "+f"(d[18]), "+f"(d[19]), "+f"(d[20]), "+f"(d[21]), "+f"(d[22]), "+f"(d[23]),
        "+f"(d[24]), "+f"(d[25]), "+f"(d[26]), "+f"(d[27]), "+f"(d[28]), "+f"(d[29]), "+f"(d[30]), "+f"(d[31]),
        "+f"(d[32]), "+f"(d[33]), "+f"(d[34]), "+f"(d[35]), "+f"(d[36]), "+f"(d[37]), "+f"(d[38]), "+f"(d[39]),
        "+f"(d[40]), "+f"(d[41]), "+f"(d[42]), "+f"(d[43]), "+f"(d[44]), "+f"(d[45]), "+f"(d[46]), "+f"(d[47]),
        "+f"(d[48]), "+f"(d[49]), "+f"(d[50]), "+f"(d[51]), "+f"(d[52]), "+f"(d[53]), "+f"(d[54]), "+f"(d[55]),
        "+f"(d[56]), "+f"(d[57]), "+f"(d[58]), "+f"(d[59]), "+f"(d[60]), "+f"(d[61]), "+f"(d[62]), "+f"(d[63]),
        "+f"(d[64]), "+f"(d[65]), "+f"(d[66]), "+f"(d[67]), "+f"(d[68]), "+f"(d[69]), "+f"(d[70]), "+f"(d[71]),
        "+f"(d[72]), "+f"(d[73]), "+f"(d[74]), "+f"(d[75]), "+f"(d[76]), "+f"(d[77]), "+f"(d[78]), "+f"(d[79]),
        "+f"(d[80]), "+f"(d[81]), "+f"(d[82]), "+f"(d[83]), "+f"(d[84]), "+f"(d[85]), "+f"(d[86]), "+f"(d[87]),
        "+f"(d[88]), "+f"(d[89]), "+f"(d[90]), "+f"(d[91]), "+f"(d[92]), "+f"(d[93]), "+f"(d[94]), "+f"(d[95])
      : "r"(a0), "r"(a1), "r"(a23), "l"(db));
}

__device__ __forceinline__ uint32_t pack_bf16(float lo, float hi) {
  uint32_t r;
  asm("cvt.rn.bf16x2.f32 %0, %1, %2;" : "=r"(r) : "f"(hi), "f"(lo));
  return r;
}
__device__ __forceinline__ float bf_lo(uint32_t v) { return __uint_as_float(v << 16); }
__device__ __forceinline__ float bf_hi(uint32_t v) { return __uint_as_float(v & 0xFFFF0000u); }
__device__ __forceinline__ float ex2(float x) { float r; asm("ex2.approx.ftz.f32 %0, %1;" : "=f"(r) : "f"(x)); return r; }
__device__ __forceinline__ float rcp(float x) { float r; asm("rcp.approx.ftz.f32 %0, %1;" : "=f"(r) : "f"(x)); return r; }
__device__ __forceinline__ uint32_t movm(uint32_t a) {
  uint32_t d;
  asm volatile("movmatrix.sync.aligned.m8n8.trans.b16 %0, %1;" : "=r"(d) : "r"(a));
  return d;
}
__device__ __forceinline__ void mma16816(float (&c)[4], uint32_t a0, uint32_t a1, uint32_t a2, uint32_t a3, uint32_t b0, uint32_t b1) {
  asm volatile("mma.sync.aligned.m16n8k16.row.col.f32.bf16.bf16.f32 {%0,%1,%2,%3}, {%4,%5,%6,%7}, {%8,%9}, {%0,%1,%2,%3};"
               : "+f"(c[0]), "+f"(c[1]), "+f"(c[2]), "+f"(c[3]) : "r"(a0), "r"(a1), "r"(a2), "r"(a3), "r"(b0), "r"(b1));
}
__device__ __forceinline__ void mma1688(float (&c)[4], uint32_t a0, uint32_t a1, uint32_t b0) {
  asm volatile("mma.sync.aligned.m16n8k8.row.col.f32.bf16.bf16.f32 {%0,%1,%2,%3}, {%4,%5}, {%6}, {%0,%1,%2,%3};"
               : "+f"(c[0]), "+f"(c[1]), "+f"(c[2]), "+f"(c[3]) : "r"(a0), "r"(a1), "r"(b0));
}
__device__ __forceinline__ void stsm4(uint32_t addr, uint32_t a, uint32_t b, uint32_t c, uint32_t d) {
  asm volatile("stmatrix.sync.aligned.m8n8.x4.shared.b16 [%0], {%1,%2,%3,%4};" ::"r"(addr), "r"(a), "r"(b), "r"(c), "r"(d) : "memory");
}
__device__ __forceinline__ void stsm4_t(uint32_t addr, uint32_t a, uint32_t b, uint32_t c, uint32_t d) {
  asm volatile("stmatrix.sync.aligned.m8n8.x4.trans.shared.b16 [%0], {%1,%2,%3,%4};" ::"r"(addr), "r"(a), "r"(b), "r"(c), "r"(d) : "memory");
}
__device__ __forceinline__ void ldsm4(uint32_t addr, uint32_t (&v)[4]) {
  asm volatile("ldmatrix.sync.aligned.m8n8.x4.shared.b16 {%0,%1,%2,%3}, [%4];"
               : "=r"(v[0]), "=r"(v[1]), "=r"(v[2]), "=r"(v[3]) : "r"(addr) : "memory");
}
__device__ __forceinline__ void sts128(uint32_t addr, uint4 v) {
  asm volatile("st.shared.v4.b32 [%0], {%1,%2,%3,%4};" ::"r"(addr), "r"(v.x), "r"(v.y), "r"(v.z), "r"(v.w) : "memory");
}
__device__ __forceinline__ uint4 lds128(uint32_t addr) {
  uint4 v;
  asm volatile("ld.shared.v4.b32 {%0,%1,%2,%3}, [%4];" : "=r"(v.x), "=r"(v.y), "=r"(v.z), "=r"(v.w) : "r"(addr) : "memory");
  return v;
}
__device__ __forceinline__ void sts64(uint32_t addr, uint32_t a, uint32_t b) {
  asm volatile("st.shared.v2.b32 [%0], {%1,%2};" ::"r"(addr), "r"(a), "r"(b) : "memory");
}
__device__ __forceinline__ void sts32(uint32_t addr, uint32_t a) { asm volatile("st.shared.b32 [%0], %1;" ::"r"(addr), "r"(a) : "memory"); }
__device__ __forceinline__ uint32_t lds32(uint32_t addr) {
  uint32_t v;
  asm volatile("ld.shared.b32 %0, [%1];" : "=r"(v) : "r"(addr) : "memory");
  return v;
}
__device__ __forceinline__ float2 lds64f_const(uint32_t addr) {
  float2 v;
  asm("ld.shared.v2.f32 {%0,%1}, [%2];" : "=f"(v.x), "=f"(v.y) : "r"(addr));
  return v;
}
template <int N, bool PAIR>
__device__ __forceinline__ void load_tagged(uint3 (&out)[N], const uint4* src, int stride, uint32_t tag, const uint4* last = nullptr) {
  uint32_t bad;
  int spins = 0;
#pragma unroll 1
  do {
    if (++spins > 2000000) __trap();
    bad = 0;
#pragma unroll
    for (int i = 0; i < N; i++) {
      const uint4 v = ld_b128(N == 5 && i == 4 ? last : src + i * stride);
      out[i] = make_uint3(v.x, v.y, v.z);
      bad |= (v.w ^ tag) | (PAIR ? v.z ^ tag : 0);
    }
    if (N == 4) bad = __any_sync(~0u, bad != 0);
    if (bad) __nanosleep(kBackoffNs);
  } while (bad);
}
__device__ __forceinline__ void sts64f(uint32_t addr, float2 v) { sts64(addr, __float_as_uint(v.x), __float_as_uint(v.y)); }
__device__ __forceinline__ float bf_rest(float v) { return v - __uint_as_float(__float_as_uint(v) & 0xFFFF0000u); }
__device__ __forceinline__ uint32_t bf_upper(float lo, float hi) { return __byte_perm(__float_as_uint(lo), __float_as_uint(hi), 0x7632); }
__device__ __forceinline__ float low_peak(uint4 v) {
  asm("max.xorsign.abs.bf16x2 %0, %0, %1;" : "+r"(v.x) : "r"(v.y));
  asm("max.xorsign.abs.bf16x2 %0, %0, %1;" : "+r"(v.z) : "r"(v.w));
  asm("max.xorsign.abs.bf16x2 %0, %0, %1;" : "+r"(v.x) : "r"(v.z));
  asm("max.xorsign.abs.bf16x2 %0, %0, %1;" : "+r"(v.x) : "r"(v.x << 16));
  return __uint_as_float(__reduce_min_sync(~0u, v.x & 0x7FFF0000u));
}
__device__ __forceinline__ float bias_at(float v) { return __uint_as_float((__float_as_uint(fminf(v, 1e37f)) & 0x7F800000u) | 0x00400000u); }
struct RowConst {
  float nmean, k0, k1, half;
};
__device__ __forceinline__ float gate_scale(float t, const RowConst& k) {
  float th;
  asm("tanh.approx.f32 %0, %1;" : "=f"(th) : "f"(t * fmaf(t * t, k.k1, k.k0)));
  return fmaf(th, k.half, k.half);
}

template <int N>
__device__ __forceinline__ void mma_k16(float (&acc)[2][96], uint32_t a, uint32_t b, int kk, int add = 1) {
#pragma unroll
  for (int m = 0; m < 2; m++) {
    const uint64_t da = desc(a) + (m * 512 + kk * 2), db = desc(b) + kk * 128;
    if (N == 128) wgmma_n128(acc[m], da, db); else wgmma_n192(acc[m], da, db, add);
  }
}

__device__ __forceinline__ void stage_quarter(const float* acc, uint32_t frag, uint32_t frag_x, int b, const uint4* add = nullptr) {
#pragma unroll
  for (int j = 0; j < 4; j++) {
    const float* v = acc + 8 * j;
    uint32_t h[4] = {pack_bf16(v[0], v[1]), pack_bf16(v[2], v[3]), pack_bf16(v[4], v[5]), pack_bf16(v[6], v[7])};
    if (add) {
      const uint32_t a[4] = {add[j].x, add[j].y, add[j].z, add[j].w};
#pragma unroll
      for (int e = 0; e < 4; e++) asm("add.rn.bf16x2 %0, %0, %1;" : "+r"(h[e]) : "r"(a[e]));
    }
    stsm4(frag + b * 8192 + ((frag_x ^ (j * 2)) << 4), h[0], h[1], h[2], h[3]);
  }
}

inline int g1_block(int j, int c) { return j < 16 ? j : ((j + 12) & 15) ^ (c == 5 && j >= 28 ? 2 : 0); }
inline int g2_block(int j, int c) { return j < 8 ? j : j == 8 ? 8 + c : j - (j - 9 < c); }
inline int g3_tile(int j) { return j < 4 ? j >> 1 : j < 18 ? 0 : j >> 4; }
inline int g3_block(int j, int c) {
  const int i = j < 32 ? (j < 16 ? 0xDCBA976543218080ull : 0x7654321BA9FEDCFEull) >> 4 * (j & 15) : j + (~j >> 2 & 4), o = i & 7;
  return 2 * (j < 32 && (o == c || o == 0) ? c - o : o) + (i >> 3 & 1);
}
__device__ __forceinline__ bool g3_is_up(int tile, int a) { return a == 1 || (a == 2 && tile >= 2); }
__device__ __forceinline__ int g3_atom(int tile, int a, int c) { return c * 7 + (tile & 1) * 3 + (a == 2 ? 1 : tile == 4 ? 6 : tile & 2); }
inline int g4_block(int i) {
  const int n = i * 43 >> 7, j = i - 3 * n, m = j ? n : n + (16 - kFirstShared / 3);
  return i < 48 ? 7 * (m & 7) + 3 * (m >> 3 & 1) + j : 7 * i - 330;
}

constexpr int kInPlace = 16, kShared = 64, kNextWave = 128;

template <int N, int TAIL>
__device__ __forceinline__ void mainloop(Scratch* sc, float (&acc)[2][96], uint32_t sb, int ph, int j0, int nsteps, int pause_at, bool last,
                                         bool hand_over, bool local, int wg, int own = -1, const CUtensorMap* out = nullptr, int out_col = 0,
                                         int out_row = 0, int warp = 0, __nv_bfloat16* outp = nullptr) {
  constexpr int NSLOT = N == 128 ? 5 : 4, SLOT = N == 128 ? 32768 : 40960;
  const int lane = fresh_tid() & 31;
  const uint32_t full = sb + kBars + 8 * ring_base(ph);
  const uint32_t empty = map_cta(full + 8 * (NSLOT + (ph == 3)), lane & 1);
  const uint32_t ring = desc_lo(sb + kRing, 16);
  int bi = j0 % NSLOT, par = (j0 / NSLOT) & 1;
  const int release_end = lane < (N == 192 && !hand_over ? 4 : 2) ? (last ? nsteps - 1 - NSLOT : nsteps) : 0;
  uint32_t rel = empty;
  const uint32_t special = ph == 0 && wg == 0 ? 3 : pause_at < 0 ? 1 : 1 | 2 << pause_at;
  int i = 0;
#pragma unroll 1
  for (;;) {
  const int end = TAIL <= 0 ? nsteps : !own ? nsteps - TAIL - 1 : i ? i + 2 : kFirstShared;
#pragma unroll 1
  do {
    uint32_t a = ring + bi * (SLOT >> 4), b = a + kToB;
    if (TAIL > 0 ? i == 0 : special >> i & 1) {
      if (i == 0) nb_sync(kNbOrder + wg, ph == 0 && wg == 0 ? 160 : 256);
      else if (ph == 0 && wg == 0) cluster_wait();
      else if (ph < 2) nb_sync(kNbWin + 1, 256);
    }
    if (N == 192 && local) {
      a = ring + ((kStage + i * 16384) >> 4);
      b = ring + bi * (32768 >> 4) + desc_lo(32768, 8192) - desc_lo(0, 16);
    }
    if (ph == 0 && i >> 1 == own) a = ring + ((kOwn + (i & 1) * 16384) >> 4);
    if (ph == 1 && i == 8) a = ring + ((kStage + 32768) >> 4);
    mbar_wait(full + 8 * bi, par);
    if (N == 192 && local) mbar_wait(sb + kBars + 8 * (kHalfBar + i), 0);
    const bool release = (uint32_t)(i - 1) < (uint32_t)release_end;
    wg_fence();
    mma_k16<N>(acc, a, b, 0, ph == 0 ? i | wg : 1);
    mma_k16<N>(acc, a, b, 1);
    wg_commit();
    wg_wait<1>();
    mbar_arrive_cluster_if(rel, release);
    wg_fence();
    mma_k16<N>(acc, a, b, 2);
    mma_k16<N>(acc, a, b, 3);
    wg_commit();
    rel = empty + 8 * bi;
    if (++bi == NSLOT + (TAIL > 0 && i >= kWide - 16)) { bi = 0; par ^= 1; }
    if (ph < 2 && i == pause_at) nb_arrive(kNbWin, 256);
  } while (++i < end);
  if (TAIL <= 0 || own-- == 0) break;
  const uint32_t a = ring + bi * (SLOT >> 4);
  mbar_wait(full + 8 * bi, par);
  wg_fence();
#pragma unroll
  for (int k = 0; k < 4; k++) wgmma_n128(acc[1], desc(a) + (512 + k * 2), desc(a + kToB) + k * 128);
  wg_commit();
  wg_wait<1>();
  mbar_arrive_cluster_if(rel, lane < 2);
  rel = empty + 8 * bi;
  if (++bi == NSLOT + 1) { bi = 0; par ^= 1; }
  i++;
  }
  if (TAIL < 0) return;
  if (TAIL > 0) {
    uint32_t at[TAIL + 2];
    bi = par = 0;
    const int t = fresh_tid() & 127;
    uint32_t frag = sb + kStage + ((t >> 5) * 16 + (t & 15)) * 128, frag_x = ((t >> 4) & 1) ^ (t & 7);
    const uint32_t back = sb + kStage + (t >> 5) * 2048 + ((t >> 3) & 3) * 128, back_x = ((t ^ (t >> 3 & 3)) & 7) << 4;
    outp = plus(outp, (2 * (out_row + (t >> 5) * 16 + ((t >> 3) & 3)) + (blockIdx.x & 1)) * kD + out_col + (t & 7) * 8);
    auto rows = [&](int m, int i0, int i1) {
      wg_fence();
#pragma unroll
      for (int i = 4 * i0; i < 4 * i1; i++)
        wgmma_n128(acc[m], desc_kept(ring, sb) + (at[i >> 2] + m * 512 + (i & 3) * 2), desc_kept(ring, sb) + (at[i >> 2] + kToB + (i & 3) * 128));
      wg_commit();
    };
    auto last_rows = [&](int i0, int i1) { rows(1, i0, i1); };
    uint4 part[8];
#pragma unroll
    for (int i = 0; i <= TAIL; i++) {
      at[i] = bi * (SLOT >> 4);
      mbar_wait(full + 8 * bi, par);
      if (++bi == NSLOT) { bi = 0; par ^= 1; }
      rows(0, i, i + 1);
      if (i == kPartAt) nb_sync(kNbPart, 256);
      if (i == kPartAt || i == kPartAt + 1) {
#pragma unroll
        for (int k = 4 * (i - kPartAt); k < 4 * (i - kPartAt + 1); k++) part[k] = lds128(sb + kStage + 32768 + (t >> 5) * 4096 + (t & 31) * 16 + k * 512);
      }
    }
    last_rows(0, 2);
#pragma unroll
    for (int b = 0; b < 4; b++) {
      if (b == 0) wg_wait<1>();
      if (b == 1) last_rows(3, 4);
      if (b == 2) wg_wait<0>();
      if (!(b & 1)) {
#pragma unroll
        for (int i = 0; i < 64; i++) asm volatile("" : "+f"(acc[b >> 1][i])::"memory");
        if (t == 0) TSS(b);
      }
      stage_quarter(&acc[b >> 1][32 * (b & 1)], frag, frag_x, b, b < 2 ? &part[4 * b] : nullptr);
      if (b == 3) {
        __syncwarp();
        uint4 v[4];
#pragma unroll
        for (int i = 0; i < 4; i++) v[i] = lds128(back + b * 8192 + i * 512 + ((i & 1) ? back_x ^ 64 : back_x));
#pragma unroll
        for (int i = 0; i < 4; i++) __stcs((uint4*)(outp + ((b >> 1) * 128 + i * 8) * kD + (b & 1) * 64), v[i]);
        if (t == 0) TSS(4 + b);
        continue;
      }
      if (b < 2) last_rows(2 + 2 * b, 3 + 2 * b);
      fence_async_smem();
      __syncwarp();
      if (elect_one()) tma_store3d(out, sb + kStage + b * 8192 + warp * 2048, out_col + (b & 1) * 64, out_row + (b >> 1) * 64 + warp * 16, blockIdx.x & 1);
      __syncwarp();
      if (t == 0) TSS(4 + b);
    }
    if (elect_one()) {
      bulk_commit();
      bulk_wait_read();
    }
    if (t == 0) TSS(1);
    return;
  }
  if (hand_over) nb_arrive(kNbOrder + (wg ^ 1), 256);
  if (N == 192 && !local) {
    mbar_wait(sb + kBars + 8 * (kAuxBar + wg), j0 < 32);
    if (j0 < 32) mbar_wait(sb + kBars + 8 * kStatBar, 1);
    mbar_wait(sb + kBars + 8 * (kStgBar + wg), ((j0 >> 5) ^ wg ^ 1) & 1);
  }
  wg_wait<0>();
  mbar_arrive_cluster_if(rel, release_end == nsteps);
#pragma unroll
  for (int i = 0; i < N / 2; i++) asm volatile("" : "+f"(acc[0][i]), "+f"(acc[1][i])::"memory");
}

template <int PH>
struct Ring {
  static constexpr int NSLOT = 4 + (PH & 1), SLOT = PH & 1 ? 32768 : 40960;
  uint32_t full, dst0;
  int j = PH == 0 ? 4 : 0, bi = 0, par = PH == 0 ? 0 : 1;
  __device__ __forceinline__ Ring(uint32_t sb, uint32_t ofs) : full(sb + kBars + 8 * (PH * 9 - (PH & 1))), dst0(sb + kRing + ofs) {}
  __device__ __forceinline__ uint32_t bar() const { return full + 8 * bi; }
  __device__ __forceinline__ uint32_t dst() const { return dst0 + bi * SLOT; }
  __device__ __forceinline__ void acquire_first() const {
    const bool first = j < NSLOT;
    mbar_wait(full + (first ? 8 * min(j, 3) - 32 : 8 * (NSLOT + (PH == 3) + bi)), PH == 2 && first ? 0 : par);
  }
  __device__ __forceinline__ void acquire() const { mbar_wait(full + 8 * (NSLOT + (PH == 3) + bi), par); }
  __device__ __forceinline__ void next() {
    j++;
    if (++bi == NSLOT + (PH == 3 && j > kWide)) { bi = 0; par ^= 1; }
  }
};

__device__ __forceinline__ void check_blocks(const Params& p, Scratch* sc, uint32_t sb, int r, int c, bool g3, uint32_t& par) {
  const int lane = fresh_tid() & 31, nslot = g3 ? 4 : 5, slot_bytes = g3 ? 40960 : 32768;
  const uint32_t mine = (lane >> 2) * 132 + (lane & 3) * 32, ring_end = sb + kRing + kStage + mine;
  const uint32_t to_full = 8 * (kLandBar - (g3 ? ring_base(2) : ring_base(1)));
  uint32_t src = sb + kRing + mine + (g3 ? 0 : 4 * 32768);
  int bi = g3 ? 0 : 4, spins = 0;
#pragma unroll 1
  for (int i = g3 ? 2 : 9; i < 16;) {
    const uint32_t land = sb + kBars + 8 * (kLandBar + bi);
    mbar_wait(land, (par >> bi) & 1);
    uint32_t v[16];
#pragma unroll
    for (int k = 0; k < 16; k++) v[k] = lds32(src + k * 1024);
#pragma unroll
    for (int k = 0; k < 5; k++) v[k] = max(max(v[3 * k + 1], v[3 * k + 2]), k ? v[3 * k] : max(v[0], v[15]));
    const bool again = __any_sync(~0u, max(max(max(v[0], v[1]), v[2]), max(v[3], v[4])) == kPoison);
    asm volatile("{\n.reg .pred p;\nsetp.eq.u32 p, %1, 0;\n@p mbarrier.arrive.shared::cta.b64 _, [%0];\n}\n"
                 ::"r"(land - to_full), "r"(lane + again) : "memory");
    par ^= 1u << bi;
    if (again) {
      if (++spins > 100000) __trap();
      if (elect_one()) {
        mbar_expect_tx(land, 16384);
        tma2d(src - mine, g3 ? &p.h : &p.o, ((g3 ? p.g3[c][i + 2] : p.g2[c][i]) & 15) * 64, r * 128, land);
      }
      nb_sync(kNbSelf + 1, 32);
      continue;
    }
    if (lane == 0 && (i == 2 || i == 3 || (!g3 && (i == 9 || i == 12)))) TS(i < 4 ? 88 + 2 * i : i == 9 ? 120 : 122);
    i++;
    if (++bi == nslot) bi = 0;
    src += slot_bytes;
    if (src == ring_end) src -= kStage;
  }
}

__device__ __forceinline__ void colsum_cta(const Params& p, Scratch* sc, uint32_t sb, int warp, int bid) {
  constexpr int kSlots = 4, kSlot = 49152;
  constexpr int kRows = kMost * 16384, kIn = (kCs - kRows) / 8192;
  const int lane = threadIdx.x & 31, c0 = (bid - 128) * 2;
  const uint32_t full = sb + kBars, empty = full + 8 * kSlots;
  const uint32_t event = full + 64, rfull = full + 128, rempty = full + 256;
  if (threadIdx.x == 0) {
#pragma unroll 1
    for (int i = 0; i < 48; i++) mbar_init(full + 8 * i, i & (i < 16 ? 4 : 32) ? 8 : 1);
    asm volatile("fence.mbarrier_init.release.cluster;" ::: "memory");
  }
  __syncthreads();
  const uint32_t ep = ld_epoch(sc);
  if (warp == 8) {
    if (elect_one()) {
#pragma unroll 1
      for (int n = 0; n < 112 + kSlots; n++) {
        const int u = n >> 4, c = c0 + ((n >> 3) & 1), k0 = (n & 7) * 128, slot = n & (kSlots - 1);
        if (n == kQuietAt) flag_wait(sc->flags + kFlPace, ep);
        const uint32_t bar = full + 8 * slot;
        mbar_wait(empty + 8 * slot, ((n / kSlots) & 1) ^ 1);
        if (n == 108) mbar_arrive(event);
        if (u == 7) continue;
        mbar_expect_tx(bar, u == 6 ? 32768 : 49152);
#pragma unroll
        for (int a = 0; a < 3; a++) {
          if (a == 2 && u == 6) break;
          const CUtensorMap* m = u < 2 ? &p.wqkv : g3_is_up(u - 2, a) ? &p.wu : &p.wg;
          const int col = (u < 2 ? a * 16 + u * 8 + c : g3_atom(u - 2, a, c)) * 64;
          tma2d(sb + slot * kSlot + a * 8192, m, col, k0, bar);
          tma2d(sb + slot * kSlot + a * 8192 + 24576, m, col, k0 + 64, bar);
        }
      }
      mbar_wait(event + 8, 0);
      asm volatile("fence.proxy.async.global;" ::: "memory");
      int slot = 0, par = 1, w = 0;
#pragma unroll 1
      for (int job = 0; job < 32; job++) {
        const int k = lds32(sb + kPlan + (job >> 4) * 4) >> (job & 14) * 2 & 15;
        if (job == 16) {
          mbar_wait(rempty + 8 * (slot ? slot - 1 : kIn - 1), par ^ (slot != 0));
          w = 0;
        }
#pragma unroll 1
        for (int i = 0; i < k; i++) {
          const uint32_t bar = rfull + 8 * slot;
          mbar_wait(bar + 128, par);
          mbar_expect_tx(bar, w < kMost ? 24576 : 8192);
          tma2d(sb + kRows + slot * 8192, &p.hhst, i * (7 * 64), (job & 15) * 128, bar);
          if (w < kMost) {
#pragma unroll
            for (int a = 0; a < 2; a++)
              tma2d(sb + w * 16384 + a * 8192, &p.wd, ((c0 + (job >> 4)) * 2 + a) * 64, w * (7 * 64), bar);
            w++;
          }
          if (++slot == kIn) { slot = 0; par ^= 1; }
        }
      }
    }
  } else if (warp < 8) {
    uint32_t src[3];
#pragma unroll
    for (int j = 0; j < 3; j++) src[j] = sb + ((warp * 3 + j) >> 3) * 8192 + lane * 128 + ((((warp * 3 + j) & 7) ^ (lane & 7)) << 4);
    const uint32_t ones = 0x3F803F80u;
#pragma unroll 1
    for (int s = 0; s < 112; s++) {
      float a[3][2][4] = {};
#pragma unroll 1
      for (;; s++) {
      const int slot = s & (kSlots - 1);
      mbar_wait(full + 8 * slot, (s / kSlots) & 1);
      uint32_t b[3][4][4];
#pragma unroll
      for (int j = 0; j < 3; j++)
#pragma unroll
        for (int k = 0; k < 4; k++)
          asm volatile("ldmatrix.sync.aligned.m8n8.x4.trans.shared.b16 {%0,%1,%2,%3}, [%4];"
                       : "=r"(b[j][k][0]), "=r"(b[j][k][1]), "=r"(b[j][k][2]), "=r"(b[j][k][3])
                       : "r"(src[j] + slot * kSlot + (k >> 1) * 24576 + (k & 1) * 4096) : "memory");
      __syncwarp();
      if (lane == 0) mbar_arrive(empty + 8 * slot);
#pragma unroll
      for (int k = 0; k < 4; k++)
#pragma unroll
        for (int j = 0; j < 3; j++) {
          mma16816(a[j][0], ones, ones, ones, ones, b[j][k][0], b[j][k][1]);
          mma16816(a[j][1], ones, ones, ones, ones, b[j][k][2], b[j][k][3]);
        }
      if ((s & 7) == 7) break;
      }
      {
        if (lane < 12) {
          const int j = lane >> 2;
          const float x = j == 0 ? a[0][0][0] + a[0][1][0] : j == 1 ? a[1][0][0] + a[1][1][0] : a[2][0][0] + a[2][1][0];
          const float y = j == 0 ? a[0][0][1] + a[0][1][1] : j == 1 ? a[1][0][1] + a[1][1][1] : a[2][0][1] + a[2][1][1];
          const float x1 = bf_rest(x), y1 = bf_rest(y);
          const bool split = s < 32;
          st_b128(SC_AT(cs, ((s >> 4) * 8 + c0 + ((s >> 3) & 1)) * 96 + warp * 12 + lane), split ? bf_upper(x, y) : __float_as_uint(x),
                  split ? bf_upper(x1, y1) : __float_as_uint(y), bf_upper(bf_rest(x1), bf_rest(y1)), ep);
        }
        if (threadIdx.x == 0 && (s & 8)) TSK(s >> 4);
      }
    }
    const int wg = warp >> 2;
    mbar_wait(event + 8, 0);
#pragma unroll 1
    for (int job = wg, first = 0; job < 32; job += 2) {
      const int k = __shfl_sync(~0u, lds32(sb + kPlan + (job >> 4) * 4), 0) >> (job & 14) * 2 & 15;
      if (k == 0) continue;
      float acc[96];
#pragma unroll
      for (int i = 0; i < 64; i++) asm volatile("" : "=f"(acc[i]));
      static_assert(kIn == 12, "");
      int slot = first + wg * k, par = slot * 171 >> 11, i = 0;
      slot -= par * kIn;
      first += 2 * k;
      uint32_t done = 0;
      if (job) nb_sync(kNbOrder + wg, 256);
#pragma unroll 1
      do {
        mbar_wait(rfull + 8 * slot, par & 1);
        wg_fence();
#pragma unroll
        for (int kk = 0; kk < 4; kk++)
          wgmma_n128(acc, desc(desc_lo(sb + kRows, 16) + slot * 512) + kk * 2, desc(desc_lo(sb, 8192) + i * 1024) + kk * 128, kk | i);
        wg_commit();
        wg_wait<1>();
        if (lane < 2 && i) mbar_arrive(done);
        done = rempty + 8 * slot;
        if (++slot == kIn) { slot = 0; par++; }
      } while (++i < k);
      nb_arrive(kNbOrder + (wg ^ 1), 256);
      uint4* dst = SC_AT(part, ((job & 15) * 8 + c0 + (job >> 4)) * 1024 + (warp & 3) * 256 + lane);
      wg_wait<0>();
#pragma unroll
      for (int i = 0; i < 64; i++) asm volatile("" : "+f"(acc[i])::"memory");
      if (lane < 2) mbar_arrive(done);
#pragma unroll
      for (int i = 0; i < 8; i++) {
        const float* v = &acc[8 * i];
        asm volatile("st.relaxed.gpu.global.v4.b32 [%0], {%1, %2, %3, %4};"
                     ::"l"(dst + i * 32),
                     "r"(pack_bf16(v[0], v[1])), "r"(pack_bf16(v[2], v[3])), "r"(pack_bf16(v[4], v[5])), "r"(pack_bf16(v[6], v[7])) : "memory");
      }
    }
    if (threadIdx.x == 128) TSK(7);
  } else if (warp == 10) {
    mbar_wait(event, 0);
    flag_wait(sc->flags + kFlHH + (lane & 15) * kFlRow, ep * 8);
    int late = await_word(sc->finish + (uint32_t)((lane & 15) * 8 + c0 + (lane >> 4)), ep);
    __syncwarp();
    late -= __shfl_sync(~0u, late, 0);
    late = max(late, __shfl_xor_sync(~0u, late, 1));
    late = max(min(late - (__reduce_add_sync(~0u, late) >> 5) + kShare * kStepNs, 4096), -4096);
    int k;
#pragma unroll 1
    do {
      k = min(max((late * (8192 / kStepNs) >> 13) + 1, (lane & 14) == 0), kMost);
      late -= kStepNs / 4;
    } while (__reduce_add_sync(~0u, k ? max(2 * k, k + 4) : 0) > kBudget);
    k <<= (lane & 14) * 2;
#pragma unroll
    for (int o = 2; o < 16; o <<= 1) k |= __shfl_xor_sync(~0u, k, o);
    asm volatile("fence.acquire.gpu;" ::: "memory");
    send_word(sc->plan + (uint32_t)(c0 + (lane >> 4)), k, ep);
    sts32(sb + kPlan + (lane >> 4) * 4, k);
    __syncwarp();
    if (lane == 0) mbar_arrive(event + 8);
  }
}

#define PROF_BEGIN
template <bool BY_SM>
__global__ void __cluster_dims__(2, 1, 1) __launch_bounds__(kThreads, 1) fused_block_kernel(Scratch* sc, const __nv_bfloat16* xp, const __nv_bfloat16* wqkvp, __nv_bfloat16* outp,
                                                                   const __grid_constant__ Params p) {
  extern __shared__ __align__(1024) uint8_t smem_raw[];
  if (threadIdx.x == 256) { prefetch_map(&p.x); prefetch_map(&p.wqkv); }
  if (threadIdx.x < 56) {
    const int l = threadIdx.x & 31, b = blockIdx.x & 127;
    if (threadIdx.x < 32) prefetch_l2(xp + (b * 16 + (l & 15)) * kD + (l >> 4) * 64);
    else prefetch_l2(wqkvp + b * (3 * kD) + (l >> 3) * kD + (l & 7) * 64);
  }
  const uint32_t sb = smem_u32(smem_raw);
  const int bid = role_id<BY_SM>();
  const int r = bid >> 3, c = bid & 7, rank = blockIdx.x & 1;
  auto first_fill = [&](int j) {
    const uint32_t fb = sb + kBars + 8 * j, dst = sb + kRing + j * 40960;
    mbar_expect_tx(fb, 40960);
    tma3d(j >> 1 == c ? sb + kOwn + (j & 1) * 16384 : dst, &p.x, j * 64, (r >> 1) * 128, rank, fb);
#pragma unroll
    for (int a = 0; a < 3; a++) tma2d(dst + 16384 + a * 8192, &p.wqkv, a * kD + c * 64, j * 64, fb);
    mbar_arrive(fb);
  };
  const int tid = threadIdx.x, warp = __shfl_sync(~0u, tid >> 5, 0), wg = warp >> 2;
  if (bid >= 128) {
    if (tid == 0) PROF_BEGIN;
    colsum_cta(p, sc, sb, warp, bid);
    return;
  }
  if (wg == 2) {
    if (warp == 8 && elect_one()) {
      mbar_init(sb + kBars, 2);
      asm volatile("fence.mbarrier_init.release.cluster;" ::: "memory");
      first_fill(0);
#pragma unroll
      for (int j = 1; j < 4; j++) mbar_init(sb + kBars + 8 * j, 2);
      asm volatile("fence.mbarrier_init.release.cluster;" ::: "memory");
      TSS(0);
    }
    __syncwarp();
    if (warp == 8) nb_arrive(kNbOrder, 160);
    asm volatile("setmaxnreg.dec.sync.aligned.u32 40;");
    if (warp == 8) {
      cluster_arrive();
      if (elect_one()) {
#pragma unroll 1
        for (int j = 1; j < 4; j++) first_fill(j);
        TSS(1);
      }
      __syncwarp();
    } else {
      if (elect_one()) {
        uint64_t shifts = warp == 9 ? bar_shifts(4) : warp == 10 ? bar_shifts(22) : bar_shifts(40);
#pragma unroll 1
        for (int i = 0; i < 18; i++, shifts >>= 3) mbar_init(sb + kBars + 8 * (18 * warp - 158 + i), 1u << (shifts & 7));
        if (warp == 10) asm volatile("mbarrier.arrive.shared::cta.b64 _, [%0], 2;" ::"r"(sb + kBars + 8 * 31) : "memory");
        sts32(sb + kZero, 0);
        sts32(sb + kScale + 4, 0);
        sts32(sb + kRole, bid);
        sts128(sb + kOnes, make_uint4(0x3F803F80u, 0, 0, 0x3F803F80u));
        asm volatile("fence.mbarrier_init.release.cluster;" ::: "memory");
      }
      __syncwarp();
      cluster_arrive();
    }
    cluster_wait();
    const uint32_t ep = ld_epoch(sc);
    if (tid == 320) sts32(sb + kEpoch, ep);
    if (tid == 320) PROF_BEGIN;
    const int pw = warp & 3;
    if (pw == 0) {
      if (elect_one()) {
        const int row = r * 128;
        const uint32_t land = sb + kBars + 8 * kLandBar;
#pragma unroll 1
        for (Ring<0> q(sb, 0); q.j < 32; q.next()) {
          q.acquire();
          const int kb = p.g1[c][q.j];
          if (kb & kInPlace) { mbar_arrive(q.bar()); continue; }
          mbar_expect_tx(q.bar(), 16384);
          tma3d(kb >> 1 == c ? sb + kOwn + (kb & 1) * 16384 : q.dst(), &p.x, kb * 64, (r >> 1) * 128, rank, q.bar());
        }
        prefetch_map(&p.o);
        prefetch_map(&p.o16);
        flag_wait(sc->flags + kFlO + r * kFlRow, ep * 8);
        fence_async();
        TS(40);
#pragma unroll 1
        for (Ring<1> q(sb, 0); q.j < 16; q.next()) {
          q.acquire_first();
          if (q.j == 8) {
            prefetch_map(&p.wg);
            prefetch_map(&p.wu);
            prefetch_map(&p.h);
            prefetch_map(&p.h16);
            mbar_wait(sb + kBars + 8 * kSentBar, 0);
            mbar_arrive(q.bar());
            mbar_arrive(sb + kBars + 8 * (kStgBar + 1));
            if (bid == 0) __stcg(sc->flags + kFlPace, ep);
            __nanosleep(kGateONs);
            continue;
          }
          const uint32_t bar = q.j < 8 ? q.bar() : land + 8 * q.bi;
          if (q.j == 9) TS(41);
          mbar_expect_tx(bar, 16384);
          tma2d(q.dst(), &p.o, p.g2[c][q.j] * 64, row, bar);
        }
#pragma unroll 1
        for (Ring<2> q(sb, 0); q.j < 64; q.next()) {
          q.acquire_first();
          const int kb = p.g3[c][q.j];
          if (kb & kInPlace) { mbar_arrive(q.bar()); continue; }
          if (q.j == 4) { __nanosleep(kGateHNs); TS(42); }
          const uint32_t bar = q.j < 18 ? land + 8 * q.bi : q.bar();
          mbar_expect_tx(bar, 16384);
          tma2d(q.dst(), &p.h, (kb & 15) * 64, row, bar);
        }
        prefetch_map(&p.hh);
        prefetch_map(&p.out);
        Ring<3> q(sb, 0);
#pragma unroll 1
        for (; q.j < 16; q.next()) {
          q.acquire_first();
          if (q.j == 0) { mbar_arrive(q.bar()); continue; }
          mbar_expect_tx(q.bar(), 16384);
          tma2d(q.dst(), &p.h, ((q.j + 9) & 15) * 64, row, q.bar());
        }
        uint32_t wave = sb + kBars + 8 * kWaveBar;
        int share = 0;
#pragma unroll 1
        for (; q.j < 72; q.next()) {
          const int kb = p.g4[q.j - 16];
          if (kb & kNextWave) {
            mbar_wait(wave, 0);
            fence_async();
            wave += 8;
            if (q.j == 16) share = lds32(sb + kPlan);
          }
          q.acquire();
          const bool half = (kb & kShared) && --share >= 0;
          mbar_expect_tx(q.bar(), half ? 8192 : 16384);
          tma2d(q.dst() + half * 8192, half ? &p.hhst : &p.hh, (kb & 63) * 64, row + half * 64, q.bar());
        }
      }
    } else if (pw == 1) {
      if (elect_one()) {
        const int rp = r >> 1;
#pragma unroll 1
        for (Ring<0> q(sb, 16384); q.j < 32; q.next()) {
          q.acquire();
          mbar_expect_tx(q.bar(), 24576);
          const int col = ((q.j >> 4) * 8 + c) * 64, k0 = (p.g1[c][q.j] & 15) * 64;
          tma2d_mc(q.dst() + rank * 8192, &p.wqkv, rank * kD + col, k0, q.bar());
          if ((q.j & 1) == rank) tma2d_mc(q.dst() + 16384, &p.wqkv, 2 * kD + col, k0, q.bar());
          if (q.j == max(r, 4))
            for (int a = 0; a < 3; a++) tma_prefetch2d(&p.wqkv, a * kD + (8 + c) * 64, ((r + 12) & 15) * 64);
          if (q.j >> 1 == rp + 8) tma_prefetch2d(&p.wo, (c * 2 + rank) * 64, (q.j & 15) * 64);
        }
        if (r < 6) tma_prefetch2d(rp == 1 ? &p.wu : &p.wg, (c * 7 + 3 + (rp >> 1)) * 64, (c * 2 + rank) * 64);
#pragma unroll 1
        for (Ring<1> q(sb, 16384 + rank * 8192); q.j < 16; q.next()) {
          q.acquire_first();
          mbar_expect_tx(q.bar(), 16384);
          tma2d_mc(q.dst(), &p.wo, (c * 2 + rank) * 64, p.g2[c][q.j] * 64, q.bar());
        }
        const CUtensorMap* mine = rank ? &p.wu : &p.wg;
#pragma unroll 1
        for (Ring<2> q(sb, 16384); q.j < 64; q.next()) {
          const int kb = p.g3[c][q.j], tile = kb >> 5, f0 = c * 7 + (tile & 1) * 3, fp = f0 + (tile & 2);
          const int k0 = (kb & 15) * 64;
          q.acquire_first();
          mbar_expect_tx(q.bar(), 24576);
          const uint32_t dst = q.j < 4 ? sb + kRing + (q.j + 1) * 32768 : q.dst();
          tma2d_mc(dst + rank * 8192, mine, fp * 64, k0, q.bar());
          if ((q.j & 1) == rank) tma2d_mc(dst + 16384, tile & 2 ? &p.wu : &p.wg, (f0 + 1) * 64, k0, q.bar());
          const int d = q.j - kPfStep - (c & 1) * 5 - (r >> 2);
          if (d == 0 || d == 11 || d == 22) {
            const int f = c * 7 + (d == 0 ? 2 : d == 11 ? 5 : 6);
            tma_prefetch2d(&p.wg, f * 64, r * 64);
            tma_prefetch2d(&p.wu, f * 64, r * 64);
            if (d != 22) tma_prefetch2d(&p.wu, (f - 1) * 64, r * 64);
            else tma_prefetch2d(&p.wd, (c * 2 + rank) * 64, rp * (7 * 64));
          }
          if (q.j >> 1 == rp + 24) tma_prefetch2d(&p.wd, (c * 2 + rank) * 64, (p.g4[q.j & 15] & 63) * 64);
        }
        Ring<3> q(sb, 16384 + rank * 8192);
#pragma unroll 1
        for (; q.j < 16; q.next()) {
          q.acquire_first();
          mbar_expect_tx(q.bar(), 16384);
          tma2d_mc(q.dst(), mine, (c * 7 + 6) * 64, ((q.j + 9) & 15) * 64, q.bar());
          if (q.j >> 1 == rp) tma_prefetch2d(&p.wd, (c * 2 + rank) * 64, (p.g4[q.j + 16] & 63) * 64);
        }
#pragma unroll 1
        for (; q.j < 72; q.next()) {
          q.acquire();
          mbar_expect_tx(q.bar(), 16384);
          tma2d_mc(q.dst(), &p.wd, (c * 2 + rank) * 64, (p.g4[q.j - 16] & 63) * 64, q.bar());
          if ((q.j & 15) >> 1 == rp && q.j < 40) tma_prefetch2d(&p.wd, (c * 2 + rank) * 64, (p.g4[q.j + 16] & 63) * 64);
        }
      }
    } else {
      const int cw = pw - 2;
      const uint32_t stg = sb + kStage + cw * 32768, rb = sb + kBars + 8 * kResBar;
      uint32_t land_par = 0;
      sts64(sb + kPlan, global_ns(), clock());
      if (cw == 0) {
#pragma unroll 1
        for (int i = 0; i < 16; i++) sts128(sb + kFill + i * 512 + (tid & 31) * 16, make_uint4(kPoison, kPoison, kPoison, kPoison));
        __nanosleep(kSampleNs);
        const uint32_t l15 = tid & 15;
        const uint4 os = __ldg(plus(p.wop, (tid & 31) * 128 + c * 16 + l15));
        const uint4 gs = __ldg(plus(tid & 16 ? p.wup : p.wgp, l15 * 451 + c * 56));
        const uint4 ws = __ldg(plus((const uint4*)wqkvp, (tid & 7) * 385 + (tid & 24) * 16 + (8 + c) * 8));
        sts64(sb + kScale, __float_as_uint(low_peak(os) * kBias3 * low_peak(gs)), __float_as_uint(low_peak(ws) * kBias1) | 1);
        if (tid == 320) TS(93);
      }
#pragma unroll 1
      for (int ev = -1; ev < 4; ev++) {
        const bool quads = cw == 0 && ev == 1;
        if (ev >= cw && !quads) nb_sync(kNbPub + cw, 160);
        if (ev >= cw && elect_one()) {
          if (quads) {
            mbar_wait(sb + kBars + 8 * (kHalfBar + 1), 0);
#pragma unroll 1
            for (int i = 0; i < 2; i++) {
              __nanosleep(i ? kPaceNs : kHoldNs);
              tma_store2d(&p.hst, stg + 16384 + i * 8192, c * 128 + 64, r * 128 + i * 64);
              TS(100 + i);
            }
            bulk_commit();
            bulk_wait_read();
            mbar_arrive(sb + kBars + 8 * kStgBar);
          } else {
            if (ev == 1) {
              const uint32_t now = global_ns();
              const float left = (float)(now - lds32(sb + kPlan)) * (float)kRemain * rcp((float)((uint32_t)clock() - lds32(sb + kPlan + 4)));
              send_word(sc->finish + (uint32_t)bid, now + (uint32_t)left, ep);
            }
            const int it = ev - 2 + cw, f0 = c * 7 + (1 - cw) * 3, fp = it == 2 ? c * 7 + 6 : f0 + 2 * it;
            const bool is_o = ev == 0;
            const CUtensorMap* m = is_o ? &p.ost : &p.hhst;
            const int b0 = is_o ? c : f0 + 1, b1 = fp;
#pragma unroll 1
            for (int i = is_o || it == 1 ? 0 : 2; i < (is_o ? 2 : 4); i++) {
              tma_store2d(m, stg + i * 8192, (i < 2 ? b0 : b1) * 64, r * 128 + (i & 1) * 64);
              if (!is_o) {
                bulk_commit();
                bulk_wait_read();
                __nanosleep(kPaceNs);
              }
            }
            bulk_commit();
            bulk_wait_all();
            mbar_arrive(sb + kBars + 8 * (kStgBar + cw));
            if (ev == 3 + cw) {
#pragma unroll
              for (int i = 0; i < 2; i++) asm volatile("mbarrier.arrive.shared::cluster.b64 _, [%0], 4;" ::"r"(map_cta(sb + kBars + 8 * 37, i)) : "memory");
            }
            flag_signal(SC_AT(flags, kFlHH + ev * 2 - 3 + cw + r * kFlRow));
            TS(44 + cw * 8 + ev);
            if (ev == 2 && cw) {
              sts32(sb + kPlan, await_word(sc->plan + (uint32_t)c, ep) >> (r >> 1) * 4 & 15);
              mbar_expect_tx(rb, 16384);
#pragma unroll 1
              for (int i = 0; i < 2; i++) tma2d(stg + 8192 + i * 16384, &p.hst, c * 128 + i * 64, r * 128 + 64, rb);
            }
          }
        }
        nb_sync(kNbSelf + cw, 32);
        if (ev >= 2 && ev + cw >= 3 && elect_one()) {
          const int wv = cw == 0 ? 3 : ev == 2 ? 0 : 4;
#pragma unroll 1
          for (int i = wv; i <= max(wv, 2); i++) flag_wait(SC_AT(flags, kFlHH + i + r * kFlRow), ep * 8);
          fence_async();
          mbar_arrive(sb + kBars + 8 * (kWaveBar + (wv >> 1)));
          if (wv == 4) {
            mbar_expect_tx(sb + kBars + 8 * kPartBar, 16384);
#pragma unroll 1
            for (int i = 0; i < 2; i++) tma2d(stg + 16384 + i * 8192, &p.hst, c * 128 + i * 64, r * 128, sb + kBars + 8 * kPartBar);
          }
        }
        nb_sync(kNbSelf + cw, 32);
#pragma unroll 1
        for (int sub = 0; ev < 3 && (ev != 0 || cw == 1); sub++) {
          nb_sync(kNbSelf + cw, 32);
          if (ev == 0) check_blocks(p, sc, sb, r, c, sub, land_par);
          const int u = ev < 0 ? cw : 2 * ev + 1 + cw, lane = fresh_tid() & 31;
          if (u == 1 && !sub) {
            uint3 st[5];
            load_tagged<5, true>(st, SC_AT(stat1, r * 128 + lane), 32, ep, SC_AT(stat1, (r < 2 ? r : r - 2) * 128 + (lane & 7)) + 120);
#pragma unroll
            for (int i = 0; i < 4; i++) sts64(sb + kStat + (i * 32 + lane) * 8, st[i].x, st[i].y);
            sts64(sb + kStat - 64 + (lane & 7) * 8, st[4].x, st[4].y);
            nb_sync(kNbSelf + cw, 32);
            if (lane < 4) mbar_arrive(sb + kBars + 8 * kStatBar);
            if (lane == 0) TS(17);
          }
          if (u == 1) {
            const uint4* gh = SC_AT(halo, (sub * 128 + bid) * 192 + lane) - 16 * 192;
            uint4 hv[6] = {};
            nb_sync(kNbHalo, 64);
            uint32_t ns = sub ? kHaloNs : 2 * kBackoffNs;
#pragma unroll 1
            for (int spins = 0; r >= 2; spins++) {
              if (ns) __nanosleep(ns);
              ns = sub ? 0 : kBackoffNs;
              if (spins > 2000000) __trap();
#pragma unroll
              for (int i = 0; i < 6; i++) hv[i] = ld_b128(gh + i * 32);
              uint32_t bad = (hv[5].y ^ ep) | (hv[5].z ^ ep);
#pragma unroll
              for (int i = 0; i < 6; i++) bad |= hv[i].w ^ ep;
              if (!__any_sync(~0u, bad != 0)) break;
            }
            const uint32_t dst = sb + kStage + sub * 32768 + lane * 16;
            sts128(dst, make_uint4(hv[0].x, hv[0].y, hv[0].z, hv[1].x));
            sts128(dst + 512, make_uint4(hv[1].y, hv[1].z, hv[2].x, hv[2].y));
            sts128(dst + 1024, make_uint4(hv[2].z, hv[3].x, hv[3].y, hv[3].z));
            sts128(dst + 1536, make_uint4(hv[4].x, hv[4].y, hv[4].z, hv[5].x));
            nb_arrive(kNbHalo + 1, 64);
            if (lane == 0) TS(123 + sub);
          }
          if (sub) break;
          uint3 v[3];
          load_tagged<3, false>(v, SC_AT(cs, c * 96 + u * 768 + lane), 32, ep);
          if (u < 2) {
#pragma unroll
            for (int i = 0; i < 3; i++)
#pragma unroll
              for (int k = 0; k < 8; k++)
                sts32(sb + kAug + cw * 4096 + i * 1024 + k * 128 + ((lane * 4) ^ (k * 16)), k == 7 ? 0x3F803F80u : k == 4 || k == 6 ? v[i].z : k & 1 && k != 5 ? v[i].y : v[i].x);
            fence_async_smem();
          } else {
#pragma unroll
            for (int i = 0; i < 3; i++) sts64(sb + kCs + cw * 768 + (i * 32 + lane) * 8, v[i].x, v[i].y);
          }
          nb_sync(kNbSelf + cw, 32);
          if (lane == 0) { mbar_arrive(sb + kBars + 8 * (kAuxBar + cw)); TS(104 + u); }
        }
        nb_sync(kNbSelf + cw, 32);
        if (ev < 0 && cw == 0 && elect_one()) {
#pragma unroll 1
          for (int i = 0; i < 6; i++) {
            __nanosleep(i == 0 ? (c >> 1) * (kFillNs / 4) : kFillNs);
            tma_store2d(i < 2 ? &p.ost : &p.hst, sb + kFill, i < 2 ? (8 + c) * 64 : (c * 2 - 1 + (i >> 1)) * 64, r * 128 + (i & 1) * 64);
            bulk_commit();
          }
          uint32_t peer;
          asm volatile("ld.shared::cluster.b32 %0, [%1];" : "=r"(peer) : "r"(map_cta(sb + kRole, rank ^ 1)) : "memory");
          if (peer != (bid ^ 8)) __trap();
          TS(90);
        }
        nb_sync(kNbSelf + cw, 32);
      }
    }
  } else {
    if (tid == 0) TSS(2);
    cluster_arrive();
    float bias = 0.f;
    float sx = 0.f, mx = 0.f;
    asm volatile("setmaxnreg.inc.sync.aligned.u32 232;");
    if (tid == 0) TSS(4);
    int task;
    asm volatile("mov.u32 %0, %1;" : "=r"(task) : "r"(8 - wg));

#pragma unroll 1
    for (task = __shfl_sync(~0u, task, 0);; task++) {
      if (task == 1 + wg || task == 9 - wg) {
        const int t = fresh_tid();
        uint2 scale;
        do asm volatile("ld.volatile.shared.v2.b32 {%0, %1}, [%2];" : "=r"(scale.x), "=r"(scale.y) : "r"(sb + kScale) : "memory");
        while (scale.y == 0);
        __syncwarp();
        bias = bias_at(low_peak(lds128(sb + (task > 5 ? kRing : kStage + wg * 32768) + (t & 126) * 64 + (t & 14) * 8 + (t & 1) * 8192)) *
                       __uint_as_float(task > 5 ? scale.y : scale.x));
        if (t == 128 && task > 5) TS(95);
      }
      if (wg == 0 && (task == 1 || task == 4)) {
        float acc[2][96];
        const int t = fresh_tid() & 127;
        const uint32_t frag = sb + kOwn + ((t >> 5) * 16 + (t & 15)) * 128, frag_x = ((t >> 4) & 1) ^ (t & 7);
        TSG(2);
        if (task == 4) mbar_wait(sb + kBars + 8 * kResBar, 0);
        auto residual = [&](int m) {
#pragma unroll
          for (int i = 0; i < 8; i++) {
            uint32_t v[4];
            ldsm4(frag + (i >> 2) * 16384 + m * 8192 + ((frag_x ^ (i * 2 & 6)) << 4), v);
#pragma unroll
            for (int e = 0; e < 4; e++) {
              float* d = &acc[m][8 * i + 2 * e];
              asm("shl.b32 %0, %1, 16;" : "=f"(d[0]) : "r"(v[e]));
              asm("and.b32 %0, %1, 0xFFFF0000;" : "=f"(d[1]) : "r"(v[e]));
            }
          }
        };
        residual(1);
        if (task == 1) {
          residual(0);
        } else {
#pragma unroll
          for (int i = 0; i < 64; i++) acc[0][i] = 0.f;
        }
        __syncwarp();
        if ((t & 31) == 0) mbar_arrive(sb + kBars + 8 * kResFreeBar);
        TSG(4);
        if ((tid & 127) == 0) TS(task == 1 ? 6 : 14);
        if (task == 4) {
          mainloop<128, kTail>(sc, acc, sb, 3, 16, 56, -2, true, false, false, 0, __shfl_sync(~0u, lds32(sb + kPlan), 0), &p.out, c * 128, (r >> 1) * 128, warp, outp);
          if ((tid & 127) == 0) TSK(15);
          if (fresh_tid() == 0) {
            if (bid == 0) __stcg(sc->epoch, lds32(sb + kEpoch));
            TSK(19);
          }
          break;
        }
        mainloop<128, -1>(sc, acc, sb, 1, 0, 15, kPauseG2, false, true, false, 0);
        const int t2 = fresh_tid() & 127;
        const uint32_t frag2 = sb + kStage + ((t2 >> 5) * 16 + (t2 & 15)) * 128, frag2_x = ((t2 >> 4) & 1) ^ (t2 & 7);
        const uint32_t empty = map_cta(sb + kBars + 8 * (ring_base(1) + 5), t2 & 1);
        mbar_wait(sb + kBars + 8 * kStgBar, 0);
        mbar_wait(sb + kBars + 8 * ring_base(1), 1);
#pragma unroll
        for (int m = 0; m < 2; m++) {
          const uint32_t a = desc_lo(sb + kRing, 16);
          wg_fence();
#pragma unroll
          for (int k = 0; k < 4; k++) wgmma_n128(acc[m], desc_kept(a, sb) + (m * 512 + k * 2), desc_kept(a, sb) + (kToB + k * 128));
          wg_commit();
          if (m) nb_arrive(kNbOrder + 1, 256);
          wg_wait<1>();
          if (!m) mbar_arrive_cluster_if(empty + 8 * 4, (t2 & 31) < 2);
        }
#pragma unroll
        for (int b = 0; b < 4; b++) {
          if (b == 1) {
            wg_wait<0>();
            if (t2 == 0) TSK(7);
          }
          if (b < 2) {
#pragma unroll
            for (int i = 0; i < 64; i++) asm volatile("" : "+f"(acc[b][i])::"memory");
          }
          stage_quarter(&acc[b & 1][32 * (b >> 1)], frag2, frag2_x, b);
          if (b & 1) {
            fence_async_smem();
            __syncwarp();
            if (elect_one()) {
              mbar_arrive(sb + kBars + 8 * (kHalfBar + (b >> 1)));
#pragma unroll
              for (int m = 0; m < 2; m++)
                if (b == 1) tma_store2d(&p.h16, sb + kStage + m * 8192 + warp * 2048, c * 128, r * 128 + m * 64 + warp * 16);
            }
            __syncwarp();
          }
        }
        if (t2 == 0) TS(8);
        sx = mx = 0.f;
        continue;
      }
      float acc[2][96];
      if (task == 8 + wg) {
        wg_fence();
#pragma unroll
        for (int m = 0; m < 2; m++) wgmma_n192_any(acc[m], desc(64 + m), desc(64 + m));
        wg_commit();
        wg_wait<0>();
#pragma unroll
        for (int i = 0; i < 96; i++) asm volatile("" : "+f"(acc[0][i]), "+f"(acc[1][i])::"memory");
      } else {
        const uint32_t z = fresh_tid() >> 10;
#pragma unroll
        for (int i = 0; i < 96; i++) {
#pragma unroll
          for (int m = 0; m < 2; m++)
            asm("{\n.reg .b32 t;\nlop3.b32 t, %1, %2, %3, 0xEA;\nmov.b32 %0, t;\n}\n" : "=f"(acc[m][i]) : "r"(z), "r"(2 * i + m + 1), "r"(__float_as_uint(bias)));
        }
      }
      if (task > 5) {
      if (wg) {
        if (task == 7) cluster_wait();
        if (tid == 128 && task == 7) { TSS(5); TSK(69); }
        const int t = fresh_tid() & 127, lr = c * 16 + (t >> 3);
        uint32_t pf = t < 64 ? (bid * 16 + (t >> 2)) * kD + (t & 3) * 64 : (r * 48 + t - 64) * kD + c * 64;
        const uint32_t src = sb + kRing + lr * 128 + (((t ^ lr) & 7) << 4), empty = map_cta(sb + kBars + 8 * 4, t & 1), zero = fresh_tid() >> 10;
#pragma unroll 1
        for (int j = task == 7 ? 0 : kSplit; j < (task == 7 ? kSplit : 16); j++) {
          mbar_wait(sb + kBars + 8 * (j & 3), (j >> 2) & 1);
          if (j < 2 && t == 0) TS(102 + j);
          const uint4 v = lds128(src + (j >> 1 == c ? kOwn + (j & 1) * 16384 : (j & 3) * 40960));
          __syncwarp();
          mbar_arrive_cluster_if(empty + 8 * (j & 3) + (v.x & zero), (t & 31) < 2);
          if ((j == 0 || j == 3 || j == 6) && t < 112) { pf += t < 64 ? 256 : 256 * 3 * kD; prefetch_l2(plus(t < 64 ? xp : wqkvp, pf)); }
          const uint32_t u[4] = {v.x, v.y, v.z, v.w};
#pragma unroll
          for (int e = 0; e < 4; e++) {
            const float d0 = bf_lo(u[e]), d1 = bf_hi(u[e]);
            sx += d0 + d1;
            mx = fmaf(d1, d1, fmaf(d0, d0, mx));
          }
        }
        if (task == 7) {
          if (t == 0) TS(96);
          continue;
        }
#pragma unroll
        for (int o = 4; o > 0; o >>= 1) { sx += __shfl_xor_sync(~0u, sx, o); mx += __shfl_xor_sync(~0u, mx, o); }
        const float mean = sx * (1.f / kD);
        float rstd;
        asm("rsqrt.approx.ftz.f32 %0, %1;" : "=f"(rstd) : "f"(fmaxf(mx * (1.f / kD) - mean * mean, 0.f) + 1e-5f));
        const uint32_t ep = lds32(sb + kEpoch);
        const int t2 = fresh_tid();
        if ((t2 & 7) == 0) st_b128(SC_AT(stat1, bid * 16 + (t2 >> 3 & 15)), __float_as_uint(rstd), __float_as_uint(-mean), ep, ep);
        if (t == 0) TS(16);
      }
      if (tid == 0) TSS(6);
      mainloop<192, -1>(sc, acc, sb, 0, wg * 16, wg ? 16 - kAhead : 16, wg ? kPauseG1 : -2, false, wg == 0, false, wg,
                        wg ? min((c + 2) & 7, 6) : c);
      int t = fresh_tid() & 127, lane = t & 31, g = lane >> 2, q = lane & 3;
      const int w = warp & 3;
      const uint32_t stg = sb + kStage + wg * 32768;
      auto tail = [&](int m, int k0, int k1) {
        wg_fence();
#pragma unroll
        for (int k = k0; k < k1; k++) {
          const uint64_t a = desc_kept(desc_lo(sb + kRing, 16), sb) + (4 - kAhead + (k >> 2)) * (40960 >> 4);
          wgmma_n192(acc[m], a + (m * 512 + (k & 3) * 2), a + (kToB + (k & 3) * 128));
        }
      };
      auto release = [&](int j, bool cond) { mbar_arrive_cluster_if(map_cta(sb + kBars + 8 * (4 + (j & 3)), lane & 1), cond); };
      if (wg) {
#pragma unroll
        for (int j = 32 - kAhead; j < 32; j++) {
          TST(2 * (j & 1));
          mbar_wait(sb + kBars + 8 * (j & 3), 1);
          TST(2 * (j & 1) + 1);
          tail(1, 4 * (j - 32 + kAhead), 4 * (j - 31 + kAhead));
          wg_commit();
          if (j == 32 - kAhead) {
            wg_wait<1>();
            release(j - 1, lane < 4);
            mbar_wait(sb + kBars + 8 * kResFreeBar, 0);
          }
        }
      } else {
        nb_arrive(kNbOrder + 1, 256);
        wg_wait<0>();
        release(15, lane < 2);
        if (t == 0) TSK(1);
      }
      TST(4);
      mbar_wait(sb + kBars + 8 * (kAuxBar + wg), 0);
      mbar_wait(sb + kBars + 8 * kStatBar, 0);
      {
        uint32_t am[4];
#pragma unroll
        for (int i = 0; i < 4; i++) {
          const float m1 = __uint_as_float(lds32(sb + kStat + (w * 16 + g) * 8 + 4 + (i >> 1) * 512 + (i & 1) * 64));
          const float m2 = bf_rest(m1), lo = q & 1 ? m2 : m1;
          am[i] = bf_upper(lo, q == 3 ? -bias : q == 2 ? bf_rest(m2) : lo);
        }
        const uint64_t db = (uint64_t)desc_lo(sb + kAug + wg * 4096, 1024) | (0x40000000ull << 32);
        TST(5);
        wg_fence();
        wgmma_n192_rs(acc[1], am[2], am[3], 0u, db);
        wg_commit();
        TST(6);
        wg_fence();
        wgmma_n192_rs(acc[0], am[0], am[1], 0u, db);
        wg_commit();
        if (wg) {
          tail(0, 0, 4 * kAhead);
          wg_commit();
          wg_wait<2>();
        } else {
          wg_wait<1>();
        }
        TST(8);
#pragma unroll
        for (int i = 0; i < 96; i++) asm volatile("" : "+f"(acc[1][i])::"memory");
      }
      t = fresh_tid() & 127, lane = t & 31;
      const uint32_t ep = lds32(sb + kEpoch);
      uint32_t pk[2][48];
      auto fold = [&](int pp, int jn, int hf) {
        const uint32_t v = pack_bf16(acc[pp][4 * jn + 2 * hf], acc[pp][4 * jn + 2 * hf + 1]);
        pk[pp][2 * jn + hf] = jn >= 16 ? movm(v) : v;
      };
      if (t == 96) TS(115 + wg);
#pragma unroll
      for (int jn = 8; jn < 24; jn++) fold(1, jn, 1);
      if (w < 3) {
#pragma unroll
        for (int i = 0; i < 4; i++)
          sts128(stg + (w + 5) * 2048 + i * 512 + lane * 16, make_uint4(pk[1][17 + 8 * i], pk[1][19 + 8 * i], pk[1][21 + 8 * i], pk[1][23 + 8 * i]));
      } else if (r < 14) {
        uint4* gh = SC_AT(halo, (wg * 128 + bid) * 192 + lane);
#pragma unroll
        for (int i = 0; i < 6; i++) st_b128(gh + i * 32, pk[1][17 + 6 * i], i < 5 ? pk[1][(19 + 6 * i) % 48] : ep, i < 5 ? pk[1][(21 + 6 * i) % 48] : ep, ep);
        if (wg == 0) {
#pragma unroll 1
          for (int i = 0; i < 6; i++, gh += 32) st_b128(gh + 128 * 192, 0, 0, 0, ep - 1);
        }
      }
      if (w == 3) nb_arrive(kNbHalo, 64);
      if (wg) nb_arrive(kNbOrder, 256);
      TST(9);
      if (t == 96) TS(111 + wg);
#pragma unroll
      for (int jn = 23; jn >= 0; jn--) {
        fold(1, jn, 0);
        if (jn < 8) fold(1, jn, 1);
      }
      t = fresh_tid() & 127, lane = t & 31, g = lane >> 2, q = lane & 3;
      const bool sel0 = 2 * q > g, sel1 = 2 * q + 1 > g, no_prev = (r < 2 && w == 0);
      const uint4 ones = lds128(sb + kOnes);
      const uint32_t lowmask = (sel0 ? 0x0000FFFFu : 0u) | (sel1 ? 0xFFFF0000u : 0u) | ones.y;
      float rs[4][2], rk[4][2];
#pragma unroll
      for (int i = 0; i < 4; i++) {
        const uint32_t a = sb + kStat + w * 128 + (i >> 1) * 512 + (i & 1) * 64;
        const float rq = __uint_as_float(lds32(a + g * 8)) * (0.17677669529663687f * 1.4426950408889634f);
        rk[i][0] = __uint_as_float(lds32(a + q * 16 - (sel0 ? 64 : 0)));
        rk[i][1] = __uint_as_float(lds32(a + q * 16 + 8 - (sel1 ? 64 : 0)));
        rs[i][0] = rk[i][0] * rq;
        rs[i][1] = rk[i][1] * rq;
      }
      {
        uint32_t all = ~0u;
#pragma unroll
        for (int i = 0; i < 48; i++) if (i < 16 || !(i & 1)) all &= pk[1][i];
        if (all == kPoison) sts32(sb + kZero + 8, 0);
      }
      TST(10);
      wg_wait<0>();
      TST(11);
#pragma unroll
      for (int j = 32 - kAhead; j < 32; j++) release(j, lane < 4 * wg && (w != 0 || j < 31));
#pragma unroll
      for (int i = 0; i < 96; i++) asm volatile("" : "+f"(acc[0][i])::"memory");
      if (t == 0 && wg) TSK(21);
#pragma unroll
      for (int jn = 8; jn < 24; jn++) fold(0, jn, 1);
#pragma unroll
      for (int i = 0; i < 4; i++)
        sts128(stg + (w + 1) * 2048 + i * 512 + lane * 16, make_uint4(pk[0][17 + 8 * i], pk[0][19 + 8 * i], pk[0][21 + 8 * i], pk[0][23 + 8 * i]));
#pragma unroll
      for (int jn = 23; jn >= 0; jn--) {
        fold(0, jn, 0);
        if (jn < 8) fold(0, jn, 1);
      }
      if (t == 0) TS(113 + wg);
      nb_sync(kNbWg + wg, 128);
      uint32_t hal[2][16];
      auto load_halo = [&](int m) {
#pragma unroll
        for (int i = 0; i < 4; i++) {
          const uint4 v = lds128(stg + w * 2048 + m * 8192 + i * 512 + lane * 16);
          uint32_t* h = &hal[m][i * 4];
          h[0] = v.x; h[1] = v.y; h[2] = v.z; h[3] = v.w;
        }
      };
      load_halo(1);
      if (w == 0) {
        nb_sync(kNbHalo + 1, 64);
        release(31, lane < 4 * wg);
      }
      load_halo(0);
      __syncwarp();
      if (t == 0) TS(2 + wg * 20);
      {
        uint32_t all = lowmask;
#pragma unroll
        for (int i = 0; i < 32; i++) if (i < 16 || !(i & 1)) all &= pk[0][i];
#pragma unroll
        for (int i = 0; i < 8; i++) all &= __float_as_uint(rs[i >> 1][i & 1]);
        if (all == kPoison) sts32(sb + kZero + 8, 0);
      }
      nb_sync(kNbWin, 256);
      if (t == 0) TS(9 + wg * 20);
      const uint32_t zero = lds32(sb + kZero);
      float s0[4][4], s1[4][4], s2[4][4];
#pragma unroll
      for (int k = 0; k < 4; k++) {
        pk[k >> 1][8 * (k & 1)] |= zero;
#pragma unroll
        for (int e = 0; e < 4; e++) s0[k][e] = s1[k][e] = s2[k][e] = 0.f;
      }
#pragma unroll
      for (int ks = 0; ks < 2; ks++)
#pragma unroll
        for (int k = 0; k < 4; k++) {
          const uint32_t* qf = &pk[k >> 1][8 * (k & 1) + 4 * ks];
          const uint32_t* kf = &pk[k >> 1][16 + 8 * (k & 1) + 4 * ks];
          const uint32_t* hf = &hal[k >> 1][4 * (k & 1) + 2 * ks];
          mma16816(s0[k], qf[0], qf[1], qf[2], qf[3], hf[0], hf[1]);
          mma16816(s1[k], qf[0], qf[1], qf[2], qf[3], kf[0], kf[2]);
          mma16816(s2[k], qf[0], qf[1], qf[2], qf[3], kf[1], kf[3]);
        }
      float ea[4][2], eb[4][2], ma[4], mb[4];
#pragma unroll
      for (int k = 0; k < 4; k++) {
        const float *ra = rs[k & 2], *rb = rs[(k & 2) + 1];
        if (no_prev && k < 2) s0[k][0] = s0[k][1] = -INFINITY;
        ea[k][0] = (sel0 ? s0[k][0] : s1[k][0]) * ra[0]; ea[k][1] = (sel1 ? s0[k][1] : s1[k][1]) * ra[1];
        eb[k][0] = (sel0 ? s1[k][2] : s2[k][2]) * rb[0]; eb[k][1] = (sel1 ? s1[k][3] : s2[k][3]) * rb[1];
        ma[k] = fmaxf(ea[k][0], ea[k][1]); mb[k] = fmaxf(eb[k][0], eb[k][1]);
      }
#pragma unroll
      for (int o = 1; o < 4; o <<= 1)
#pragma unroll
        for (int k = 0; k < 4; k++) {
          ma[k] = fmaxf(ma[k], __shfl_xor_sync(~0u, ma[k], o));
          mb[k] = fmaxf(mb[k], __shfl_xor_sync(~0u, mb[k], o));
        }
      float ov[4][4][4], ls[4][4];
      uint32_t all = 0;
#pragma unroll
      for (int k = 0; k < 4; k++) {
        const float *ra = rk[k & 2], *rb = rk[(k & 2) + 1];
        ea[k][0] = ex2(ea[k][0] - ma[k]); ea[k][1] = ex2(ea[k][1] - ma[k]);
        eb[k][0] = ex2(eb[k][0] - mb[k]); eb[k][1] = ex2(eb[k][1] - mb[k]);
        const uint32_t pa = pack_bf16(ea[k][0] * ra[0], ea[k][1] * ra[1]), pb = pack_bf16(eb[k][0] * rb[0], eb[k][1] * rb[1]);
        const uint32_t* vf = &pk[k >> 1][32 + 8 * (k & 1)];
        const uint32_t* hf = &hal[k >> 1][8 + 4 * (k & 1)];
#pragma unroll
        for (int d2 = 0; d2 < 2; d2++) {
#pragma unroll
          for (int e = 0; e < 4; e++) ov[k][d2][e] = ov[k][2 + d2][e] = 0.f;
          mma1688(ov[k][d2], hf[2 * d2], hf[2 * d2 + 1], pa & lowmask);
          mma1688(ov[k][2 + d2], vf[4 * d2], vf[4 * d2 + 2], pb & lowmask);
        }
#pragma unroll
        for (int d2 = 0; d2 < 2; d2++) {
          mma1688(ov[k][d2], vf[4 * d2], vf[4 * d2 + 2], pa & ~lowmask);
          mma1688(ov[k][2 + d2], vf[4 * d2 + 1], vf[4 * d2 + 3], pb & ~lowmask);
        }
        ls[k][0] = ls[k][1] = ls[k][2] = ls[k][3] = 0.f;
        mma16816(ls[k], ones.x, ones.y, ones.z, ones.w, pack_bf16(ea[k][0], ea[k][1]), pack_bf16(eb[k][0], eb[k][1]));
        if (k >= kDone) all |= pa & pb;
      }
#pragma unroll
      for (int k = 0; k < 4; k++) {
        if (k == kDone) {
          if (all == 0xFFFFFFFFu) sts32(sb + kZero + 8, 0);
          nb_arrive(kNbWin + 1, 256);
          all = 0;
        }
        all |= (__float_as_uint(ov[k][0][0]) & __float_as_uint(ov[k][1][0]) & __float_as_uint(ov[k][2][0])) &
               (__float_as_uint(ov[k][3][0]) & __float_as_uint(ls[k][0]));
      }
      const uint32_t nil = lds32(sb + kZero);
      const uint32_t frag = stg + (w * 16 + (lane & 15)) * 128, frag_x = (lane >> 4) ^ (lane & 7);
      uint32_t after = all;
#pragma unroll
      for (int k = 0; k < 4; k++) {
        uint32_t h[2][4];
#pragma unroll
        for (int hf = 0; hf < 2; hf++) {
          const float i0 = rcp(__uint_as_float(__float_as_uint(ls[k][2 * hf]) | (after & nil)));
          const float i1 = rcp(__uint_as_float(__float_as_uint(ls[k][2 * hf + 1]) | (after & nil)));
#pragma unroll
          for (int e = 0; e < 4; e++) h[e >> 1][2 * (e & 1) + hf] = pack_bf16(ov[k][2 * hf + (e >> 1)][2 * (e & 1)] * i0, ov[k][2 * hf + (e >> 1)][2 * (e & 1) + 1] * i1);
          after = h[0][hf];
        }
#pragma unroll
        for (int d2 = 0; d2 < 2; d2++) stsm4_t(frag + (k >> 1) * 8192 + ((frag_x ^ ((k & 1) * 4 + d2 * 2)) << 4), h[d2][0], h[d2][1], h[d2][2], h[d2][3]);
      }
      fence_async_smem();
      if (wg) {
        __syncwarp();
        if (elect_one()) {
          tma_store2d(&p.o16, stg + w * 2048, (8 + c) * 64, r * 128 + w * 16);
          tma_store2d(&p.o16, stg + 8192 + w * 2048, (8 + c) * 64, r * 128 + 64 + w * 16);
          bulk_commit();
          bulk_wait_read();
          mbar_arrive(sb + kBars + 8 * kSentBar);
        }
        __syncwarp();
      } else {
        nb_arrive(kNbPub, 160);
      }
      if (t == 0) TS(3 + wg * 20);
      task = wg;
      sx = mx = bias = 0.f;
      continue;
      }

      {
#pragma unroll 1
        for (int part = task != 2; part < 2; part++) {
          if ((tid & 127) == 0) TS(6 + 2 * task + wg * 20);
          if (task + part == 5) {
            mainloop<128, 0>(sc, acc, sb, 3, 0, 16, -2, false, true, false, 1);
            continue;
          }
          const int j0 = task == 3 ? 48 - wg * 16 : part == 0 ? 2 - 2 * wg : 18 - 14 * wg;
          mainloop<192, 0>(sc, acc, sb, 2, j0, task != 2 ? 16 : part == 0 ? 2 : 14, -2, false, true, part == 0, wg);
          if (part == 0 && wg == 0) {
            const int t = fresh_tid() & 127;
            const uint32_t ep = lds32(sb + kEpoch);
            {
              float s = 0.f, ss = 0.f;
#pragma unroll 1
              for (int i = 0; i < 16; i++) {
                const uint4 v = lds128(sb + kStage + t * 128 + (i >> 3) * 16384 + (((i ^ t) & 7) << 4));
                const uint32_t u[4] = {v.x, v.y, v.z, v.w};
#pragma unroll
                for (int e = 0; e < 4; e++) {
                  const float d0 = bf_lo(u[e]), d1 = bf_hi(u[e]);
                  s = (s + d0) + d1;
                  ss = fmaf(d1, d1, fmaf(d0, d0, ss));
                }
              }
              st_b128(SC_AT(stat2, c * kS + r * 128 + t), __float_as_uint(s), __float_as_uint(ss), ep, ep);
            }
            __nanosleep(kStatNs);
            float2 sum = make_float2(0.f, 0.f);
#pragma unroll 1
            for (int i = 0; i < 2; i++) {
              uint3 a[4];
              load_tagged<4, true>(a, SC_AT(stat2, i * 4 * kS + r * 128 + t), kS, ep);
              sum.x += (__uint_as_float(a[0].x) + __uint_as_float(a[1].x)) + (__uint_as_float(a[2].x) + __uint_as_float(a[3].x));
              sum.y += (__uint_as_float(a[0].y) + __uint_as_float(a[1].y)) + (__uint_as_float(a[2].y) + __uint_as_float(a[3].y));
            }
            const float mean = sum.x * (1.f / kD);
            sts64f(sb + kStat + t * 8, make_float2(fmaxf(sum.y * (1.f / kD) - mean * mean, 0.f) + 1e-5f, -mean));
            __syncwarp();
            if (elect_one()) {
              bulk_commit();
              bulk_wait_read();
              mbar_arrive(sb + kBars + 8 * kStatBar);
            }
            __syncwarp();
            if (t == 0) TS(37);
          }
        }
      }
      const int t = fresh_tid() & 127, w = warp & 3, lane = t & 31, g = lane >> 2, q = lane & 3;
      const uint32_t stg = sb + kStage + wg * 32768;
      uint32_t csv = sb + kCs + wg * 768 + q * 8;
      uint32_t statv = sb + kStat + (w * 16 + g) * 8;
      const uint32_t frag = stg + (w * 16 + (lane & 15)) * 128;
      const uint32_t frag_x = (lane >> 4) ^ (lane & 7);
      const uint32_t priv = stg + (t & 96) * 64 + lane * 16;
      if (t == 0) TSK(7 + 2 * task + wg * 20);

      if (task == 4) {
        mbar_wait(sb + kBars + 8 * (kAuxBar + 1), 1);
        mbar_wait(sb + kBars + 8 * kResFreeBar, 1);
        mbar_wait(sb + kBars + 8 * (kStgBar + 1), 0);
      }
      asm volatile("" : "+r"(csv), "+r"(statv)::"memory");

      {
#pragma unroll
        for (int i = 0; i < 96; i++) asm volatile("sub.f32 %0, %0, %1;" : "+f"(acc[0][i]) : "f"(bias));
#define NEXT(i) asm volatile("sub.f32 %0, %1, %2;" : "=f"(acc[0][i]) : "f"(acc[1][i]), "f"(bias))
#pragma unroll 1
        for (int pp = 0; pp < 2; pp++) {
          TSG(pp);
          RowConst rc[2];
#pragma unroll
          for (int hf = 0; hf < 2; hf++) {
            const float2 st = lds64f_const(statv + pp * 512 + hf * 64);
            float rstd;
            asm("rsqrt.approx.ftz.f32 %0, %1;" : "=f"(rstd) : "f"(st.x));
            rc[hf] = {st.y, 0.7978845608f * rstd, 0.0356774081f * rstd * rstd * rstd, 0.5f * rstd * rstd};
          }
#pragma unroll
          for (int j2 = 0; j2 < 4; j2++) {
            uint32_t hv[4];
#pragma unroll
            for (int jj = 0; jj < 2; jj++) {
              const int jn = 2 * j2 + jj;
              const float2 cg = lds64f_const(csv + jn * 32), cu = lds64f_const(csv + 256 + jn * 32);
#pragma unroll
              for (int hf = 0; hf < 2; hf++) {
                const float nm = rc[hf].nmean;
                const float g0 = fmaf(nm, cg.x, acc[0][4 * jn + 2 * hf]), g1 = fmaf(nm, cg.y, acc[0][4 * jn + 2 * hf + 1]);
                const float u0 = fmaf(nm, cu.x, acc[0][32 + 4 * jn + 2 * hf]), u1 = fmaf(nm, cu.y, acc[0][33 + 4 * jn + 2 * hf]);
                hv[2 * jj + hf] = pack_bf16(g0 * u0 * gate_scale(g0, rc[hf]), g1 * u1 * gate_scale(g1, rc[hf]));
              }
            }
            stsm4(frag + 16384 + pp * 8192 + ((frag_x ^ (j2 * 2)) << 4), hv[0], hv[1], hv[2], hv[3]);
          }
          if (task < 4) {
            if (task == 2) {
#pragma unroll
              for (int j2 = 0; j2 < 4; j2++) {
                uint32_t hv[4];
#pragma unroll
                for (int jj = 0; jj < 2; jj++) {
                  const int jn = 16 + 2 * j2 + jj;
                  const float2 cs = lds64f_const(csv + jn * 32);
#pragma unroll
                  for (int hf = 0; hf < 2; hf++) {
                    const float nm = rc[hf].nmean;
                    const float t0 = fmaf(nm, cs.x, acc[0][4 * jn + 2 * hf]), t1 = fmaf(nm, cs.y, acc[0][4 * jn + 2 * hf + 1]);
                    hv[2 * jj + hf] = pack_bf16(t0 * gate_scale(t0, rc[hf]), t1 * gate_scale(t1, rc[hf]));
                  }
                }
                sts128(priv + pp * 8192 + j2 * 512, make_uint4(hv[0], hv[1], hv[2], hv[3]));
              }
            } else {
              uint4 park[4];
#pragma unroll
              for (int j2 = 0; j2 < 4; j2++) park[j2] = lds128(priv + pp * 8192 + j2 * 512);
              __syncwarp();
#pragma unroll
              for (int j2 = 0; j2 < 4; j2++) {
                const uint32_t pv[4] = {park[j2].x, park[j2].y, park[j2].z, park[j2].w};
                uint32_t hv[4];
#pragma unroll
                for (int jj = 0; jj < 2; jj++) {
                  const int jn = 16 + 2 * j2 + jj;
                  const float2 cs = lds64f_const(csv + jn * 32);
#pragma unroll
                  for (int hf = 0; hf < 2; hf++) {
                    const float nm = rc[hf].nmean;
                    const float t0 = fmaf(nm, cs.x, acc[0][4 * jn + 2 * hf]), t1 = fmaf(nm, cs.y, acc[0][4 * jn + 2 * hf + 1]);
                    asm("mul.rn.bf16x2 %0, %1, %2;" : "=r"(hv[2 * jj + hf]) : "r"(pack_bf16(t0, t1)), "r"(pv[2 * jj + hf]));
                  }
                }
                stsm4(frag + pp * 8192 + ((frag_x ^ (j2 * 2)) << 4), hv[0], hv[1], hv[2], hv[3]);
              }
            }
            if (pp == 1) break;
#pragma unroll
            for (int i = 64; i < 96; i++) NEXT(i);
          }
          if (pp == 1) break;
#pragma unroll
          for (int i = 0; i < 64; i++) NEXT(i);
        }
      }
      const int t3 = fresh_tid() & 127;
      uint4* part = SC_AT(part, bid * 1024 + (t3 & 96) * 8 + (t3 & 31));
      if (task == 2 && wg) {
#pragma unroll
        for (int k = 0; k < 8; k++) st_b128(part + k * 32, kPoison, kPoison, kPoison, kPoison);
      }
      fence_async_smem();
      nb_arrive(kNbPub + wg, 160);
      if (t == 0) TS(task == 4 ? 57 : 56 + task + wg * 2);
      if (task == 4) {
        mbar_wait(sb + kBars + 8 * kPartBar, 0);
        const bool none = lds32(sb + kPlan) == 0;
#pragma unroll 1
        for (int b = 1, spins = 0; b >= 0;) {
          uint4 v[4] = {};
          uint32_t top = 0;
          if (!none) {
#pragma unroll
            for (int k = 0; k < 4; k++) v[k] = ld_b128(part + (128 + k * 32));
          }
#pragma unroll
          for (int k = 0; k < 4; k++) {
            top = max(max(top, v[k].x), max(v[k].y, max(v[k].z, v[k].w)));
          }
          if (__any_sync(~0u, top == kPoison)) {
            if (++spins > 100000) __trap();
            __nanosleep(kPartNs);
            continue;
          }
#pragma unroll
          for (int k = 0; k < 4; k++) {
            uint32_t h[4];
            ldsm4(frag + 16384 + b * 8192 + ((frag_x ^ (k * 2)) << 4), h);
            asm("add.rn.bf16x2 %0, %0, %1;" : "+r"(v[k].x) : "r"(h[0]));
            asm("add.rn.bf16x2 %0, %0, %1;" : "+r"(v[k].y) : "r"(h[1]));
            asm("add.rn.bf16x2 %0, %0, %1;" : "+r"(v[k].z) : "r"(h[2]));
            asm("add.rn.bf16x2 %0, %0, %1;" : "+r"(v[k].w) : "r"(h[3]));
            sts128(stg + (t3 & 96) * 128 + (t3 & 31) * 16 + b * 2048 + k * 512, v[k]);
          }
          b--;
          part -= 128;
        }
        if (t == 0) TSK(56);
        nb_arrive(kNbPart, 256);
        break;
      }
      sx = mx = 0.f;
    }
  }
}

typedef CUresult (*EncodeTiledFn)(CUtensorMap*, CUtensorMapDataType, cuuint32_t, void*, const cuuint64_t*, const cuuint64_t*,
                                  const cuuint32_t*, const cuuint32_t*, CUtensorMapInterleave, CUtensorMapSwizzle,
                                  CUtensorMapL2promotion, CUtensorMapFloatOOBfill);

void encode(EncodeTiledFn fn, CUtensorMap* m, const void* base, int rank, cuuint64_t d0, cuuint64_t d1, cuuint64_t d2,
            cuuint64_t s1, cuuint64_t s2, cuuint32_t b2, cuuint32_t b1 = 64) {
  const cuuint64_t dims[3] = {d0, d1, d2}, strides[2] = {s1, s2};
  const cuuint32_t box[3] = {64, b1, b2}, es[3] = {1, 1, 1};
  fn(m, CU_TENSOR_MAP_DATA_TYPE_BFLOAT16, rank, const_cast<void*>(base), dims, strides, box, es, CU_TENSOR_MAP_INTERLEAVE_NONE,
     CU_TENSOR_MAP_SWIZZLE_128B, CU_TENSOR_MAP_L2_PROMOTION_L2_128B, CU_TENSOR_MAP_FLOAT_OOB_FILL_NONE);
}

}

extern "C" void kernel_launch(void* const* d_in, const int* in_sizes, int n_in, void* d_out, int out_size) {
  void* fnp = nullptr;
  cudaDriverEntryPointQueryResult qr;
  cudaGetDriverEntryPoint("cuTensorMapEncodeTiled", &fnp, cudaEnableDefault, &qr);
  EncodeTiledFn fn = (EncodeTiledFn)fnp;
  void *o, *h, *hh;
  cudaGetSymbolAddress(&o, g_o);
  cudaGetSymbolAddress(&h, g_h);
  cudaGetSymbolAddress(&hh, g_hh);

  Params p;
  Scratch* sc;
  cudaGetSymbolAddress((void**)&sc, g_scratch);
  encode(fn, &p.x, d_in[0], 3, kD, kS / 2, 2, 4 * kD, 2 * kD, 1, 128);
  encode(fn, &p.out, d_out, 3, kD, kS / 2, 2, 4 * kD, 2 * kD, 1, 16);
  encode(fn, &p.wqkv, d_in[1], 2, 3 * kD, kD, 1, 6 * kD, 0, 1);
  encode(fn, &p.wo, d_in[2], 2, kD, kD, 1, 2 * kD, 0, 1);
  encode(fn, &p.wd, d_in[6], 2, kD, kF, 1, 2 * kD, 0, 1);
  encode(fn, &p.wg, d_in[4], 2, kF, kD, 1, 2 * kF, 0, 1);
  encode(fn, &p.wu, d_in[5], 2, kF, kD, 1, 2 * kF, 0, 1);
  encode(fn, &p.o, o, 2, kD, kS, 1, 2 * kD, 0, 1, 128);
  encode(fn, &p.h, h, 2, kD, kS, 1, 2 * kD, 0, 1, 128);
  encode(fn, &p.hh, hh, 2, kF, kS, 1, 2 * kF, 0, 1, 128);
  encode(fn, &p.ost, o, 2, kD, kS, 1, 2 * kD, 0, 1);
  encode(fn, &p.o16, o, 2, kD, kS, 1, 2 * kD, 0, 1, 16);
  encode(fn, &p.h16, h, 2, kD, kS, 1, 2 * kD, 0, 1, 16);
  encode(fn, &p.hst, h, 2, kD, kS, 1, 2 * kD, 0, 1);
  encode(fn, &p.hhst, hh, 2, kF, kS, 1, 2 * kF, 0, 1);
  for (int c = 0; c < 8; c++) {
    for (int j = 0; j < 32; j++) p.g1[c][j] = g1_block(j, c) | (j >= 16 && (j < 20 || g1_block(j, c) >> 1 == c) ? kInPlace : 0);
    for (int j = 0; j < 16; j++) p.g2[c][j] = g2_block(j, c);
    for (int j = 0; j < 64; j++)
      p.g3[c][j] = g3_block(j, c) | ((0x000F000F003C000Full >> j & 1) && j != 28 + c ? kInPlace : 0) | g3_tile(j) << 5;
  }
  for (int i = 0; i < 56; i++)
    p.g4[i] = g4_block(i) | (i >= kFirstShared && i % 3 == 0 && i < kFirstShared + 3 * kMost ? kShared : 0) | (i % 24 == 0 ? kNextWave : 0);
  p.wop = (const uint4*)d_in[2];
  p.wgp = (const uint4*)d_in[4];
  p.wup = (const uint4*)d_in[5];

  int dev = 0, sms = 0;
  cudaGetDevice(&dev);
  cudaDeviceGetAttribute(&sms, cudaDevAttrMultiProcessorCount, dev);
  auto* kernel = sms == 132 ? fused_block_kernel<true> : fused_block_kernel<false>;
  cudaFuncSetAttribute(kernel, cudaFuncAttributeMaxDynamicSharedMemorySize, kSmemBytes);
  kernel<<<132, kThreads, kSmemBytes, cudaStreamPerThread>>>(sc, (const __nv_bfloat16*)d_in[0], (const __nv_bfloat16*)d_in[1],
                                                                  (__nv_bfloat16*)d_out, p);
}
```

```cpp
#include <cuda_runtime.h>
#include <cuda_bf16.h>
#include <cuda.h>
#include <stddef.h>
#include <stdint.h>

namespace {

constexpr int kS = 2048, kD = 1024, kF = 3584;
constexpr int kThreads = 384;

constexpr int kRing = 0;
constexpr int kStage = 163840;
constexpr int kAug = kStage + 16384;
constexpr int kOwn = kStage + 32768;
constexpr int kFill = kStage + 24576;
constexpr int kCs = kStage + 65536;
constexpr int kStat = kCs + 1536;
constexpr int kBars = kStat + 1024;
constexpr int kSmemBytes = kBars + 512;
constexpr int kResBar = 38;
constexpr int kAuxBar = 39;
constexpr int kStgBar = 41;
constexpr int kResFreeBar = 43;
constexpr int kStatBar = 44;
constexpr int kPartBar = 45;
constexpr int kWaveBar = 46;
constexpr int kHalfBar = 49;
constexpr int kSentBar = 51;
constexpr int kLandBar = 52;
constexpr int kNumBars = 58;
static_assert(kNumBars == 4 + 3 * 18, "barrier initialisation is split 4 + 3 x 18");
__host__ __device__ constexpr int bar_count(int i) {
  const int ph = i < 8 ? 0 : i < 18 ? 1 : i < 26 ? 2 : 3, base = ph * 9 - (ph & 1);
  return i < 38 ? (i - base < 4 + (ph & 1) + (ph == 3) ? 2 : ph == 0 ? 16 : 8) : i == kResFreeBar || i == kStatBar || (i >= kHalfBar && i < kLandBar) ? 4 : 1;
}
__host__ __device__ constexpr uint64_t bar_shifts(int first) {
  uint64_t m = 0;
  for (int i = 17; i >= 0; i--) {
    const int n = bar_count(first + i);
    m = m << 3 | (n == 16 ? 4 : n == 8 ? 3 : n >> 1);
  }
  return m;
}
constexpr int kScale = kBars + 464;
constexpr int kPlan = kBars + 472;
constexpr int kOnes = kBars + 480;
constexpr int kZero = kBars + 496;
constexpr int kRole = kBars + 508;
constexpr int kEpoch = kBars + 500;
__device__ __forceinline__ int ring_base(int ph) { return ph * 9 - (ph & 1); }
constexpr int kWide = 25;
constexpr int kFirstShared = 15;
constexpr int kNbOrder = 1;
constexpr int kNbWg = 3;
constexpr int kNbPub = 5;
constexpr int kNbWin = 7;
constexpr int kNbSelf = 13;
constexpr int kNbPart = 11;
constexpr int kNbHalo = 9;

constexpr int kFlO = 0;
constexpr int kFlPace = 1;
constexpr int kFlHH = 3;
constexpr int kFlRow = 32;
constexpr int kNumFlags = 16 * kFlRow;

constexpr int kPauseG1 = 7;
constexpr int kPauseG2 = 1;
constexpr int kAhead = 2;
constexpr int kSplit = 13;
constexpr int kTail = 4;
constexpr int kPartAt = 2;
constexpr int kShare = 5;
constexpr int kMost = 8;
constexpr int kBudget = 328;
constexpr int kStepNs = 167;
constexpr int kRemain = 65500;
constexpr int kDone = 3;
constexpr int kQuietAt = 48;
constexpr int kPfStep = 8;
constexpr int kBackoffNs = 200;
constexpr int kPaceNs = 300;
constexpr int kPartNs = 500;
constexpr int kFillNs = 500;
constexpr int kHaloNs = 150;
constexpr int kGateONs = 150;
constexpr int kGateHNs = 150;
constexpr int kHoldNs = 1200;
constexpr int kSampleNs = 1000;
constexpr int kStatNs = 1500;
constexpr float kBias1 = 512.f, kBias3 = 32768.f;

struct Scratch {
  uint32_t flags[kNumFlags];
  uint32_t epoch[32];
  uint4 stat1[kS];
  uint4 stat2[8 * kS];
  uint4 cs[7 * 8 * 96];
  uint2 finish[128];
  uint2 plan[16];
  uint4 halo[2 * 16 * 8 * 6 * 32];
  uint4 part[128 * 8 * 128];
};
struct Params {
  CUtensorMap x, wqkv, o, wo, h, wg, wu, hh, wd, out;
  CUtensorMap ost, hst, hhst;
  CUtensorMap o16, h16;
  const uint4 *wop, *wgp, *wup;
  uint8_t g1[8][32], g2[8][16], g3[8][64], g4[56];
};

__device__ __align__(256) __nv_bfloat16 g_o[kS * kD];
__device__ __align__(256) __nv_bfloat16 g_h[kS * kD];
__device__ __align__(256) __nv_bfloat16 g_hh[kS * kF];
__device__ __align__(256) Scratch g_scratch;

template <bool BY_SM>
__device__ __forceinline__ int role_id() {
  uint32_t sm;
  asm("mov.u32 %0, %%smid;" : "=r"(sm));
  const int tpc = (BY_SM ? sm : blockIdx.x) >> 1, rank = blockIdx.x & 1;
  if ((tpc | 1) == 61) return 8 + 2 * tpc + rank;
  const int u = tpc - 32, s7 = (u * 37) >> 8;
  const int g = tpc < 32 ? tpc & 7 : tpc < 60 ? 1 + u - 7 * s7 : 0, s = tpc < 32 ? tpc >> 3 : tpc < 60 ? 4 + s7 : tpc - 58;
  return (g * 2 + rank) * 8 + s;
}
#define TS(i) do { } while (0)
#define TSK(i) do { } while (0)
#define TSS(i) do { } while (0)
#define TST(i)
#define TSG(i)

__device__ __forceinline__ uint32_t smem_u32(const void* p) { return (uint32_t)__cvta_generic_to_shared(p); }
template <class T>
__device__ __forceinline__ T* plus(T* p, uint32_t n) {
  uint64_t r;
  asm("{\n.reg .b32 lo, hi;\nmov.b64 {lo, hi}, %1;\nadd.cc.u32 lo, lo, %2;\naddc.u32 hi, hi, 0;\nmov.b64 %0, {lo, hi};\n}\n"
      : "=l"(r) : "l"(p), "r"(n * (uint32_t)sizeof(T)));
  return (T*)r;
}
#define SC_AT(member, n) ((decltype(+sc->member))((char*)plus((decltype(+sc->member))sc, n) + offsetof(Scratch, member)))
__device__ __forceinline__ void mbar_init(uint32_t bar, uint32_t cnt) {
  asm volatile("mbarrier.init.shared::cta.b64 [%0], %1;" ::"r"(bar), "r"(cnt));
}
__device__ __forceinline__ void mbar_expect_tx(uint32_t bar, uint32_t bytes) {
  asm volatile("mbarrier.arrive.expect_tx.shared::cta.b64 _, [%0], %1;" ::"r"(bar), "r"(bytes) : "memory");
}
__device__ __forceinline__ uint32_t map_cta(uint32_t addr, uint32_t cta) {
  uint32_t r;
  asm("mapa.shared::cluster.u32 %0, %1, %2;" : "=r"(r) : "r"(addr), "r"(cta));
  return r;
}
__device__ __forceinline__ void mbar_arrive_cluster_if(uint32_t bar, bool cond) {
  asm volatile("{\n.reg .pred p;\nsetp.ne.u32 p, %1, 0;\n@p mbarrier.arrive.shared::cluster.b64 _, [%0];\n}\n"
               ::"r"(bar), "r"((uint32_t)cond) : "memory");
}
__device__ __forceinline__ void mbar_wait(uint32_t bar, uint32_t parity) {
  asm volatile("{\n.reg .pred p;\nLAB_WAIT:\nmbarrier.try_wait.parity.shared::cta.b64 p, [%0], %1;\n@!p bra LAB_WAIT;\n}\n"
               ::"r"(bar), "r"(parity) : "memory");
  return;
  asm volatile("{\n.reg .pred p;\n.reg .u32 c;\nmov.u32 c, 0;\n"
               "LAB_WAIT:\nmbarrier.try_wait.parity.shared::cta.b64 p, [%0], %1;\n@p bra LAB_DONE;\n"
               "add.u32 c, c, 1;\nsetp.lt.u32 p, c, 2000000;\n@p bra LAB_WAIT;\ntrap;\nLAB_DONE:\n}\n"
               ::"r"(bar), "r"(parity) : "memory");
}
__device__ __forceinline__ void mbar_arrive(uint32_t bar) {
  asm volatile("mbarrier.arrive.shared::cta.b64 _, [%0];" ::"r"(bar) : "memory");
}
__device__ __forceinline__ void flag_signal(uint32_t* flag) {
  asm volatile("red.release.gpu.global.add.u32 [%0], 1;" ::"l"(flag) : "memory");
}
__device__ __forceinline__ void st_b128(uint4* p, uint32_t a, uint32_t b, uint32_t c, uint32_t d) {
  asm volatile("{\n.reg .b128 t;\n.reg .b64 lo, hi;\nmov.b64 lo, {%1,%2};\nmov.b64 hi, {%3,%4};\nmov.b128 t, {lo, hi};\n"
               "st.relaxed.gpu.global.b128 [%0], t;\n}\n" ::"l"(p), "r"(a), "r"(b), "r"(c), "r"(d) : "memory");
}
__device__ __forceinline__ uint4 ld_b128(const uint4* p) {
  uint4 v;
  asm volatile("{\n.reg .b128 t;\n.reg .b64 lo, hi;\nld.relaxed.gpu.global.b128 t, [%4];\nmov.b128 {lo, hi}, t;\n"
               "mov.b64 {%0,%1}, lo;\nmov.b64 {%2,%3}, hi;\n}\n" : "=r"(v.x), "=r"(v.y), "=r"(v.z), "=r"(v.w) : "l"(p) : "memory");
  return v;
}
__device__ __forceinline__ uint32_t ld_epoch(Scratch* sc) {
  uint32_t v;
  asm volatile("ld.relaxed.gpu.global.u32 %0, [%1];" : "=r"(v) : "l"(sc->epoch) : "memory");
  return v + 1;
}
__device__ __forceinline__ void flag_wait(uint32_t* flag, uint32_t target) {
  asm volatile("{\n.reg .pred p;\n.reg .u32 c, v;\nmov.u32 c, 0;\n"
               "LAB_WAIT:\nld.relaxed.gpu.global.u32 v, [%0];\nsub.u32 v, v, %1;\nsetp.ge.s32 p, v, 0;\n@p bra LAB_DONE;\n"
               "add.u32 c, c, 1;\nsetp.lt.u32 p, c, 4000000;\n@p bra LAB_WAIT;\ntrap;\nLAB_DONE:\n}\n"
               ::"l"(flag), "r"(target) : "memory");
}
__device__ __forceinline__ void send_word(uint2* p, uint32_t v, uint32_t tag) {
  asm volatile("{\n.reg .b64 t;\nmov.b64 t, {%1, %2};\nst.relaxed.gpu.global.b64 [%0], t;\n}\n" ::"l"(p), "r"(v), "r"(tag) : "memory");
}
__device__ __forceinline__ uint32_t await_word(const uint2* p, uint32_t tag) {
  uint32_t v;
  asm volatile("{\n.reg .pred p;\n.reg .u32 c, g;\n.reg .b64 t;\nmov.u32 c, 0;\n"
               "LAB_WAIT:\nld.relaxed.gpu.global.b64 t, [%1];\nmov.b64 {%0, g}, t;\nsetp.eq.u32 p, g, %2;\n@p bra LAB_DONE;\n"
               "add.u32 c, c, 1;\nsetp.lt.u32 p, c, 4000000;\n@p bra LAB_WAIT;\ntrap;\nLAB_DONE:\n}\n"
               : "=r"(v) : "l"(p), "r"(tag) : "memory");
  return v;
}
__device__ __forceinline__ uint32_t global_ns() {
  uint32_t v;
  asm volatile("mov.u32 %0, %%globaltimer_lo;" : "=r"(v));
  return v;
}
__device__ __forceinline__ int fresh_tid() {
  int v;
  asm volatile("mov.u32 %0, %%tid.x;" : "=r"(v));
  return v;
}
constexpr uint32_t kPoison = 0xFFFFFFFFu;
__device__ __forceinline__ bool elect_one() {
  uint32_t p;
  asm volatile("{\n.reg .pred P;\nelect.sync _|P, 0xffffffff;\nselp.u32 %0, 1, 0, P;\n}\n" : "=r"(p));
  return p != 0;
}
__device__ __forceinline__ void fence_async() { asm volatile("fence.acquire.gpu;\nfence.proxy.async.global;" ::: "memory"); }
__device__ __forceinline__ void fence_async_smem() { asm volatile("fence.proxy.async.shared::cta;" ::: "memory"); }
__device__ __forceinline__ void nb_sync(int id, int n) { asm volatile("bar.sync %0, %1;" ::"r"(id), "r"(n) : "memory"); }
__device__ __forceinline__ void nb_arrive(int id, int n) { asm volatile("bar.arrive %0, %1;" ::"r"(id), "r"(n) : "memory"); }

__device__ __forceinline__ void tma2d(uint32_t dst, const CUtensorMap* m, int c0, int c1, uint32_t bar) {
  asm volatile("cp.async.bulk.tensor.2d.shared::cluster.global.mbarrier::complete_tx::bytes [%0], [%1, {%3, %4}], [%2];"
               ::"r"(dst), "l"(m), "r"(bar), "r"(c0), "r"(c1) : "memory");
}
__device__ __forceinline__ void tma2d_mc(uint32_t dst, const CUtensorMap* m, int c0, int c1, uint32_t bar) {
  asm volatile("cp.async.bulk.tensor.2d.shared::cluster.global.mbarrier::complete_tx::bytes.multicast::cluster"
               " [%0], [%1, {%3, %4}], [%2], %5;"
               ::"r"(dst), "l"(m), "r"(bar), "r"(c0), "r"(c1), "h"((uint16_t)3) : "memory");
}
__device__ __forceinline__ void tma3d(uint32_t dst, const CUtensorMap* m, int c0, int c1, int c2, uint32_t bar) {
  asm volatile("cp.async.bulk.tensor.3d.shared::cluster.global.mbarrier::complete_tx::bytes [%0], [%1, {%3, %4, %5}], [%2];"
               ::"r"(dst), "l"(m), "r"(bar), "r"(c0), "r"(c1), "r"(c2) : "memory");
}
__device__ __forceinline__ void tma_store2d(const CUtensorMap* m, uint32_t src, int c0, int c1) {
  asm volatile("cp.async.bulk.tensor.2d.global.shared::cta.bulk_group [%0, {%2, %3}], [%1];"
               ::"l"(m), "r"(src), "r"(c0), "r"(c1) : "memory");
}
__device__ __forceinline__ void tma_store3d(const CUtensorMap* m, uint32_t src, int c0, int c1, int c2) {
  asm volatile("cp.async.bulk.tensor.3d.global.shared::cta.bulk_group [%0, {%2, %3, %4}], [%1];"
               ::"l"(m), "r"(src), "r"(c0), "r"(c1), "r"(c2) : "memory");
}
__device__ __forceinline__ void tma_prefetch2d(const CUtensorMap* m, int c0, int c1) {
  asm volatile("cp.async.bulk.prefetch.tensor.2d.L2.global [%0, {%1, %2}];" ::"l"(m), "r"(c0), "r"(c1) : "memory");
}
__device__ __forceinline__ void prefetch_map(const CUtensorMap* m) { asm volatile("prefetch.tensormap [%0];" ::"l"(m) : "memory"); }
__device__ __forceinline__ void bulk_commit() { asm volatile("cp.async.bulk.commit_group;" ::: "memory"); }
__device__ __forceinline__ void bulk_wait_all() { asm volatile("cp.async.bulk.wait_group 0;" ::: "memory"); }
__device__ __forceinline__ void bulk_wait_read() { asm volatile("cp.async.bulk.wait_group.read 0;" ::: "memory"); }
__device__ __forceinline__ void prefetch_l2(const void* p) { asm volatile("prefetch.global.L2 [%0];" ::"l"(p)); }
__device__ __forceinline__ void cluster_arrive() { asm volatile("barrier.cluster.arrive.relaxed.aligned;" ::: "memory"); }
__device__ __forceinline__ void cluster_wait() { asm volatile("barrier.cluster.wait.aligned;" ::: "memory"); }

__device__ __forceinline__ void wg_fence() { asm volatile("wgmma.fence.sync.aligned;" ::: "memory"); }
__device__ __forceinline__ void wg_commit() { asm volatile("wgmma.commit_group.sync.aligned;" ::: "memory"); }
template <int N> __device__ __forceinline__ void wg_wait() { asm volatile("wgmma.wait_group.sync.aligned %0;" ::"n"(N) : "memory"); }
__device__ __forceinline__ uint32_t desc_lo(uint32_t addr, uint32_t lbo) { return ((addr & 0x3FFFF) >> 4) | ((lbo >> 4) << 16); }
__device__ __forceinline__ uint64_t desc(uint32_t lo) { return (uint64_t)lo | (0x40000040ull << 32); }
__device__ __forceinline__ uint64_t desc_kept(uint32_t lo, uint32_t sb) { return (uint64_t)lo | (uint64_t)(0x40000040u | sb >> 31) << 32; }
constexpr int kToB = (16384 >> 4) + ((8192 - 16) >> 4 << 16);

__device__ __forceinline__ void wgmma_n128(float (&d)[96], uint64_t da, uint64_t db, int add = 1) {
  asm volatile(
      "{\n.reg .pred p;\nsetp.ne.b32 p, %66, 0;\n"
      "wgmma.mma_async.sync.aligned.m64n128k16.f32.bf16.bf16 {"
      "%0, %1, %2, %3, %4, %5, %6, %7, %8, %9, %10, %11, %12, %13, %14, %15, "
      "%16, %17, %18, %19, %20, %21, %22, %23, %24, %25, %26, %27, %28, %29, %30, %31, "
      "%32, %33, %34, %35, %36, %37, %38, %39, %40, %41, %42, %43, %44, %45, %46, %47, "
      "%48, %49, %50, %51, %52, %53, %54, %55, %56, %57, %58, %59, %60, %61, %62, %63}, "
      "%64, %65, p, 1, 1, 0, 1;\n}\n"
      :
        "+f"(d[0]), "+f"(d[1]), "+f"(d[2]), "+f"(d[3]), "+f"(d[4]), "+f"(d[5]), "+f"(d[6]), "+f"(d[7]),
        "+f"(d[8]), "+f"(d[9]), "+f"(d[10]), "+f"(d[11]), "+f"(d[12]), "+f"(d[13]), "+f"(d[14]), "+f"(d[15]),
        "+f"(d[16]), "+f"(d[17]), "+f"(d[18]), "+f"(d[19]), "+f"(d[20]), "+f"(d[21]), "+f"(d[22]), "+f"(d[23]),
        "+f"(d[24]), "+f"(d[25]), "+f"(d[26]), "+f"(d[27]), "+f"(d[28]), "+f"(d[29]), "+f"(d[30]), "+f"(d[31]),
        "+f"(d[32]), "+f"(d[33]), "+f"(d[34]), "+f"(d[35]), "+f"(d[36]), "+f"(d[37]), "+f"(d[38]), "+f"(d[39]),
        "+f"(d[40]), "+f"(d[41]), "+f"(d[42]), "+f"(d[43]), "+f"(d[44]), "+f"(d[45]), "+f"(d[46]), "+f"(d[47]),
        "+f"(d[48]), "+f"(d[49]), "+f"(d[50]), "+f"(d[51]), "+f"(d[52]), "+f"(d[53]), "+f"(d[54]), "+f"(d[55]),
        "+f"(d[56]), "+f"(d[57]), "+f"(d[58]), "+f"(d[59]), "+f"(d[60]), "+f"(d[61]), "+f"(d[62]), "+f"(d[63])
      : "l"(da), "l"(db), "r"(add));
}

__device__ __forceinline__ void wgmma_n192(float (&d)[96], uint64_t da, uint64_t db, int add = 1) {
  asm volatile(
      "{\n.reg .pred p;\nsetp.ne.b32 p, %98, 0;\n"
      "wgmma.mma_async.sync.aligned.m64n192k16.f32.bf16.bf16 {"
      "%0, %1, %2, %3, %4, %5, %6, %7, %8, %9, %10, %11, %12, %13, %14, %15, "
      "%16, %17, %18, %19, %20, %21, %22, %23, %24, %25, %26, %27, %28, %29, %30, %31, "
      "%32, %33, %34, %35, %36, %37, %38, %39, %40, %41, %42, %43, %44, %45, %46, %47, "
      "%48, %49, %50, %51, %52, %53, %54, %55, %56, %57, %58, %59, %60, %61, %62, %63, "
      "%64, %65, %66, %67, %68, %69, %70, %71, %72, %73, %74, %75, %76, %77, %78, %79, "
      "%80, %81, %82, %83, %84, %85, %86, %87, %88, %89, %90, %91, %92, %93, %94, %95}, "
      "%96, %97, p, 1, 1, 0, 1;\n}\n"
      :
        "+f"(d[0]), "+f"(d[1]), "+f"(d[2]), "+f"(d[3]), "+f"(d[4]), "+f"(d[5]), "+f"(d[6]), "+f"(d[7]),
        "+f"(d[8]), "+f"(d[9]), "+f"(d[10]), "+f"(d[11]), "+f"(d[12]), "+f"(d[13]), "+f"(d[14]), "+f"(d[15]),
        "+f"(d[16]), "+f"(d[17]), "+f"(d[18]), "+f"(d[19]), "+f"(d[20]), "+f"(d[21]), "+f"(d[22]), "+f"(d[23]),
        "+f"(d[24]), "+f"(d[25]), "+f"(d[26]), "+f"(d[27]), "+f"(d[28]), "+f"(d[29]), "+f"(d[30]), "+f"(d[31]),
        "+f"(d[32]), "+f"(d[33]), "+f"(d[34]), "+f"(d[35]), "+f"(d[36]), "+f"(d[37]), "+f"(d[38]), "+f"(d[39]),
        "+f"(d[40]), "+f"(d[41]), "+f"(d[42]), "+f"(d[43]), "+f"(d[44]), "+f"(d[45]), "+f"(d[46]), "+f"(d[47]),
        "+f"(d[48]), "+f"(d[49]), "+f"(d[50]), "+f"(d[51]), "+f"(d[52]), "+f"(d[53]), "+f"(d[54]), "+f"(d[55]),
        "+f"(d[56]), "+f"(d[57]), "+f"(d[58]), "+f"(d[59]), "+f"(d[60]), "+f"(d[61]), "+f"(d[62]), "+f"(d[63]),
        "+f"(d[64]), "+f"(d[65]), "+f"(d[66]), "+f"(d[67]), "+f"(d[68]), "+f"(d[69]), "+f"(d[70]), "+f"(d[71]),
        "+f"(d[72]), "+f"(d[73]), "+f"(d[74]), "+f"(d[75]), "+f"(d[76]), "+f"(d[77]), "+f"(d[78]), "+f"(d[79]),
        "+f"(d[80]), "+f"(d[81]), "+f"(d[82]), "+f"(d[83]), "+f"(d[84]), "+f"(d[85]), "+f"(d[86]), "+f"(d[87]),
        "+f"(d[88]), "+f"(d[89]), "+f"(d[90]), "+f"(d[91]), "+f"(d[92]), "+f"(d[93]), "+f"(d[94]), "+f"(d[95])
      : "l"(da), "l"(db), "r"(add));
}

__device__ __forceinline__ void wgmma_n192_any(float (&d)[96], uint64_t da, uint64_t db) {
  asm volatile(
      "wgmma.mma_async.sync.aligned.m64n192k16.f32.bf16.bf16 {"
      "%0, %1, %2, %3, %4, %5, %6, %7, %8, %9, %10, %11, %12, %13, %14, %15, "
      "%16, %17, %18, %19, %20, %21, %22, %23, %24, %25, %26, %27, %28, %29, %30, %31, "
      "%32, %33, %34, %35, %36, %37, %38, %39, %40, %41, %42, %43, %44, %45, %46, %47, "
      "%48, %49, %50, %51, %52, %53, %54, %55, %56, %57, %58, %59, %60, %61, %62, %63, "
      "%64, %65, %66, %67, %68, %69, %70, %71, %72, %73, %74, %75, %76, %77, %78, %79, "
      "%80, %81, %82, %83, %84, %85, %86, %87, %88, %89, %90, %91, %92, %93, %94, %95}, "
      "%96, %97, 0, 1, 1, 0, 1;\n"
      :
        "=f"(d[0]), "=f"(d[1]), "=f"(d[2]), "=f"(d[3]), "=f"(d[4]), "=f"(d[5]), "=f"(d[6]), "=f"(d[7]),
        "=f"(d[8]), "=f"(d[9]), "=f"(d[10]), "=f"(d[11]), "=f"(d[12]), "=f"(d[13]), "=f"(d[14]), "=f"(d[15]),
        "=f"(d[16]), "=f"(d[17]), "=f"(d[18]), "=f"(d[19]), "=f"(d[20]), "=f"(d[21]), "=f"(d[22]), "=f"(d[23]),
        "=f"(d[24]), "=f"(d[25]), "=f"(d[26]), "=f"(d[27]), "=f"(d[28]), "=f"(d[29]), "=f"(d[30]), "=f"(d[31]),
        "=f"(d[32]), "=f"(d[33]), "=f"(d[34]), "=f"(d[35]), "=f"(d[36]), "=f"(d[37]), "=f"(d[38]), "=f"(d[39]),
        "=f"(d[40]), "=f"(d[41]), "=f"(d[42]), "=f"(d[43]), "=f"(d[44]), "=f"(d[45]), "=f"(d[46]), "=f"(d[47]),
        "=f"(d[48]), "=f"(d[49]), "=f"(d[50]), "=f"(d[51]), "=f"(d[52]), "=f"(d[53]), "=f"(d[54]), "=f"(d[55]),
        "=f"(d[56]), "=f"(d[57]), "=f"(d[58]), "=f"(d[59]), "=f"(d[60]), "=f"(d[61]), "=f"(d[62]), "=f"(d[63]),
        "=f"(d[64]), "=f"(d[65]), "=f"(d[66]), "=f"(d[67]), "=f"(d[68]), "=f"(d[69]), "=f"(d[70]), "=f"(d[71]),
        "=f"(d[72]), "=f"(d[73]), "=f"(d[74]), "=f"(d[75]), "=f"(d[76]), "=f"(d[77]), "=f"(d[78]), "=f"(d[79]),
        "=f"(d[80]), "=f"(d[81]), "=f"(d[82]), "=f"(d[83]), "=f"(d[84]), "=f"(d[85]), "=f"(d[86]), "=f"(d[87]),
        "=f"(d[88]), "=f"(d[89]), "=f"(d[90]), "=f"(d[91]), "=f"(d[92]), "=f"(d[93]), "=f"(d[94]), "=f"(d[95])
      : "l"(da), "l"(db));
}

__device__ __forceinline__ void wgmma_n192_rs(float (&d)[96], uint32_t a0, uint32_t a1, uint32_t a23, uint64_t db) {
  asm volatile(
      "wgmma.mma_async.sync.aligned.m64n192k16.f32.bf16.bf16 {"
      "%0, %1, %2, %3, %4, %5, %6, %7, %8, %9, %10, %11, %12, %13, %14, %15, "
      "%16, %17, %18, %19, %20, %21, %22, %23, %24, %25, %26, %27, %28, %29, %30, %31, "
      "%32, %33, %34, %35, %36, %37, %38, %39, %40, %41, %42, %43, %44, %45, %46, %47, "
      "%48, %49, %50, %51, %52, %53, %54, %55, %56, %57, %58, %59, %60, %61, %62, %63, "
      "%64, %65, %66, %67, %68, %69, %70, %71, %72, %73, %74, %75, %76, %77, %78, %79, "
      "%80, %81, %82, %83, %84, %85, %86, %87, %88, %89, %90, %91, %92, %93, %94, %95}, "
      "{%96, %97, %98, %98}, %99, 1, 1, 1, 1;\n"
      :
        "+f"(d[0]), "+f"(d[1]), "+f"(d[2]), "+f"(d[3]), "+f"(d[4]), "+f"(d[5]), "+f"(d[6]), "+f"(d[7]),
        "+f"(d[8]), "+f"(d[9]), "+f"(d[10]), "+f"(d[11]), "+f"(d[12]), "+f"(d[13]), "+f"(d[14]), "+f"(d[15]),
        "+f"(d[16]), "+f"(d[17]), "+f"(d[18]), "+f"(d[19]), "+f"(d[20]), "+f"(d[21]), "+f"(d[22]), "+f"(d[23]),
        "+f"(d[24]), "+f"(d[25]), "+f"(d[26]), "+f"(d[27]), "+f"(d[28]), "+f"(d[29]), "+f"(d[30]), "+f"(d[31]),
        "+f"(d[32]), "+f"(d[33]), "+f"(d[34]), "+f"(d[35]), "+f"(d[36]), "+f"(d[37]), "+f"(d[38]), "+f"(d[39]),
        "+f"(d[40]), "+f"(d[41]), "+f"(d[42]), "+f"(d[43]), "+f"(d[44]), "+f"(d[45]), "+f"(d[46]), "+f"(d[47]),
        "+f"(d[48]), "+f"(d[49]), "+f"(d[50]), "+f"(d[51]), "+f"(d[52]), "+f"(d[53]), "+f"(d[54]), "+f"(d[55]),
        "+f"(d[56]), "+f"(d[57]), "+f"(d[58]), "+f"(d[59]), "+f"(d[60]), "+f"(d[61]), "+f"(d[62]), "+f"(d[63]),
        "+f"(d[64]), "+f"(d[65]), "+f"(d[66]), "+f"(d[67]), "+f"(d[68]), "+f"(d[69]), "+f"(d[70]), "+f"(d[71]),
        "+f"(d[72]), "+f"(d[73]), "+f"(d[74]), "+f"(d[75]), "+f"(d[76]), "+f"(d[77]), "+f"(d[78]), "+f"(d[79]),
        "+f"(d[80]), "+f"(d[81]), "+f"(d[82]), "+f"(d[83]), "+f"(d[84]), "+f"(d[85]), "+f"(d[86]), "+f"(d[87]),
        "+f"(d[88]), "+f"(d[89]), "+f"(d[90]), "+f"(d[91]), "+f"(d[92]), "+f"(d[93]), "+f"(d[94]), "+f"(d[95])
      : "r"(a0), "r"(a1), "r"(a23), "l"(db));
}

__device__ __forceinline__ uint32_t pack_bf16(float lo, float hi) {
  uint32_t r;
  asm("cvt.rn.bf16x2.f32 %0, %1, %2;" : "=r"(r) : "f"(hi), "f"(lo));
  return r;
}
__device__ __forceinline__ float bf_lo(uint32_t v) { return __uint_as_float(v << 16); }
__device__ __forceinline__ float bf_hi(uint32_t v) { return __uint_as_float(v & 0xFFFF0000u); }
__device__ __forceinline__ float ex2(float x) { float r; asm("ex2.approx.ftz.f32 %0, %1;" : "=f"(r) : "f"(x)); return r; }
__device__ __forceinline__ float rcp(float x) { float r; asm("rcp.approx.ftz.f32 %0, %1;" : "=f"(r) : "f"(x)); return r; }
__device__ __forceinline__ uint32_t movm(uint32_t a) {
  uint32_t d;
  asm volatile("movmatrix.sync.aligned.m8n8.trans.b16 %0, %1;" : "=r"(d) : "r"(a));
  return d;
}
__device__ __forceinline__ void mma16816(float (&c)[4], uint32_t a0, uint32_t a1, uint32_t a2, uint32_t a3, uint32_t b0, uint32_t b1) {
  asm volatile("mma.sync.aligned.m16n8k16.row.col.f32.bf16.bf16.f32 {%0,%1,%2,%3}, {%4,%5,%6,%7}, {%8,%9}, {%0,%1,%2,%3};"
               : "+f"(c[0]), "+f"(c[1]), "+f"(c[2]), "+f"(c[3]) : "r"(a0), "r"(a1), "r"(a2), "r"(a3), "r"(b0), "r"(b1));
}
__device__ __forceinline__ void mma1688(float (&c)[4], uint32_t a0, uint32_t a1, uint32_t b0) {
  asm volatile("mma.sync.aligned.m16n8k8.row.col.f32.bf16.bf16.f32 {%0,%1,%2,%3}, {%4,%5}, {%6}, {%0,%1,%2,%3};"
               : "+f"(c[0]), "+f"(c[1]), "+f"(c[2]), "+f"(c[3]) : "r"(a0), "r"(a1), "r"(b0));
}
__device__ __forceinline__ void stsm4(uint32_t addr, uint32_t a, uint32_t b, uint32_t c, uint32_t d) {
  asm volatile("stmatrix.sync.aligned.m8n8.x4.shared.b16 [%0], {%1,%2,%3,%4};" ::"r"(addr), "r"(a), "r"(b), "r"(c), "r"(d) : "memory");
}
__device__ __forceinline__ void stsm4_t(uint32_t addr, uint32_t a, uint32_t b, uint32_t c, uint32_t d) {
  asm volatile("stmatrix.sync.aligned.m8n8.x4.trans.shared.b16 [%0], {%1,%2,%3,%4};" ::"r"(addr), "r"(a), "r"(b), "r"(c), "r"(d) : "memory");
}
__device__ __forceinline__ void ldsm4(uint32_t addr, uint32_t (&v)[4]) {
  asm volatile("ldmatrix.sync.aligned.m8n8.x4.shared.b16 {%0,%1,%2,%3}, [%4];"
               : "=r"(v[0]), "=r"(v[1]), "=r"(v[2]), "=r"(v[3]) : "r"(addr) : "memory");
}
__device__ __forceinline__ void sts128(uint32_t addr, uint4 v) {
  asm volatile("st.shared.v4.b32 [%0], {%1,%2,%3,%4};" ::"r"(addr), "r"(v.x), "r"(v.y), "r"(v.z), "r"(v.w) : "memory");
}
__device__ __forceinline__ uint4 lds128(uint32_t addr) {
  uint4 v;
  asm volatile("ld.shared.v4.b32 {%0,%1,%2,%3}, [%4];" : "=r"(v.x), "=r"(v.y), "=r"(v.z), "=r"(v.w) : "r"(addr) : "memory");
  return v;
}
__device__ __forceinline__ void sts64(uint32_t addr, uint32_t a, uint32_t b) {
  asm volatile("st.shared.v2.b32 [%0], {%1,%2};" ::"r"(addr), "r"(a), "r"(b) : "memory");
}
__device__ __forceinline__ void sts32(uint32_t addr, uint32_t a) { asm volatile("st.shared.b32 [%0], %1;" ::"r"(addr), "r"(a) : "memory"); }
__device__ __forceinline__ uint32_t lds32(uint32_t addr) {
  uint32_t v;
  asm volatile("ld.shared.b32 %0, [%1];" : "=r"(v) : "r"(addr) : "memory");
  return v;
}
__device__ __forceinline__ float2 lds64f_const(uint32_t addr) {
  float2 v;
  asm("ld.shared.v2.f32 {%0,%1}, [%2];" : "=f"(v.x), "=f"(v.y) : "r"(addr));
  return v;
}
template <int N, bool PAIR>
__device__ __forceinline__ void load_tagged(uint3 (&out)[N], const uint4* src, int stride, uint32_t tag, const uint4* last = nullptr) {
  uint32_t bad;
  int spins = 0;
#pragma unroll 1
  do {
    if (++spins > 2000000) __trap();
    bad = 0;
#pragma unroll
    for (int i = 0; i < N; i++) {
      const uint4 v = ld_b128(N == 5 && i == 4 ? last : src + i * stride);
      out[i] = make_uint3(v.x, v.y, v.z);
      bad |= (v.w ^ tag) | (PAIR ? v.z ^ tag : 0);
    }
    if (N == 4) bad = __any_sync(~0u, bad != 0);
    if (bad) __nanosleep(kBackoffNs);
  } while (bad);
}
__device__ __forceinline__ void sts64f(uint32_t addr, float2 v) { sts64(addr, __float_as_uint(v.x), __float_as_uint(v.y)); }
__device__ __forceinline__ float bf_rest(float v) { return v - __uint_as_float(__float_as_uint(v) & 0xFFFF0000u); }
__device__ __forceinline__ uint32_t bf_upper(float lo, float hi) { return __byte_perm(__float_as_uint(lo), __float_as_uint(hi), 0x7632); }
__device__ __forceinline__ float low_peak(uint4 v) {
  asm("max.xorsign.abs.bf16x2 %0, %0, %1;" : "+r"(v.x) : "r"(v.y));
  asm("max.xorsign.abs.bf16x2 %0, %0, %1;" : "+r"(v.z) : "r"(v.w));
  asm("max.xorsign.abs.bf16x2 %0, %0, %1;" : "+r"(v.x) : "r"(v.z));
  asm("max.xorsign.abs.bf16x2 %0, %0, %1;" : "+r"(v.x) : "r"(v.x << 16));
  return __uint_as_float(__reduce_min_sync(~0u, v.x & 0x7FFF0000u));
}
__device__ __forceinline__ float bias_at(float v) { return __uint_as_float((__float_as_uint(fminf(v, 1e37f)) & 0x7F800000u) | 0x00400000u); }
struct RowConst {
  float nmean, k0, k1, half;
};
__device__ __forceinline__ float gate_scale(float t, const RowConst& k) {
  float th;
  asm("tanh.approx.f32 %0, %1;" : "=f"(th) : "f"(t * fmaf(t * t, k.k1, k.k0)));
  return fmaf(th, k.half, k.half);
}

template <int N>
__device__ __forceinline__ void mma_k16(float (&acc)[2][96], uint32_t a, uint32_t b, int kk, int add = 1) {
#pragma unroll
  for (int m = 0; m < 2; m++) {
    const uint64_t da = desc(a) + (m * 512 + kk * 2), db = desc(b) + kk * 128;
    if (N == 128) wgmma_n128(acc[m], da, db); else wgmma_n192(acc[m], da, db, add);
  }
}

__device__ __forceinline__ void stage_quarter(const float* acc, uint32_t frag, uint32_t frag_x, int b, const uint4* add = nullptr) {
#pragma unroll
  for (int j = 0; j < 4; j++) {
    const float* v = acc + 8 * j;
    uint32_t h[4] = {pack_bf16(v[0], v[1]), pack_bf16(v[2], v[3]), pack_bf16(v[4], v[5]), pack_bf16(v[6], v[7])};
    if (add) {
      const uint32_t a[4] = {add[j].x, add[j].y, add[j].z, add[j].w};
#pragma unroll
      for (int e = 0; e < 4; e++) asm("add.rn.bf16x2 %0, %0, %1;" : "+r"(h[e]) : "r"(a[e]));
    }
    stsm4(frag + b * 8192 + ((frag_x ^ (j * 2)) << 4), h[0], h[1], h[2], h[3]);
  }
}

inline int g1_block(int j, int c) { return j < 16 ? j : ((j + 12) & 15) ^ (c == 5 && j >= 28 ? 2 : 0); }
inline int g2_block(int j, int c) { return j < 8 ? j : j == 8 ? 8 + c : j - (j - 9 < c); }
inline int g3_tile(int j) { return j < 4 ? j >> 1 : j < 18 ? 0 : j >> 4; }
inline int g3_block(int j, int c) {
  const int i = j < 32 ? (j < 16 ? 0xDCBA976543218080ull : 0x7654321BA9FEDCFEull) >> 4 * (j & 15) : j + (~j >> 2 & 4), o = i & 7;
  return 2 * (j < 32 && (o == c || o == 0) ? c - o : o) + (i >> 3 & 1);
}
__device__ __forceinline__ bool g3_is_up(int tile, int a) { return a == 1 || (a == 2 && tile >= 2); }
__device__ __forceinline__ int g3_atom(int tile, int a, int c) { return c * 7 + (tile & 1) * 3 + (a == 2 ? 1 : tile == 4 ? 6 : tile & 2); }
inline int g4_block(int i) {
  const int n = i * 43 >> 7, j = i - 3 * n, m = j ? n : n + (16 - kFirstShared / 3);
  return i < 48 ? 7 * (m & 7) + 3 * (m >> 3 & 1) + j : 7 * i - 330;
}

constexpr int kInPlace = 16, kShared = 64, kNextWave = 128;

template <int N, int TAIL>
__device__ __forceinline__ void mainloop(Scratch* sc, float (&acc)[2][96], uint32_t sb, int ph, int j0, int nsteps, int pause_at, bool last,
                                         bool hand_over, bool local, int wg, int own = -1, const CUtensorMap* out = nullptr, int out_col = 0,
                                         int out_row = 0, int warp = 0, __nv_bfloat16* outp = nullptr) {
  constexpr int NSLOT = N == 128 ? 5 : 4, SLOT = N == 128 ? 32768 : 40960;
  const int lane = fresh_tid() & 31;
  const uint32_t full = sb + kBars + 8 * ring_base(ph);
  const uint32_t empty = map_cta(full + 8 * (NSLOT + (ph == 3)), lane & 1);
  const uint32_t ring = desc_lo(sb + kRing, 16);
  int bi = j0 % NSLOT, par = (j0 / NSLOT) & 1;
  const int release_end = lane < (N == 192 && !hand_over ? 4 : 2) ? (last ? nsteps - 1 - NSLOT : nsteps) : 0;
  uint32_t rel = empty;
  const uint32_t special = ph == 0 && wg == 0 ? 3 : pause_at < 0 ? 1 : 1 | 2 << pause_at;
  int i = 0;
#pragma unroll 1
  for (;;) {
    const int end = TAIL <= 0 ? nsteps : !own ? nsteps - TAIL - 1 : i ? i + 2 : kFirstShared;
#pragma unroll 1
    do {
      uint32_t a = ring + bi * (SLOT >> 4), b = a + kToB;
      if (TAIL > 0 ? i == 0 : special >> i & 1) {
        if (i == 0) nb_sync(kNbOrder + wg, ph == 0 && wg == 0 ? 160 : 256);
        else if (ph == 0 && wg == 0) cluster_wait();
        else if (ph < 2) nb_sync(kNbWin + 1, 256);
      }
      if (N == 192 && local) {
        a = ring + ((kStage + i * 16384) >> 4);
        b = ring + bi * (32768 >> 4) + desc_lo(32768, 8192) - desc_lo(0, 16);
      }
      if (ph == 0 && i >> 1 == own) a = ring + ((kOwn + (i & 1) * 16384) >> 4);
      if (ph == 1 && i == 8) a = ring + ((kStage + 32768) >> 4);
      mbar_wait(full + 8 * bi, par);
      if (N == 192 && local) mbar_wait(sb + kBars + 8 * (kHalfBar + i), 0);
      const bool release = (uint32_t)(i - 1) < (uint32_t)release_end;
      wg_fence();
      mma_k16<N>(acc, a, b, 0, ph == 0 ? i | wg : 1);
      mma_k16<N>(acc, a, b, 1);
      wg_commit();
      wg_wait<1>();
      mbar_arrive_cluster_if(rel, release);
      wg_fence();
      mma_k16<N>(acc, a, b, 2);
      mma_k16<N>(acc, a, b, 3);
      wg_commit();
      rel = empty + 8 * bi;
      if (++bi == NSLOT + (TAIL > 0 && i >= kWide - 16)) { bi = 0; par ^= 1; }
      if (ph < 2 && i == pause_at) nb_arrive(kNbWin, 256);
    } while (++i < end);
    if (TAIL <= 0 || own-- == 0) break;
    const uint32_t a = ring + bi * (SLOT >> 4);
    mbar_wait(full + 8 * bi, par);
    wg_fence();
#pragma unroll
    for (int k = 0; k < 4; k++) wgmma_n128(acc[1], desc(a) + (512 + k * 2), desc(a + kToB) + k * 128);
    wg_commit();
    wg_wait<1>();
    mbar_arrive_cluster_if(rel, lane < 2);
    rel = empty + 8 * bi;
    if (++bi == NSLOT + 1) { bi = 0; par ^= 1; }
    i++;
  }
  if (TAIL < 0) return;
  if (TAIL > 0) {
    uint32_t at[TAIL + 2];
    bi = par = 0;
    const int t = fresh_tid() & 127;
    uint32_t frag = sb + kStage + ((t >> 5) * 16 + (t & 15)) * 128, frag_x = ((t >> 4) & 1) ^ (t & 7);
    const uint32_t back = sb + kStage + (t >> 5) * 2048 + ((t >> 3) & 3) * 128, back_x = ((t ^ (t >> 3 & 3)) & 7) << 4;
    outp = plus(outp, (2 * (out_row + (t >> 5) * 16 + ((t >> 3) & 3)) + (blockIdx.x & 1)) * kD + out_col + (t & 7) * 8);
    auto rows = [&](int m, int i0, int i1) {
      wg_fence();
#pragma unroll
      for (int i = 4 * i0; i < 4 * i1; i++)
        wgmma_n128(acc[m], desc_kept(ring, sb) + (at[i >> 2] + m * 512 + (i & 3) * 2), desc_kept(ring, sb) + (at[i >> 2] + kToB + (i & 3) * 128));
      wg_commit();
    };
    uint4 part[8];
#pragma unroll
    for (int i = 0; i <= TAIL; i++) {
      at[i] = bi * (SLOT >> 4);
      mbar_wait(full + 8 * bi, par);
      if (++bi == NSLOT) { bi = 0; par ^= 1; }
      rows(0, i, i + 1);
      if (i == kPartAt) nb_sync(kNbPart, 256);
      if (i == kPartAt || i == kPartAt + 1) {
#pragma unroll
        for (int k = 4 * (i - kPartAt); k < 4 * (i - kPartAt + 1); k++) part[k] = lds128(sb + kStage + 32768 + (t >> 5) * 4096 + (t & 31) * 16 + k * 512);
      }
    }
    rows(1, 0, 2);
#pragma unroll
    for (int b = 0; b < 4; b++) {
      if (b == 0) wg_wait<1>();
      if (b == 1) rows(1, 3, 4);
      if (b == 2) wg_wait<0>();
      if (!(b & 1)) {
#pragma unroll
        for (int i = 0; i < 64; i++) asm volatile("" : "+f"(acc[b >> 1][i])::"memory");
        if (t == 0) TSS(b);
      }
      stage_quarter(&acc[b >> 1][32 * (b & 1)], frag, frag_x, b, b < 2 ? &part[4 * b] : nullptr);
      if (b == 3) {
        __syncwarp();
        uint4 v[4];
#pragma unroll
        for (int i = 0; i < 4; i++) v[i] = lds128(back + b * 8192 + i * 512 + ((i & 1) ? back_x ^ 64 : back_x));
#pragma unroll
        for (int i = 0; i < 4; i++) __stcs((uint4*)(outp + ((b >> 1) * 128 + i * 8) * kD + (b & 1) * 64), v[i]);
        if (t == 0) TSS(4 + b);
        continue;
      }
      if (b < 2) rows(1, 2 + 2 * b, 3 + 2 * b);
      fence_async_smem();
      __syncwarp();
      if (elect_one()) tma_store3d(out, sb + kStage + b * 8192 + warp * 2048, out_col + (b & 1) * 64, out_row + (b >> 1) * 64 + warp * 16, blockIdx.x & 1);
      __syncwarp();
      if (t == 0) TSS(4 + b);
    }
    if (elect_one()) {
      bulk_commit();
      bulk_wait_read();
    }
    if (t == 0) TSS(1);
    return;
  }
  if (hand_over) nb_arrive(kNbOrder + (wg ^ 1), 256);
  if (N == 192 && !local) {
    mbar_wait(sb + kBars + 8 * (kAuxBar + wg), j0 < 32);
    if (j0 < 32) mbar_wait(sb + kBars + 8 * kStatBar, 1);
    mbar_wait(sb + kBars + 8 * (kStgBar + wg), ((j0 >> 5) ^ wg ^ 1) & 1);
  }
  wg_wait<0>();
  mbar_arrive_cluster_if(rel, release_end == nsteps);
#pragma unroll
  for (int i = 0; i < N / 2; i++) asm volatile("" : "+f"(acc[0][i]), "+f"(acc[1][i])::"memory");
}

template <int PH>
struct Ring {
  static constexpr int NSLOT = 4 + (PH & 1), SLOT = PH & 1 ? 32768 : 40960;
  uint32_t full, dst0;
  int j = PH == 0 ? 4 : 0, bi = 0, par = PH == 0 ? 0 : 1;
  __device__ __forceinline__ Ring(uint32_t sb, uint32_t ofs) : full(sb + kBars + 8 * (PH * 9 - (PH & 1))), dst0(sb + kRing + ofs) {}
  __device__ __forceinline__ uint32_t bar() const { return full + 8 * bi; }
  __device__ __forceinline__ uint32_t dst() const { return dst0 + bi * SLOT; }
  __device__ __forceinline__ void acquire_first() const {
    const bool first = j < NSLOT;
    mbar_wait(full + (first ? 8 * min(j, 3) - 32 : 8 * (NSLOT + (PH == 3) + bi)), PH == 2 && first ? 0 : par);
  }
  __device__ __forceinline__ void acquire() const { mbar_wait(full + 8 * (NSLOT + (PH == 3) + bi), par); }
  __device__ __forceinline__ void next() {
    j++;
    if (++bi == NSLOT + (PH == 3 && j > kWide)) { bi = 0; par ^= 1; }
  }
};

__device__ __forceinline__ void check_blocks(const Params& p, Scratch* sc, uint32_t sb, int r, int c, bool g3, uint32_t& par) {
  const int lane = fresh_tid() & 31, nslot = g3 ? 4 : 5, slot_bytes = g3 ? 40960 : 32768;
  const uint32_t mine = (lane >> 2) * 132 + (lane & 3) * 32, ring_end = sb + kRing + kStage + mine;
  const uint32_t to_full = 8 * (kLandBar - (g3 ? ring_base(2) : ring_base(1)));
  uint32_t src = sb + kRing + mine + (g3 ? 0 : 4 * 32768);
  int bi = g3 ? 0 : 4, spins = 0;
#pragma unroll 1
  for (int i = g3 ? 2 : 9; i < 16;) {
    const uint32_t land = sb + kBars + 8 * (kLandBar + bi);
    mbar_wait(land, (par >> bi) & 1);
    uint32_t v[16];
#pragma unroll
    for (int k = 0; k < 16; k++) v[k] = lds32(src + k * 1024);
#pragma unroll
    for (int k = 0; k < 5; k++) v[k] = max(max(v[3 * k + 1], v[3 * k + 2]), k ? v[3 * k] : max(v[0], v[15]));
    const bool again = __any_sync(~0u, max(max(max(v[0], v[1]), v[2]), max(v[3], v[4])) == kPoison);
    asm volatile("{\n.reg .pred p;\nsetp.eq.u32 p, %1, 0;\n@p mbarrier.arrive.shared::cta.b64 _, [%0];\n}\n"
                 ::"r"(land - to_full), "r"(lane + again) : "memory");
    par ^= 1u << bi;
    if (again) {
      if (++spins > 100000) __trap();
      if (elect_one()) {
        mbar_expect_tx(land, 16384);
        tma2d(src - mine, g3 ? &p.h : &p.o, ((g3 ? p.g3[c][i + 2] : p.g2[c][i]) & 15) * 64, r * 128, land);
      }
      nb_sync(kNbSelf + 1, 32);
      continue;
    }
    if (lane == 0 && (i == 2 || i == 3 || (!g3 && (i == 9 || i == 12)))) TS(i < 4 ? 88 + 2 * i : i == 9 ? 120 : 122);
    i++;
    if (++bi == nslot) bi = 0;
    src += slot_bytes;
    if (src == ring_end) src -= kStage;
  }
}

__device__ __forceinline__ void colsum_cta(const Params& p, Scratch* sc, uint32_t sb, int warp, int bid) {
  constexpr int kSlots = 4, kSlot = 49152;
  constexpr int kRows = kMost * 16384, kIn = (kCs - kRows) / 8192;
  const int lane = threadIdx.x & 31, c0 = (bid - 128) * 2;
  const uint32_t full = sb + kBars, empty = full + 8 * kSlots;
  const uint32_t event = full + 64, rfull = full + 128, rempty = full + 256;
  if (threadIdx.x == 0) {
#pragma unroll 1
    for (int i = 0; i < 48; i++) mbar_init(full + 8 * i, i & (i < 16 ? 4 : 32) ? 8 : 1);
    asm volatile("fence.mbarrier_init.release.cluster;" ::: "memory");
  }
  __syncthreads();
  const uint32_t ep = ld_epoch(sc);
  if (warp == 8) {
    if (elect_one()) {
#pragma unroll 1
      for (int n = 0; n < 112 + kSlots; n++) {
        const int u = n >> 4, c = c0 + ((n >> 3) & 1), k0 = (n & 7) * 128, slot = n & (kSlots - 1);
        if (n == kQuietAt) flag_wait(sc->flags + kFlPace, ep);
        const uint32_t bar = full + 8 * slot;
        mbar_wait(empty + 8 * slot, ((n / kSlots) & 1) ^ 1);
        if (n == 108) mbar_arrive(event);
        if (u == 7) continue;
        mbar_expect_tx(bar, u == 6 ? 32768 : 49152);
#pragma unroll
        for (int a = 0; a < 3; a++) {
          if (a == 2 && u == 6) break;
          const CUtensorMap* m = u < 2 ? &p.wqkv : g3_is_up(u - 2, a) ? &p.wu : &p.wg;
          const int col = (u < 2 ? a * 16 + u * 8 + c : g3_atom(u - 2, a, c)) * 64;
          tma2d(sb + slot * kSlot + a * 8192, m, col, k0, bar);
          tma2d(sb + slot * kSlot + a * 8192 + 24576, m, col, k0 + 64, bar);
        }
      }
      mbar_wait(event + 8, 0);
      asm volatile("fence.proxy.async.global;" ::: "memory");
      int slot = 0, par = 1, w = 0;
#pragma unroll 1
      for (int job = 0; job < 32; job++) {
        const int k = lds32(sb + kPlan + (job >> 4) * 4) >> (job & 14) * 2 & 15;
        if (job == 16) {
          mbar_wait(rempty + 8 * (slot ? slot - 1 : kIn - 1), par ^ (slot != 0));
          w = 0;
        }
#pragma unroll 1
        for (int i = 0; i < k; i++) {
          const uint32_t bar = rfull + 8 * slot;
          mbar_wait(bar + 128, par);
          mbar_expect_tx(bar, w < kMost ? 24576 : 8192);
          tma2d(sb + kRows + slot * 8192, &p.hhst, i * (7 * 64), (job & 15) * 128, bar);
          if (w < kMost) {
#pragma unroll
            for (int a = 0; a < 2; a++)
              tma2d(sb + w * 16384 + a * 8192, &p.wd, ((c0 + (job >> 4)) * 2 + a) * 64, w * (7 * 64), bar);
            w++;
          }
          if (++slot == kIn) { slot = 0; par ^= 1; }
        }
      }
    }
  } else if (warp < 8) {
    uint32_t src[3];
#pragma unroll
    for (int j = 0; j < 3; j++) src[j] = sb + ((warp * 3 + j) >> 3) * 8192 + lane * 128 + ((((warp * 3 + j) & 7) ^ (lane & 7)) << 4);
    const uint32_t ones = 0x3F803F80u;
#pragma unroll 1
    for (int s = 0; s < 112; s++) {
      float a[3][2][4] = {};
#pragma unroll 1
      for (;; s++) {
        const int slot = s & (kSlots - 1);
        mbar_wait(full + 8 * slot, (s / kSlots) & 1);
        uint32_t b[3][4][4];
#pragma unroll
        for (int j = 0; j < 3; j++)
#pragma unroll
          for (int k = 0; k < 4; k++)
            asm volatile("ldmatrix.sync.aligned.m8n8.x4.trans.shared.b16 {%0,%1,%2,%3}, [%4];"
                         : "=r"(b[j][k][0]), "=r"(b[j][k][1]), "=r"(b[j][k][2]), "=r"(b[j][k][3])
                         : "r"(src[j] + slot * kSlot + (k >> 1) * 24576 + (k & 1) * 4096) : "memory");
        __syncwarp();
        if (lane == 0) mbar_arrive(empty + 8 * slot);
#pragma unroll
        for (int k = 0; k < 4; k++)
#pragma unroll
          for (int j = 0; j < 3; j++) {
            mma16816(a[j][0], ones, ones, ones, ones, b[j][k][0], b[j][k][1]);
            mma16816(a[j][1], ones, ones, ones, ones, b[j][k][2], b[j][k][3]);
          }
        if ((s & 7) == 7) break;
      }
      {
        if (lane < 12) {
          const int j = lane >> 2;
          const float x = j == 0 ? a[0][0][0] + a[0][1][0] : j == 1 ? a[1][0][0] + a[1][1][0] : a[2][0][0] + a[2][1][0];
          const float y = j == 0 ? a[0][0][1] + a[0][1][1] : j == 1 ? a[1][0][1] + a[1][1][1] : a[2][0][1] + a[2][1][1];
          const float x1 = bf_rest(x), y1 = bf_rest(y);
          const bool split = s < 32;
          st_b128(SC_AT(cs, ((s >> 4) * 8 + c0 + ((s >> 3) & 1)) * 96 + warp * 12 + lane), split ? bf_upper(x, y) : __float_as_uint(x),
                  split ? bf_upper(x1, y1) : __float_as_uint(y), bf_upper(bf_rest(x1), bf_rest(y1)), ep);
        }
        if (threadIdx.x == 0 && (s & 8)) TSK(s >> 4);
      }
    }
    const int wg = warp >> 2;
    mbar_wait(event + 8, 0);
#pragma unroll 1
    for (int job = wg, first = 0; job < 32; job += 2) {
      const int k = __shfl_sync(~0u, lds32(sb + kPlan + (job >> 4) * 4), 0) >> (job & 14) * 2 & 15;
      if (k == 0) continue;
      float acc[96];
#pragma unroll
      for (int i = 0; i < 64; i++) asm volatile("" : "=f"(acc[i]));
      static_assert(kIn == 12, "");
      int slot = first + wg * k, par = slot * 171 >> 11, i = 0;
      slot -= par * kIn;
      first += 2 * k;
      uint32_t done = 0;
      if (job) nb_sync(kNbOrder + wg, 256);
#pragma unroll 1
      do {
        mbar_wait(rfull + 8 * slot, par & 1);
        wg_fence();
#pragma unroll
        for (int kk = 0; kk < 4; kk++)
          wgmma_n128(acc, desc(desc_lo(sb + kRows, 16) + slot * 512) + kk * 2, desc(desc_lo(sb, 8192) + i * 1024) + kk * 128, kk | i);
        wg_commit();
        wg_wait<1>();
        if (lane < 2 && i) mbar_arrive(done);
        done = rempty + 8 * slot;
        if (++slot == kIn) { slot = 0; par++; }
      } while (++i < k);
      nb_arrive(kNbOrder + (wg ^ 1), 256);
      uint4* dst = SC_AT(part, ((job & 15) * 8 + c0 + (job >> 4)) * 1024 + (warp & 3) * 256 + lane);
      wg_wait<0>();
#pragma unroll
      for (int i = 0; i < 64; i++) asm volatile("" : "+f"(acc[i])::"memory");
      if (lane < 2) mbar_arrive(done);
#pragma unroll
      for (int i = 0; i < 8; i++) {
        const float* v = &acc[8 * i];
        asm volatile("st.relaxed.gpu.global.v4.b32 [%0], {%1, %2, %3, %4};"
                     ::"l"(dst + i * 32),
                     "r"(pack_bf16(v[0], v[1])), "r"(pack_bf16(v[2], v[3])), "r"(pack_bf16(v[4], v[5])), "r"(pack_bf16(v[6], v[7])) : "memory");
      }
    }
    if (threadIdx.x == 128) TSK(7);
  } else if (warp == 10) {
    mbar_wait(event, 0);
    flag_wait(sc->flags + kFlHH + (lane & 15) * kFlRow, ep * 8);
    int late = await_word(sc->finish + (uint32_t)((lane & 15) * 8 + c0 + (lane >> 4)), ep);
    __syncwarp();
    late -= __shfl_sync(~0u, late, 0);
    late = max(late, __shfl_xor_sync(~0u, late, 1));
    late = max(min(late - (__reduce_add_sync(~0u, late) >> 5) + kShare * kStepNs, 4096), -4096);
    int k;
#pragma unroll 1
    do {
      k = min(max((late * (8192 / kStepNs) >> 13) + 1, (lane & 14) == 0), kMost);
      late -= kStepNs / 4;
    } while (__reduce_add_sync(~0u, k ? max(2 * k, k + 4) : 0) > kBudget);
    k <<= (lane & 14) * 2;
#pragma unroll
    for (int o = 2; o < 16; o <<= 1) k |= __shfl_xor_sync(~0u, k, o);
    asm volatile("fence.acquire.gpu;" ::: "memory");
    send_word(sc->plan + (uint32_t)(c0 + (lane >> 4)), k, ep);
    sts32(sb + kPlan + (lane >> 4) * 4, k);
    __syncwarp();
    if (lane == 0) mbar_arrive(event + 8);
  }
}

#define PROF_BEGIN
template <bool BY_SM>
__global__ void __cluster_dims__(2, 1, 1) __launch_bounds__(kThreads, 1) fused_block_kernel(Scratch* sc, const __nv_bfloat16* xp, const __nv_bfloat16* wqkvp, __nv_bfloat16* outp,
                                                                   const __grid_constant__ Params p) {
  extern __shared__ __align__(1024) uint8_t smem_raw[];
  if (threadIdx.x == 256) {
    prefetch_map(&p.x);
    prefetch_map(&p.wqkv);
  }
  if (threadIdx.x < 56) {
    const int l = threadIdx.x & 31, b = blockIdx.x & 127;
    if (threadIdx.x < 32) prefetch_l2(xp + (b * 16 + (l & 15)) * kD + (l >> 4) * 64);
    else prefetch_l2(wqkvp + b * (3 * kD) + (l >> 3) * kD + (l & 7) * 64);
  }
  const uint32_t sb = smem_u32(smem_raw);
  const int bid = role_id<BY_SM>();
  const int r = bid >> 3, c = bid & 7, rank = blockIdx.x & 1;
  auto first_fill = [&](int j) {
    const uint32_t fb = sb + kBars + 8 * j, dst = sb + kRing + j * 40960;
    mbar_expect_tx(fb, 40960);
    tma3d(j >> 1 == c ? sb + kOwn + (j & 1) * 16384 : dst, &p.x, j * 64, (r >> 1) * 128, rank, fb);
#pragma unroll
    for (int a = 0; a < 3; a++) tma2d(dst + 16384 + a * 8192, &p.wqkv, a * kD + c * 64, j * 64, fb);
    mbar_arrive(fb);
  };
  const int tid = threadIdx.x, warp = __shfl_sync(~0u, tid >> 5, 0), wg = warp >> 2;
  if (bid >= 128) {
    if (tid == 0) PROF_BEGIN;
    colsum_cta(p, sc, sb, warp, bid);
    return;
  }
  if (wg == 2) {
    if (warp == 8 && elect_one()) {
      mbar_init(sb + kBars, 2);
      asm volatile("fence.mbarrier_init.release.cluster;" ::: "memory");
      first_fill(0);
#pragma unroll
      for (int j = 1; j < 4; j++) mbar_init(sb + kBars + 8 * j, 2);
      asm volatile("fence.mbarrier_init.release.cluster;" ::: "memory");
      TSS(0);
    }
    __syncwarp();
    if (warp == 8) nb_arrive(kNbOrder, 160);
    asm volatile("setmaxnreg.dec.sync.aligned.u32 40;");
    if (warp == 8) {
      cluster_arrive();
      if (elect_one()) {
#pragma unroll 1
        for (int j = 1; j < 4; j++) first_fill(j);
        TSS(1);
      }
      __syncwarp();
    } else {
      if (elect_one()) {
        uint64_t shifts = warp == 9 ? bar_shifts(4) : warp == 10 ? bar_shifts(22) : bar_shifts(40);
#pragma unroll 1
        for (int i = 0; i < 18; i++, shifts >>= 3) mbar_init(sb + kBars + 8 * (18 * warp - 158 + i), 1u << (shifts & 7));
        if (warp == 10) asm volatile("mbarrier.arrive.shared::cta.b64 _, [%0], 2;" ::"r"(sb + kBars + 8 * 31) : "memory");
        sts32(sb + kZero, 0);
        sts32(sb + kScale + 4, 0);
        sts32(sb + kRole, bid);
        sts128(sb + kOnes, make_uint4(0x3F803F80u, 0, 0, 0x3F803F80u));
        asm volatile("fence.mbarrier_init.release.cluster;" ::: "memory");
      }
      __syncwarp();
      cluster_arrive();
    }
    cluster_wait();
    const uint32_t ep = ld_epoch(sc);
    if (tid == 320) sts32(sb + kEpoch, ep);
    if (tid == 320) PROF_BEGIN;
    const int pw = warp & 3;
    if (pw == 0) {
      if (elect_one()) {
        const int row = r * 128;
        const uint32_t land = sb + kBars + 8 * kLandBar;
#pragma unroll 1
        for (Ring<0> q(sb, 0); q.j < 32; q.next()) {
          q.acquire();
          const int kb = p.g1[c][q.j];
          if (kb & kInPlace) { mbar_arrive(q.bar()); continue; }
          mbar_expect_tx(q.bar(), 16384);
          tma3d(kb >> 1 == c ? sb + kOwn + (kb & 1) * 16384 : q.dst(), &p.x, kb * 64, (r >> 1) * 128, rank, q.bar());
        }
        prefetch_map(&p.o);
        prefetch_map(&p.o16);
        flag_wait(sc->flags + kFlO + r * kFlRow, ep * 8);
        fence_async();
        TS(40);
#pragma unroll 1
        for (Ring<1> q(sb, 0); q.j < 16; q.next()) {
          q.acquire_first();
          if (q.j == 8) {
            prefetch_map(&p.wg);
            prefetch_map(&p.wu);
            prefetch_map(&p.h);
            prefetch_map(&p.h16);
            mbar_wait(sb + kBars + 8 * kSentBar, 0);
            mbar_arrive(q.bar());
            mbar_arrive(sb + kBars + 8 * (kStgBar + 1));
            if (bid == 0) __stcg(sc->flags + kFlPace, ep);
            __nanosleep(kGateONs);
            continue;
          }
          const uint32_t bar = q.j < 8 ? q.bar() : land + 8 * q.bi;
          if (q.j == 9) TS(41);
          mbar_expect_tx(bar, 16384);
          tma2d(q.dst(), &p.o, p.g2[c][q.j] * 64, row, bar);
        }
#pragma unroll 1
        for (Ring<2> q(sb, 0); q.j < 64; q.next()) {
          q.acquire_first();
          const int kb = p.g3[c][q.j];
          if (kb & kInPlace) { mbar_arrive(q.bar()); continue; }
          if (q.j == 4) { __nanosleep(kGateHNs); TS(42); }
          const uint32_t bar = q.j < 18 ? land + 8 * q.bi : q.bar();
          mbar_expect_tx(bar, 16384);
          tma2d(q.dst(), &p.h, (kb & 15) * 64, row, bar);
        }
        prefetch_map(&p.hh);
        prefetch_map(&p.out);
        Ring<3> q(sb, 0);
#pragma unroll 1
        for (; q.j < 16; q.next()) {
          q.acquire_first();
          if (q.j == 0) { mbar_arrive(q.bar()); continue; }
          mbar_expect_tx(q.bar(), 16384);
          tma2d(q.dst(), &p.h, ((q.j + 9) & 15) * 64, row, q.bar());
        }
        uint32_t wave = sb + kBars + 8 * kWaveBar;
        int share = 0;
#pragma unroll 1
        for (; q.j < 72; q.next()) {
          const int kb = p.g4[q.j - 16];
          if (kb & kNextWave) {
            mbar_wait(wave, 0);
            fence_async();
            wave += 8;
            if (q.j == 16) share = lds32(sb + kPlan);
          }
          q.acquire();
          const bool half = (kb & kShared) && --share >= 0;
          mbar_expect_tx(q.bar(), half ? 8192 : 16384);
          tma2d(q.dst() + half * 8192, half ? &p.hhst : &p.hh, (kb & 63) * 64, row + half * 64, q.bar());
        }
      }
    } else if (pw == 1) {
      if (elect_one()) {
        const int rp = r >> 1;
#pragma unroll 1
        for (Ring<0> q(sb, 16384); q.j < 32; q.next()) {
          q.acquire();
          mbar_expect_tx(q.bar(), 24576);
          const int col = ((q.j >> 4) * 8 + c) * 64, k0 = (p.g1[c][q.j] & 15) * 64;
          tma2d_mc(q.dst() + rank * 8192, &p.wqkv, rank * kD + col, k0, q.bar());
          if ((q.j & 1) == rank) tma2d_mc(q.dst() + 16384, &p.wqkv, 2 * kD + col, k0, q.bar());
          if (q.j == max(r, 4))
            for (int a = 0; a < 3; a++) tma_prefetch2d(&p.wqkv, a * kD + (8 + c) * 64, ((r + 12) & 15) * 64);
          if (q.j >> 1 == rp + 8) tma_prefetch2d(&p.wo, (c * 2 + rank) * 64, (q.j & 15) * 64);
        }
        if (r < 6) tma_prefetch2d(rp == 1 ? &p.wu : &p.wg, (c * 7 + 3 + (rp >> 1)) * 64, (c * 2 + rank) * 64);
#pragma unroll 1
        for (Ring<1> q(sb, 16384 + rank * 8192); q.j < 16; q.next()) {
          q.acquire_first();
          mbar_expect_tx(q.bar(), 16384);
          tma2d_mc(q.dst(), &p.wo, (c * 2 + rank) * 64, p.g2[c][q.j] * 64, q.bar());
        }
        const CUtensorMap* mine = rank ? &p.wu : &p.wg;
#pragma unroll 1
        for (Ring<2> q(sb, 16384); q.j < 64; q.next()) {
          const int kb = p.g3[c][q.j], tile = kb >> 5, f0 = c * 7 + (tile & 1) * 3, fp = f0 + (tile & 2);
          const int k0 = (kb & 15) * 64;
          q.acquire_first();
          mbar_expect_tx(q.bar(), 24576);
          const uint32_t dst = q.j < 4 ? sb + kRing + (q.j + 1) * 32768 : q.dst();
          tma2d_mc(dst + rank * 8192, mine, fp * 64, k0, q.bar());
          if ((q.j & 1) == rank) tma2d_mc(dst + 16384, tile & 2 ? &p.wu : &p.wg, (f0 + 1) * 64, k0, q.bar());
          const int d = q.j - kPfStep - (c & 1) * 5 - (r >> 2);
          if (d == 0 || d == 11 || d == 22) {
            const int f = c * 7 + (d == 0 ? 2 : d == 11 ? 5 : 6);
            tma_prefetch2d(&p.wg, f * 64, r * 64);
            tma_prefetch2d(&p.wu, f * 64, r * 64);
            if (d != 22) tma_prefetch2d(&p.wu, (f - 1) * 64, r * 64);
            else tma_prefetch2d(&p.wd, (c * 2 + rank) * 64, rp * (7 * 64));
          }
          if (q.j >> 1 == rp + 24) tma_prefetch2d(&p.wd, (c * 2 + rank) * 64, (p.g4[q.j & 15] & 63) * 64);
        }
        Ring<3> q(sb, 16384 + rank * 8192);
#pragma unroll 1
        for (; q.j < 16; q.next()) {
          q.acquire_first();
          mbar_expect_tx(q.bar(), 16384);
          tma2d_mc(q.dst(), mine, (c * 7 + 6) * 64, ((q.j + 9) & 15) * 64, q.bar());
          if (q.j >> 1 == rp) tma_prefetch2d(&p.wd, (c * 2 + rank) * 64, (p.g4[q.j + 16] & 63) * 64);
        }
#pragma unroll 1
        for (; q.j < 72; q.next()) {
          q.acquire();
          mbar_expect_tx(q.bar(), 16384);
          tma2d_mc(q.dst(), &p.wd, (c * 2 + rank) * 64, (p.g4[q.j - 16] & 63) * 64, q.bar());
          if ((q.j & 15) >> 1 == rp && q.j < 40) tma_prefetch2d(&p.wd, (c * 2 + rank) * 64, (p.g4[q.j + 16] & 63) * 64);
        }
      }
    } else {
      const int cw = pw - 2;
      const uint32_t stg = sb + kStage + cw * 32768, rb = sb + kBars + 8 * kResBar;
      uint32_t land_par = 0;
      sts64(sb + kPlan, global_ns(), clock());
      if (cw == 0) {
#pragma unroll 1
        for (int i = 0; i < 16; i++) sts128(sb + kFill + i * 512 + (tid & 31) * 16, make_uint4(kPoison, kPoison, kPoison, kPoison));
        __nanosleep(kSampleNs);
        const uint32_t l15 = tid & 15;
        const uint4 os = __ldg(plus(p.wop, (tid & 31) * 128 + c * 16 + l15));
        const uint4 gs = __ldg(plus(tid & 16 ? p.wup : p.wgp, l15 * 451 + c * 56));
        const uint4 ws = __ldg(plus((const uint4*)wqkvp, (tid & 7) * 385 + (tid & 24) * 16 + (8 + c) * 8));
        sts64(sb + kScale, __float_as_uint(low_peak(os) * kBias3 * low_peak(gs)), __float_as_uint(low_peak(ws) * kBias1) | 1);
        if (tid == 320) TS(93);
      }
#pragma unroll 1
      for (int ev = -1; ev < 4; ev++) {
        const bool quads = cw == 0 && ev == 1;
        if (ev >= cw && !quads) nb_sync(kNbPub + cw, 160);
        if (ev >= cw && elect_one()) {
          if (quads) {
            mbar_wait(sb + kBars + 8 * (kHalfBar + 1), 0);
#pragma unroll 1
            for (int i = 0; i < 2; i++) {
              __nanosleep(i ? kPaceNs : kHoldNs);
              tma_store2d(&p.hst, stg + 16384 + i * 8192, c * 128 + 64, r * 128 + i * 64);
              TS(100 + i);
            }
            bulk_commit();
            bulk_wait_read();
            mbar_arrive(sb + kBars + 8 * kStgBar);
          } else {
            if (ev == 1) {
              const uint32_t now = global_ns();
              const float left = (float)(now - lds32(sb + kPlan)) * (float)kRemain * rcp((float)((uint32_t)clock() - lds32(sb + kPlan + 4)));
              send_word(sc->finish + (uint32_t)bid, now + (uint32_t)left, ep);
            }
            const int it = ev - 2 + cw, f0 = c * 7 + (1 - cw) * 3, fp = it == 2 ? c * 7 + 6 : f0 + 2 * it;
            const bool is_o = ev == 0;
            const CUtensorMap* m = is_o ? &p.ost : &p.hhst;
            const int b0 = is_o ? c : f0 + 1, b1 = fp;
#pragma unroll 1
            for (int i = is_o || it == 1 ? 0 : 2; i < (is_o ? 2 : 4); i++) {
              tma_store2d(m, stg + i * 8192, (i < 2 ? b0 : b1) * 64, r * 128 + (i & 1) * 64);
              if (!is_o) {
                bulk_commit();
                bulk_wait_read();
                __nanosleep(kPaceNs);
              }
            }
            bulk_commit();
            bulk_wait_all();
            mbar_arrive(sb + kBars + 8 * (kStgBar + cw));
            if (ev == 3 + cw) {
#pragma unroll
              for (int i = 0; i < 2; i++) asm volatile("mbarrier.arrive.shared::cluster.b64 _, [%0], 4;" ::"r"(map_cta(sb + kBars + 8 * 37, i)) : "memory");
            }
            flag_signal(SC_AT(flags, kFlHH + ev * 2 - 3 + cw + r * kFlRow));
            TS(44 + cw * 8 + ev);
            if (ev == 2 && cw) {
              sts32(sb + kPlan, await_word(sc->plan + (uint32_t)c, ep) >> (r >> 1) * 4 & 15);
              mbar_expect_tx(rb, 16384);
#pragma unroll 1
              for (int i = 0; i < 2; i++) tma2d(stg + 8192 + i * 16384, &p.hst, c * 128 + i * 64, r * 128 + 64, rb);
            }
          }
        }
        nb_sync(kNbSelf + cw, 32);
        if (ev >= 2 && ev + cw >= 3 && elect_one()) {
          const int wv = cw == 0 ? 3 : ev == 2 ? 0 : 4;
#pragma unroll 1
          for (int i = wv; i <= max(wv, 2); i++) flag_wait(SC_AT(flags, kFlHH + i + r * kFlRow), ep * 8);
          fence_async();
          mbar_arrive(sb + kBars + 8 * (kWaveBar + (wv >> 1)));
          if (wv == 4) {
            mbar_expect_tx(sb + kBars + 8 * kPartBar, 16384);
#pragma unroll 1
            for (int i = 0; i < 2; i++) tma2d(stg + 16384 + i * 8192, &p.hst, c * 128 + i * 64, r * 128, sb + kBars + 8 * kPartBar);
          }
        }
        nb_sync(kNbSelf + cw, 32);
#pragma unroll 1
        for (int sub = 0; ev < 3 && (ev != 0 || cw == 1); sub++) {
          nb_sync(kNbSelf + cw, 32);
          if (ev == 0) check_blocks(p, sc, sb, r, c, sub, land_par);
          const int u = ev < 0 ? cw : 2 * ev + 1 + cw, lane = fresh_tid() & 31;
          if (u == 1 && !sub) {
            uint3 st[5];
            load_tagged<5, true>(st, SC_AT(stat1, r * 128 + lane), 32, ep, SC_AT(stat1, (r < 2 ? r : r - 2) * 128 + (lane & 7)) + 120);
#pragma unroll
            for (int i = 0; i < 4; i++) sts64(sb + kStat + (i * 32 + lane) * 8, st[i].x, st[i].y);
            sts64(sb + kStat - 64 + (lane & 7) * 8, st[4].x, st[4].y);
            nb_sync(kNbSelf + cw, 32);
            if (lane < 4) mbar_arrive(sb + kBars + 8 * kStatBar);
            if (lane == 0) TS(17);
          }
          if (u == 1) {
            const uint4* gh = SC_AT(halo, (sub * 128 + bid) * 192 + lane) - 16 * 192;
            uint4 hv[6] = {};
            nb_sync(kNbHalo, 64);
            uint32_t ns = sub ? kHaloNs : 2 * kBackoffNs;
#pragma unroll 1
            for (int spins = 0; r >= 2; spins++) {
              if (ns) __nanosleep(ns);
              ns = sub ? 0 : kBackoffNs;
              if (spins > 2000000) __trap();
#pragma unroll
              for (int i = 0; i < 6; i++) hv[i] = ld_b128(gh + i * 32);
              uint32_t bad = (hv[5].y ^ ep) | (hv[5].z ^ ep);
#pragma unroll
              for (int i = 0; i < 6; i++) bad |= hv[i].w ^ ep;
              if (!__any_sync(~0u, bad != 0)) break;
            }
            const uint32_t dst = sb + kStage + sub * 32768 + lane * 16;
            sts128(dst, make_uint4(hv[0].x, hv[0].y, hv[0].z, hv[1].x));
            sts128(dst + 512, make_uint4(hv[1].y, hv[1].z, hv[2].x, hv[2].y));
            sts128(dst + 1024, make_uint4(hv[2].z, hv[3].x, hv[3].y, hv[3].z));
            sts128(dst + 1536, make_uint4(hv[4].x, hv[4].y, hv[4].z, hv[5].x));
            nb_arrive(kNbHalo + 1, 64);
            if (lane == 0) TS(123 + sub);
          }
          if (sub) break;
          uint3 v[3];
          load_tagged<3, false>(v, SC_AT(cs, c * 96 + u * 768 + lane), 32, ep);
          if (u < 2) {
#pragma unroll
            for (int i = 0; i < 3; i++)
#pragma unroll
              for (int k = 0; k < 8; k++)
                sts32(sb + kAug + cw * 4096 + i * 1024 + k * 128 + ((lane * 4) ^ (k * 16)), k == 7 ? 0x3F803F80u : k == 4 || k == 6 ? v[i].z : k & 1 && k != 5 ? v[i].y : v[i].x);
            fence_async_smem();
          } else {
#pragma unroll
            for (int i = 0; i < 3; i++) sts64(sb + kCs + cw * 768 + (i * 32 + lane) * 8, v[i].x, v[i].y);
          }
          nb_sync(kNbSelf + cw, 32);
          if (lane == 0) { mbar_arrive(sb + kBars + 8 * (kAuxBar + cw)); TS(104 + u); }
        }
        nb_sync(kNbSelf + cw, 32);
        if (ev < 0 && cw == 0 && elect_one()) {
#pragma unroll 1
          for (int i = 0; i < 6; i++) {
            __nanosleep(i == 0 ? (c >> 1) * (kFillNs / 4) : kFillNs);
            tma_store2d(i < 2 ? &p.ost : &p.hst, sb + kFill, i < 2 ? (8 + c) * 64 : (c * 2 - 1 + (i >> 1)) * 64, r * 128 + (i & 1) * 64);
            bulk_commit();
          }
          uint32_t peer;
          asm volatile("ld.shared::cluster.b32 %0, [%1];" : "=r"(peer) : "r"(map_cta(sb + kRole, rank ^ 1)) : "memory");
          if (peer != (bid ^ 8)) __trap();
          TS(90);
        }
        nb_sync(kNbSelf + cw, 32);
      }
    }
  } else {
    if (tid == 0) TSS(2);
    cluster_arrive();
    float bias = 0.f;
    float sx = 0.f, mx = 0.f;
    asm volatile("setmaxnreg.inc.sync.aligned.u32 232;");
    if (tid == 0) TSS(4);
    int task;
    asm volatile("mov.u32 %0, %1;" : "=r"(task) : "r"(8 - wg));

#pragma unroll 1
    for (task = __shfl_sync(~0u, task, 0);; task++) {
      if (task == 1 + wg || task == 9 - wg) {
        const int t = fresh_tid();
        uint2 scale;
        do asm volatile("ld.volatile.shared.v2.b32 {%0, %1}, [%2];" : "=r"(scale.x), "=r"(scale.y) : "r"(sb + kScale) : "memory");
        while (scale.y == 0);
        __syncwarp();
        bias = bias_at(low_peak(lds128(sb + (task > 5 ? kRing : kStage + wg * 32768) + (t & 126) * 64 + (t & 14) * 8 + (t & 1) * 8192)) *
                       __uint_as_float(task > 5 ? scale.y : scale.x));
        if (t == 128 && task > 5) TS(95);
      }
      if (wg == 0 && (task == 1 || task == 4)) {
        float acc[2][96];
        const int t = fresh_tid() & 127;
        const uint32_t frag = sb + kOwn + ((t >> 5) * 16 + (t & 15)) * 128, frag_x = ((t >> 4) & 1) ^ (t & 7);
        TSG(2);
        if (task == 4) mbar_wait(sb + kBars + 8 * kResBar, 0);
        auto residual = [&](int m) {
#pragma unroll
          for (int i = 0; i < 8; i++) {
            uint32_t v[4];
            ldsm4(frag + (i >> 2) * 16384 + m * 8192 + ((frag_x ^ (i * 2 & 6)) << 4), v);
#pragma unroll
            for (int e = 0; e < 4; e++) {
              float* d = &acc[m][8 * i + 2 * e];
              asm("shl.b32 %0, %1, 16;" : "=f"(d[0]) : "r"(v[e]));
              asm("and.b32 %0, %1, 0xFFFF0000;" : "=f"(d[1]) : "r"(v[e]));
            }
          }
        };
        residual(1);
        if (task == 1) {
          residual(0);
        } else {
#pragma unroll
          for (int i = 0; i < 64; i++) acc[0][i] = 0.f;
        }
        __syncwarp();
        if ((t & 31) == 0) mbar_arrive(sb + kBars + 8 * kResFreeBar);
        TSG(4);
        if ((tid & 127) == 0) TS(task == 1 ? 6 : 14);
        if (task == 4) {
          mainloop<128, kTail>(sc, acc, sb, 3, 16, 56, -2, true, false, false, 0, __shfl_sync(~0u, lds32(sb + kPlan), 0), &p.out, c * 128, (r >> 1) * 128, warp, outp);
          if ((tid & 127) == 0) TSK(15);
          if (fresh_tid() == 0) {
            if (bid == 0) __stcg(sc->epoch, lds32(sb + kEpoch));
            TSK(19);
          }
          break;
        }
        mainloop<128, -1>(sc, acc, sb, 1, 0, 15, kPauseG2, false, true, false, 0);
        const int t2 = fresh_tid() & 127;
        const uint32_t frag2 = sb + kStage + ((t2 >> 5) * 16 + (t2 & 15)) * 128, frag2_x = ((t2 >> 4) & 1) ^ (t2 & 7);
        const uint32_t empty = map_cta(sb + kBars + 8 * (ring_base(1) + 5), t2 & 1);
        mbar_wait(sb + kBars + 8 * kStgBar, 0);
        mbar_wait(sb + kBars + 8 * ring_base(1), 1);
#pragma unroll
        for (int m = 0; m < 2; m++) {
          const uint32_t a = desc_lo(sb + kRing, 16);
          wg_fence();
#pragma unroll
          for (int k = 0; k < 4; k++) wgmma_n128(acc[m], desc_kept(a, sb) + (m * 512 + k * 2), desc_kept(a, sb) + (kToB + k * 128));
          wg_commit();
          if (m) nb_arrive(kNbOrder + 1, 256);
          wg_wait<1>();
          if (!m) mbar_arrive_cluster_if(empty + 8 * 4, (t2 & 31) < 2);
        }
#pragma unroll
        for (int b = 0; b < 4; b++) {
          if (b == 1) {
            wg_wait<0>();
            if (t2 == 0) TSK(7);
          }
          if (b < 2) {
#pragma unroll
            for (int i = 0; i < 64; i++) asm volatile("" : "+f"(acc[b][i])::"memory");
          }
          stage_quarter(&acc[b & 1][32 * (b >> 1)], frag2, frag2_x, b);
          if (b & 1) {
            fence_async_smem();
            __syncwarp();
            if (elect_one()) {
              mbar_arrive(sb + kBars + 8 * (kHalfBar + (b >> 1)));
#pragma unroll
              for (int m = 0; m < 2; m++)
                if (b == 1) tma_store2d(&p.h16, sb + kStage + m * 8192 + warp * 2048, c * 128, r * 128 + m * 64 + warp * 16);
            }
            __syncwarp();
          }
        }
        if (t2 == 0) TS(8);
        sx = mx = 0.f;
        continue;
      }
      float acc[2][96];
      if (task == 8 + wg) {
        wg_fence();
#pragma unroll
        for (int m = 0; m < 2; m++) wgmma_n192_any(acc[m], desc(64 + m), desc(64 + m));
        wg_commit();
        wg_wait<0>();
#pragma unroll
        for (int i = 0; i < 96; i++) asm volatile("" : "+f"(acc[0][i]), "+f"(acc[1][i])::"memory");
      } else {
        const uint32_t z = fresh_tid() >> 10;
#pragma unroll
        for (int i = 0; i < 96; i++) {
#pragma unroll
          for (int m = 0; m < 2; m++)
            asm("{\n.reg .b32 t;\nlop3.b32 t, %1, %2, %3, 0xEA;\nmov.b32 %0, t;\n}\n" : "=f"(acc[m][i]) : "r"(z), "r"(2 * i + m + 1), "r"(__float_as_uint(bias)));
        }
      }
      if (task > 5) {
        if (wg) {
          if (task == 7) cluster_wait();
          if (tid == 128 && task == 7) { TSS(5); TSK(69); }
          const int t = fresh_tid() & 127, lr = c * 16 + (t >> 3);
          uint32_t pf = t < 64 ? (bid * 16 + (t >> 2)) * kD + (t & 3) * 64 : (r * 48 + t - 64) * kD + c * 64;
          const uint32_t src = sb + kRing + lr * 128 + (((t ^ lr) & 7) << 4), empty = map_cta(sb + kBars + 8 * 4, t & 1), zero = fresh_tid() >> 10;
#pragma unroll 1
          for (int j = task == 7 ? 0 : kSplit; j < (task == 7 ? kSplit : 16); j++) {
            mbar_wait(sb + kBars + 8 * (j & 3), (j >> 2) & 1);
            if (j < 2 && t == 0) TS(102 + j);
            const uint4 v = lds128(src + (j >> 1 == c ? kOwn + (j & 1) * 16384 : (j & 3) * 40960));
            __syncwarp();
            mbar_arrive_cluster_if(empty + 8 * (j & 3) + (v.x & zero), (t & 31) < 2);
            if ((j == 0 || j == 3 || j == 6) && t < 112) { pf += t < 64 ? 256 : 256 * 3 * kD; prefetch_l2(plus(t < 64 ? xp : wqkvp, pf)); }
            const uint32_t u[4] = {v.x, v.y, v.z, v.w};
#pragma unroll
            for (int e = 0; e < 4; e++) {
              const float d0 = bf_lo(u[e]), d1 = bf_hi(u[e]);
              sx += d0 + d1;
              mx = fmaf(d1, d1, fmaf(d0, d0, mx));
            }
          }
          if (task == 7) {
            if (t == 0) TS(96);
            continue;
          }
#pragma unroll
          for (int o = 4; o > 0; o >>= 1) { sx += __shfl_xor_sync(~0u, sx, o); mx += __shfl_xor_sync(~0u, mx, o); }
          const float mean = sx * (1.f / kD);
          float rstd;
          asm("rsqrt.approx.ftz.f32 %0, %1;" : "=f"(rstd) : "f"(fmaxf(mx * (1.f / kD) - mean * mean, 0.f) + 1e-5f));
          const uint32_t ep = lds32(sb + kEpoch);
          const int t2 = fresh_tid();
          if ((t2 & 7) == 0) st_b128(SC_AT(stat1, bid * 16 + (t2 >> 3 & 15)), __float_as_uint(rstd), __float_as_uint(-mean), ep, ep);
          if (t == 0) TS(16);
        }
        if (tid == 0) TSS(6);
        mainloop<192, -1>(sc, acc, sb, 0, wg * 16, wg ? 16 - kAhead : 16, wg ? kPauseG1 : -2, false, wg == 0, false, wg,
                          wg ? min((c + 2) & 7, 6) : c);
        int t = fresh_tid() & 127, lane = t & 31, g = lane >> 2, q = lane & 3;
        const int w = warp & 3;
        const uint32_t stg = sb + kStage + wg * 32768;
        auto tail = [&](int m, int k0, int k1) {
          wg_fence();
#pragma unroll
          for (int k = k0; k < k1; k++) {
            const uint64_t a = desc_kept(desc_lo(sb + kRing, 16), sb) + (4 - kAhead + (k >> 2)) * (40960 >> 4);
            wgmma_n192(acc[m], a + (m * 512 + (k & 3) * 2), a + (kToB + (k & 3) * 128));
          }
        };
        auto release = [&](int j, bool cond) { mbar_arrive_cluster_if(map_cta(sb + kBars + 8 * (4 + (j & 3)), lane & 1), cond); };
        if (wg) {
#pragma unroll
          for (int j = 32 - kAhead; j < 32; j++) {
            TST(2 * (j & 1));
            mbar_wait(sb + kBars + 8 * (j & 3), 1);
            TST(2 * (j & 1) + 1);
            tail(1, 4 * (j - 32 + kAhead), 4 * (j - 31 + kAhead));
            wg_commit();
            if (j == 32 - kAhead) {
              wg_wait<1>();
              release(j - 1, lane < 4);
              mbar_wait(sb + kBars + 8 * kResFreeBar, 0);
            }
          }
        } else {
          nb_arrive(kNbOrder + 1, 256);
          wg_wait<0>();
          release(15, lane < 2);
          if (t == 0) TSK(1);
        }
        TST(4);
        mbar_wait(sb + kBars + 8 * (kAuxBar + wg), 0);
        mbar_wait(sb + kBars + 8 * kStatBar, 0);
        {
          uint32_t am[4];
#pragma unroll
          for (int i = 0; i < 4; i++) {
            const float m1 = __uint_as_float(lds32(sb + kStat + (w * 16 + g) * 8 + 4 + (i >> 1) * 512 + (i & 1) * 64));
            const float m2 = bf_rest(m1), lo = q & 1 ? m2 : m1;
            am[i] = bf_upper(lo, q == 3 ? -bias : q == 2 ? bf_rest(m2) : lo);
          }
          const uint64_t db = (uint64_t)desc_lo(sb + kAug + wg * 4096, 1024) | (0x40000000ull << 32);
          TST(5);
          wg_fence();
          wgmma_n192_rs(acc[1], am[2], am[3], 0u, db);
          wg_commit();
          TST(6);
          wg_fence();
          wgmma_n192_rs(acc[0], am[0], am[1], 0u, db);
          wg_commit();
          if (wg) {
            tail(0, 0, 4 * kAhead);
            wg_commit();
            wg_wait<2>();
          } else {
            wg_wait<1>();
          }
          TST(8);
#pragma unroll
          for (int i = 0; i < 96; i++) asm volatile("" : "+f"(acc[1][i])::"memory");
        }
        t = fresh_tid() & 127, lane = t & 31;
        const uint32_t ep = lds32(sb + kEpoch);
        uint32_t pk[2][48];
        auto fold = [&](int pp, int jn, int hf) {
          const uint32_t v = pack_bf16(acc[pp][4 * jn + 2 * hf], acc[pp][4 * jn + 2 * hf + 1]);
          pk[pp][2 * jn + hf] = jn >= 16 ? movm(v) : v;
        };
        if (t == 96) TS(115 + wg);
#pragma unroll
        for (int jn = 8; jn < 24; jn++) fold(1, jn, 1);
        if (w < 3) {
#pragma unroll
          for (int i = 0; i < 4; i++)
            sts128(stg + (w + 5) * 2048 + i * 512 + lane * 16, make_uint4(pk[1][17 + 8 * i], pk[1][19 + 8 * i], pk[1][21 + 8 * i], pk[1][23 + 8 * i]));
        } else if (r < 14) {
          uint4* gh = SC_AT(halo, (wg * 128 + bid) * 192 + lane);
#pragma unroll
          for (int i = 0; i < 6; i++) st_b128(gh + i * 32, pk[1][17 + 6 * i], i < 5 ? pk[1][(19 + 6 * i) % 48] : ep, i < 5 ? pk[1][(21 + 6 * i) % 48] : ep, ep);
          if (wg == 0) {
#pragma unroll 1
            for (int i = 0; i < 6; i++, gh += 32) st_b128(gh + 128 * 192, 0, 0, 0, ep - 1);
          }
        }
        if (w == 3) nb_arrive(kNbHalo, 64);
        if (wg) nb_arrive(kNbOrder, 256);
        TST(9);
        if (t == 96) TS(111 + wg);
#pragma unroll
        for (int jn = 23; jn >= 0; jn--) {
          fold(1, jn, 0);
          if (jn < 8) fold(1, jn, 1);
        }
        t = fresh_tid() & 127, lane = t & 31, g = lane >> 2, q = lane & 3;
        const bool sel0 = 2 * q > g, sel1 = 2 * q + 1 > g, no_prev = (r < 2 && w == 0);
        const uint4 ones = lds128(sb + kOnes);
        const uint32_t lowmask = (sel0 ? 0x0000FFFFu : 0u) | (sel1 ? 0xFFFF0000u : 0u) | ones.y;
        float rs[4][2], rk[4][2];
#pragma unroll
        for (int i = 0; i < 4; i++) {
          const uint32_t a = sb + kStat + w * 128 + (i >> 1) * 512 + (i & 1) * 64;
          const float rq = __uint_as_float(lds32(a + g * 8)) * (0.17677669529663687f * 1.4426950408889634f);
          rk[i][0] = __uint_as_float(lds32(a + q * 16 - (sel0 ? 64 : 0)));
          rk[i][1] = __uint_as_float(lds32(a + q * 16 + 8 - (sel1 ? 64 : 0)));
          rs[i][0] = rk[i][0] * rq;
          rs[i][1] = rk[i][1] * rq;
        }
        {
          uint32_t all = ~0u;
#pragma unroll
          for (int i = 0; i < 48; i++) if (i < 16 || !(i & 1)) all &= pk[1][i];
          if (all == kPoison) sts32(sb + kZero + 8, 0);
        }
        TST(10);
        wg_wait<0>();
        TST(11);
#pragma unroll
        for (int j = 32 - kAhead; j < 32; j++) release(j, lane < 4 * wg && (w != 0 || j < 31));
#pragma unroll
        for (int i = 0; i < 96; i++) asm volatile("" : "+f"(acc[0][i])::"memory");
        if (t == 0 && wg) TSK(21);
#pragma unroll
        for (int jn = 8; jn < 24; jn++) fold(0, jn, 1);
#pragma unroll
        for (int i = 0; i < 4; i++)
          sts128(stg + (w + 1) * 2048 + i * 512 + lane * 16, make_uint4(pk[0][17 + 8 * i], pk[0][19 + 8 * i], pk[0][21 + 8 * i], pk[0][23 + 8 * i]));
#pragma unroll
        for (int jn = 23; jn >= 0; jn--) {
          fold(0, jn, 0);
          if (jn < 8) fold(0, jn, 1);
        }
        if (t == 0) TS(113 + wg);
        nb_sync(kNbWg + wg, 128);
        uint32_t hal[2][16];
        auto load_halo = [&](int m) {
#pragma unroll
          for (int i = 0; i < 4; i++) {
            const uint4 v = lds128(stg + w * 2048 + m * 8192 + i * 512 + lane * 16);
            uint32_t* h = &hal[m][i * 4];
            h[0] = v.x; h[1] = v.y; h[2] = v.z; h[3] = v.w;
          }
        };
        load_halo(1);
        if (w == 0) {
          nb_sync(kNbHalo + 1, 64);
          release(31, lane < 4 * wg);
        }
        load_halo(0);
        __syncwarp();
        if (t == 0) TS(2 + wg * 20);
        {
          uint32_t all = lowmask;
#pragma unroll
          for (int i = 0; i < 32; i++) if (i < 16 || !(i & 1)) all &= pk[0][i];
#pragma unroll
          for (int i = 0; i < 8; i++) all &= __float_as_uint(rs[i >> 1][i & 1]);
          if (all == kPoison) sts32(sb + kZero + 8, 0);
        }
        nb_sync(kNbWin, 256);
        if (t == 0) TS(9 + wg * 20);
        const uint32_t zero = lds32(sb + kZero);
        float s0[4][4], s1[4][4], s2[4][4];
#pragma unroll
        for (int k = 0; k < 4; k++) {
          pk[k >> 1][8 * (k & 1)] |= zero;
#pragma unroll
          for (int e = 0; e < 4; e++) s0[k][e] = s1[k][e] = s2[k][e] = 0.f;
        }
#pragma unroll
        for (int ks = 0; ks < 2; ks++)
#pragma unroll
          for (int k = 0; k < 4; k++) {
            const uint32_t* qf = &pk[k >> 1][8 * (k & 1) + 4 * ks];
            const uint32_t* kf = &pk[k >> 1][16 + 8 * (k & 1) + 4 * ks];
            const uint32_t* hf = &hal[k >> 1][4 * (k & 1) + 2 * ks];
            mma16816(s0[k], qf[0], qf[1], qf[2], qf[3], hf[0], hf[1]);
            mma16816(s1[k], qf[0], qf[1], qf[2], qf[3], kf[0], kf[2]);
            mma16816(s2[k], qf[0], qf[1], qf[2], qf[3], kf[1], kf[3]);
          }
        float ea[4][2], eb[4][2], ma[4], mb[4];
#pragma unroll
        for (int k = 0; k < 4; k++) {
          const float *ra = rs[k & 2], *rb = rs[(k & 2) + 1];
          if (no_prev && k < 2) s0[k][0] = s0[k][1] = -INFINITY;
          ea[k][0] = (sel0 ? s0[k][0] : s1[k][0]) * ra[0]; ea[k][1] = (sel1 ? s0[k][1] : s1[k][1]) * ra[1];
          eb[k][0] = (sel0 ? s1[k][2] : s2[k][2]) * rb[0]; eb[k][1] = (sel1 ? s1[k][3] : s2[k][3]) * rb[1];
          ma[k] = fmaxf(ea[k][0], ea[k][1]); mb[k] = fmaxf(eb[k][0], eb[k][1]);
        }
#pragma unroll
        for (int o = 1; o < 4; o <<= 1)
#pragma unroll
          for (int k = 0; k < 4; k++) {
            ma[k] = fmaxf(ma[k], __shfl_xor_sync(~0u, ma[k], o));
            mb[k] = fmaxf(mb[k], __shfl_xor_sync(~0u, mb[k], o));
          }
        float ov[4][4][4], ls[4][4];
        uint32_t all = 0;
#pragma unroll
        for (int k = 0; k < 4; k++) {
          const float *ra = rk[k & 2], *rb = rk[(k & 2) + 1];
          ea[k][0] = ex2(ea[k][0] - ma[k]); ea[k][1] = ex2(ea[k][1] - ma[k]);
          eb[k][0] = ex2(eb[k][0] - mb[k]); eb[k][1] = ex2(eb[k][1] - mb[k]);
          const uint32_t pa = pack_bf16(ea[k][0] * ra[0], ea[k][1] * ra[1]), pb = pack_bf16(eb[k][0] * rb[0], eb[k][1] * rb[1]);
          const uint32_t* vf = &pk[k >> 1][32 + 8 * (k & 1)];
          const uint32_t* hf = &hal[k >> 1][8 + 4 * (k & 1)];
#pragma unroll
          for (int d2 = 0; d2 < 2; d2++) {
#pragma unroll
            for (int e = 0; e < 4; e++) ov[k][d2][e] = ov[k][2 + d2][e] = 0.f;
            mma1688(ov[k][d2], hf[2 * d2], hf[2 * d2 + 1], pa & lowmask);
            mma1688(ov[k][2 + d2], vf[4 * d2], vf[4 * d2 + 2], pb & lowmask);
          }
#pragma unroll
          for (int d2 = 0; d2 < 2; d2++) {
            mma1688(ov[k][d2], vf[4 * d2], vf[4 * d2 + 2], pa & ~lowmask);
            mma1688(ov[k][2 + d2], vf[4 * d2 + 1], vf[4 * d2 + 3], pb & ~lowmask);
          }
          ls[k][0] = ls[k][1] = ls[k][2] = ls[k][3] = 0.f;
          mma16816(ls[k], ones.x, ones.y, ones.z, ones.w, pack_bf16(ea[k][0], ea[k][1]), pack_bf16(eb[k][0], eb[k][1]));
          if (k >= kDone) all |= pa & pb;
        }
#pragma unroll
        for (int k = 0; k < 4; k++) {
          if (k == kDone) {
            if (all == 0xFFFFFFFFu) sts32(sb + kZero + 8, 0);
            nb_arrive(kNbWin + 1, 256);
            all = 0;
          }
          all |= (__float_as_uint(ov[k][0][0]) & __float_as_uint(ov[k][1][0]) & __float_as_uint(ov[k][2][0])) &
                 (__float_as_uint(ov[k][3][0]) & __float_as_uint(ls[k][0]));
        }
        const uint32_t nil = lds32(sb + kZero);
        const uint32_t frag = stg + (w * 16 + (lane & 15)) * 128, frag_x = (lane >> 4) ^ (lane & 7);
        uint32_t after = all;
#pragma unroll
        for (int k = 0; k < 4; k++) {
          uint32_t h[2][4];
#pragma unroll
          for (int hf = 0; hf < 2; hf++) {
            const float i0 = rcp(__uint_as_float(__float_as_uint(ls[k][2 * hf]) | (after & nil)));
            const float i1 = rcp(__uint_as_float(__float_as_uint(ls[k][2 * hf + 1]) | (after & nil)));
#pragma unroll
            for (int e = 0; e < 4; e++) h[e >> 1][2 * (e & 1) + hf] = pack_bf16(ov[k][2 * hf + (e >> 1)][2 * (e & 1)] * i0, ov[k][2 * hf + (e >> 1)][2 * (e & 1) + 1] * i1);
            after = h[0][hf];
          }
#pragma unroll
          for (int d2 = 0; d2 < 2; d2++) stsm4_t(frag + (k >> 1) * 8192 + ((frag_x ^ ((k & 1) * 4 + d2 * 2)) << 4), h[d2][0], h[d2][1], h[d2][2], h[d2][3]);
        }
        fence_async_smem();
        if (wg) {
          __syncwarp();
          if (elect_one()) {
            tma_store2d(&p.o16, stg + w * 2048, (8 + c) * 64, r * 128 + w * 16);
            tma_store2d(&p.o16, stg + 8192 + w * 2048, (8 + c) * 64, r * 128 + 64 + w * 16);
            bulk_commit();
            bulk_wait_read();
            mbar_arrive(sb + kBars + 8 * kSentBar);
          }
          __syncwarp();
        } else {
          nb_arrive(kNbPub, 160);
        }
        if (t == 0) TS(3 + wg * 20);
        task = wg;
        sx = mx = bias = 0.f;
        continue;
      }

      {
#pragma unroll 1
        for (int part = task != 2; part < 2; part++) {
          if ((tid & 127) == 0) TS(6 + 2 * task + wg * 20);
          if (task + part == 5) {
            mainloop<128, 0>(sc, acc, sb, 3, 0, 16, -2, false, true, false, 1);
            continue;
          }
          const int j0 = task == 3 ? 48 - wg * 16 : part == 0 ? 2 - 2 * wg : 18 - 14 * wg;
          mainloop<192, 0>(sc, acc, sb, 2, j0, task != 2 ? 16 : part == 0 ? 2 : 14, -2, false, true, part == 0, wg);
          if (part == 0 && wg == 0) {
            const int t = fresh_tid() & 127;
            const uint32_t ep = lds32(sb + kEpoch);
            {
              float s = 0.f, ss = 0.f;
#pragma unroll 1
              for (int i = 0; i < 16; i++) {
                const uint4 v = lds128(sb + kStage + t * 128 + (i >> 3) * 16384 + (((i ^ t) & 7) << 4));
                const uint32_t u[4] = {v.x, v.y, v.z, v.w};
#pragma unroll
                for (int e = 0; e < 4; e++) {
                  const float d0 = bf_lo(u[e]), d1 = bf_hi(u[e]);
                  s = (s + d0) + d1;
                  ss = fmaf(d1, d1, fmaf(d0, d0, ss));
                }
              }
              st_b128(SC_AT(stat2, c * kS + r * 128 + t), __float_as_uint(s), __float_as_uint(ss), ep, ep);
            }
            __nanosleep(kStatNs);
            float2 sum = make_float2(0.f, 0.f);
#pragma unroll 1
            for (int i = 0; i < 2; i++) {
              uint3 a[4];
              load_tagged<4, true>(a, SC_AT(stat2, i * 4 * kS + r * 128 + t), kS, ep);
              sum.x += (__uint_as_float(a[0].x) + __uint_as_float(a[1].x)) + (__uint_as_float(a[2].x) + __uint_as_float(a[3].x));
              sum.y += (__uint_as_float(a[0].y) + __uint_as_float(a[1].y)) + (__uint_as_float(a[2].y) + __uint_as_float(a[3].y));
            }
            const float mean = sum.x * (1.f / kD);
            sts64f(sb + kStat + t * 8, make_float2(fmaxf(sum.y * (1.f / kD) - mean * mean, 0.f) + 1e-5f, -mean));
            __syncwarp();
            if (elect_one()) {
              bulk_commit();
              bulk_wait_read();
              mbar_arrive(sb + kBars + 8 * kStatBar);
            }
            __syncwarp();
            if (t == 0) TS(37);
          }
        }
      }
      const int t = fresh_tid() & 127, w = warp & 3, lane = t & 31, g = lane >> 2, q = lane & 3;
      const uint32_t stg = sb + kStage + wg * 32768;
      uint32_t csv = sb + kCs + wg * 768 + q * 8;
      uint32_t statv = sb + kStat + (w * 16 + g) * 8;
      const uint32_t frag = stg + (w * 16 + (lane & 15)) * 128;
      const uint32_t frag_x = (lane >> 4) ^ (lane & 7);
      const uint32_t priv = stg + (t & 96) * 64 + lane * 16;
      if (t == 0) TSK(7 + 2 * task + wg * 20);

      if (task == 4) {
        mbar_wait(sb + kBars + 8 * (kAuxBar + 1), 1);
        mbar_wait(sb + kBars + 8 * kResFreeBar, 1);
        mbar_wait(sb + kBars + 8 * (kStgBar + 1), 0);
      }
      asm volatile("" : "+r"(csv), "+r"(statv)::"memory");

      {
#pragma unroll
        for (int i = 0; i < 96; i++) asm volatile("sub.f32 %0, %0, %1;" : "+f"(acc[0][i]) : "f"(bias));
        auto next_rows = [&](int i) { asm volatile("sub.f32 %0, %1, %2;" : "=f"(acc[0][i]) : "f"(acc[1][i]), "f"(bias)); };
#pragma unroll 1
        for (int pp = 0; pp < 2; pp++) {
          TSG(pp);
          RowConst rc[2];
#pragma unroll
          for (int hf = 0; hf < 2; hf++) {
            const float2 st = lds64f_const(statv + pp * 512 + hf * 64);
            float rstd;
            asm("rsqrt.approx.ftz.f32 %0, %1;" : "=f"(rstd) : "f"(st.x));
            rc[hf] = {st.y, 0.7978845608f * rstd, 0.0356774081f * rstd * rstd * rstd, 0.5f * rstd * rstd};
          }
#pragma unroll
          for (int j2 = 0; j2 < 4; j2++) {
            uint32_t hv[4];
#pragma unroll
            for (int jj = 0; jj < 2; jj++) {
              const int jn = 2 * j2 + jj;
              const float2 cg = lds64f_const(csv + jn * 32), cu = lds64f_const(csv + 256 + jn * 32);
#pragma unroll
              for (int hf = 0; hf < 2; hf++) {
                const float nm = rc[hf].nmean;
                const float g0 = fmaf(nm, cg.x, acc[0][4 * jn + 2 * hf]), g1 = fmaf(nm, cg.y, acc[0][4 * jn + 2 * hf + 1]);
                const float u0 = fmaf(nm, cu.x, acc[0][32 + 4 * jn + 2 * hf]), u1 = fmaf(nm, cu.y, acc[0][33 + 4 * jn + 2 * hf]);
                hv[2 * jj + hf] = pack_bf16(g0 * u0 * gate_scale(g0, rc[hf]), g1 * u1 * gate_scale(g1, rc[hf]));
              }
            }
            stsm4(frag + 16384 + pp * 8192 + ((frag_x ^ (j2 * 2)) << 4), hv[0], hv[1], hv[2], hv[3]);
          }
          if (task < 4) {
            if (task == 2) {
#pragma unroll
              for (int j2 = 0; j2 < 4; j2++) {
                uint32_t hv[4];
#pragma unroll
                for (int jj = 0; jj < 2; jj++) {
                  const int jn = 16 + 2 * j2 + jj;
                  const float2 cs = lds64f_const(csv + jn * 32);
#pragma unroll
                  for (int hf = 0; hf < 2; hf++) {
                    const float nm = rc[hf].nmean;
                    const float t0 = fmaf(nm, cs.x, acc[0][4 * jn + 2 * hf]), t1 = fmaf(nm, cs.y, acc[0][4 * jn + 2 * hf + 1]);
                    hv[2 * jj + hf] = pack_bf16(t0 * gate_scale(t0, rc[hf]), t1 * gate_scale(t1, rc[hf]));
                  }
                }
                sts128(priv + pp * 8192 + j2 * 512, make_uint4(hv[0], hv[1], hv[2], hv[3]));
              }
            } else {
              uint4 park[4];
#pragma unroll
              for (int j2 = 0; j2 < 4; j2++) park[j2] = lds128(priv + pp * 8192 + j2 * 512);
              __syncwarp();
#pragma unroll
              for (int j2 = 0; j2 < 4; j2++) {
                const uint32_t pv[4] = {park[j2].x, park[j2].y, park[j2].z, park[j2].w};
                uint32_t hv[4];
#pragma unroll
                for (int jj = 0; jj < 2; jj++) {
                  const int jn = 16 + 2 * j2 + jj;
                  const float2 cs = lds64f_const(csv + jn * 32);
#pragma unroll
                  for (int hf = 0; hf < 2; hf++) {
                    const float nm = rc[hf].nmean;
                    const float t0 = fmaf(nm, cs.x, acc[0][4 * jn + 2 * hf]), t1 = fmaf(nm, cs.y, acc[0][4 * jn + 2 * hf + 1]);
                    asm("mul.rn.bf16x2 %0, %1, %2;" : "=r"(hv[2 * jj + hf]) : "r"(pack_bf16(t0, t1)), "r"(pv[2 * jj + hf]));
                  }
                }
                stsm4(frag + pp * 8192 + ((frag_x ^ (j2 * 2)) << 4), hv[0], hv[1], hv[2], hv[3]);
              }
            }
            if (pp == 1) break;
#pragma unroll
            for (int i = 64; i < 96; i++) next_rows(i);
          }
          if (pp == 1) break;
#pragma unroll
          for (int i = 0; i < 64; i++) next_rows(i);
        }
      }
      const int t3 = fresh_tid() & 127;
      uint4* part = SC_AT(part, bid * 1024 + (t3 & 96) * 8 + (t3 & 31));
      if (task == 2 && wg) {
#pragma unroll
        for (int k = 0; k < 8; k++) st_b128(part + k * 32, kPoison, kPoison, kPoison, kPoison);
      }
      fence_async_smem();
      nb_arrive(kNbPub + wg, 160);
      if (t == 0) TS(task == 4 ? 57 : 56 + task + wg * 2);
      if (task == 4) {
        mbar_wait(sb + kBars + 8 * kPartBar, 0);
        const bool none = lds32(sb + kPlan) == 0;
#pragma unroll 1
        for (int b = 1, spins = 0; b >= 0;) {
          uint4 v[4] = {};
          uint32_t top = 0;
          if (!none) {
#pragma unroll
            for (int k = 0; k < 4; k++) v[k] = ld_b128(part + (128 + k * 32));
          }
#pragma unroll
          for (int k = 0; k < 4; k++) {
            top = max(max(top, v[k].x), max(v[k].y, max(v[k].z, v[k].w)));
          }
          if (__any_sync(~0u, top == kPoison)) {
            if (++spins > 100000) __trap();
            __nanosleep(kPartNs);
            continue;
          }
#pragma unroll
          for (int k = 0; k < 4; k++) {
            uint32_t h[4];
            ldsm4(frag + 16384 + b * 8192 + ((frag_x ^ (k * 2)) << 4), h);
            asm("add.rn.bf16x2 %0, %0, %1;" : "+r"(v[k].x) : "r"(h[0]));
            asm("add.rn.bf16x2 %0, %0, %1;" : "+r"(v[k].y) : "r"(h[1]));
            asm("add.rn.bf16x2 %0, %0, %1;" : "+r"(v[k].z) : "r"(h[2]));
            asm("add.rn.bf16x2 %0, %0, %1;" : "+r"(v[k].w) : "r"(h[3]));
            sts128(stg + (t3 & 96) * 128 + (t3 & 31) * 16 + b * 2048 + k * 512, v[k]);
          }
          b--;
          part -= 128;
        }
        if (t == 0) TSK(56);
        nb_arrive(kNbPart, 256);
        break;
      }
      sx = mx = 0.f;
    }
  }
}

typedef CUresult (*EncodeTiledFn)(CUtensorMap*, CUtensorMapDataType, cuuint32_t, void*, const cuuint64_t*, const cuuint64_t*,
                                  const cuuint32_t*, const cuuint32_t*, CUtensorMapInterleave, CUtensorMapSwizzle,
                                  CUtensorMapL2promotion, CUtensorMapFloatOOBfill);

void encode(EncodeTiledFn fn, CUtensorMap* m, const void* base, int rank, cuuint64_t d0, cuuint64_t d1, cuuint64_t d2,
            cuuint64_t s1, cuuint64_t s2, cuuint32_t b2, cuuint32_t b1 = 64) {
  const cuuint64_t dims[3] = {d0, d1, d2}, strides[2] = {s1, s2};
  const cuuint32_t box[3] = {64, b1, b2}, es[3] = {1, 1, 1};
  fn(m, CU_TENSOR_MAP_DATA_TYPE_BFLOAT16, rank, const_cast<void*>(base), dims, strides, box, es, CU_TENSOR_MAP_INTERLEAVE_NONE,
     CU_TENSOR_MAP_SWIZZLE_128B, CU_TENSOR_MAP_L2_PROMOTION_L2_128B, CU_TENSOR_MAP_FLOAT_OOB_FILL_NONE);
}

}

extern "C" void kernel_launch(void* const* d_in, const int* in_sizes, int n_in, void* d_out, int out_size) {
  void* fnp = nullptr;
  cudaDriverEntryPointQueryResult qr;
  cudaGetDriverEntryPoint("cuTensorMapEncodeTiled", &fnp, cudaEnableDefault, &qr);
  EncodeTiledFn fn = (EncodeTiledFn)fnp;
  void *o, *h, *hh;
  cudaGetSymbolAddress(&o, g_o);
  cudaGetSymbolAddress(&h, g_h);
  cudaGetSymbolAddress(&hh, g_hh);

  Params p;
  Scratch* sc;
  cudaGetSymbolAddress((void**)&sc, g_scratch);
  encode(fn, &p.x, d_in[0], 3, kD, kS / 2, 2, 4 * kD, 2 * kD, 1, 128);
  encode(fn, &p.out, d_out, 3, kD, kS / 2, 2, 4 * kD, 2 * kD, 1, 16);
  encode(fn, &p.wqkv, d_in[1], 2, 3 * kD, kD, 1, 6 * kD, 0, 1);
  encode(fn, &p.wo, d_in[2], 2, kD, kD, 1, 2 * kD, 0, 1);
  encode(fn, &p.wd, d_in[6], 2, kD, kF, 1, 2 * kD, 0, 1);
  encode(fn, &p.wg, d_in[4], 2, kF, kD, 1, 2 * kF, 0, 1);
  encode(fn, &p.wu, d_in[5], 2, kF, kD, 1, 2 * kF, 0, 1);
  encode(fn, &p.o, o, 2, kD, kS, 1, 2 * kD, 0, 1, 128);
  encode(fn, &p.h, h, 2, kD, kS, 1, 2 * kD, 0, 1, 128);
  encode(fn, &p.hh, hh, 2, kF, kS, 1, 2 * kF, 0, 1, 128);
  encode(fn, &p.ost, o, 2, kD, kS, 1, 2 * kD, 0, 1);
  encode(fn, &p.o16, o, 2, kD, kS, 1, 2 * kD, 0, 1, 16);
  encode(fn, &p.h16, h, 2, kD, kS, 1, 2 * kD, 0, 1, 16);
  encode(fn, &p.hst, h, 2, kD, kS, 1, 2 * kD, 0, 1);
  encode(fn, &p.hhst, hh, 2, kF, kS, 1, 2 * kF, 0, 1);
  for (int c = 0; c < 8; c++) {
    for (int j = 0; j < 32; j++) p.g1[c][j] = g1_block(j, c) | (j >= 16 && (j < 20 || g1_block(j, c) >> 1 == c) ? kInPlace : 0);
    for (int j = 0; j < 16; j++) p.g2[c][j] = g2_block(j, c);
    for (int j = 0; j < 64; j++)
      p.g3[c][j] = g3_block(j, c) | ((0x000F000F003C000Full >> j & 1) && j != 28 + c ? kInPlace : 0) | g3_tile(j) << 5;
  }
  for (int i = 0; i < 56; i++)
    p.g4[i] = g4_block(i) | (i >= kFirstShared && i % 3 == 0 && i < kFirstShared + 3 * kMost ? kShared : 0) | (i % 24 == 0 ? kNextWave : 0);
  p.wop = (const uint4*)d_in[2];
  p.wgp = (const uint4*)d_in[4];
  p.wup = (const uint4*)d_in[5];

  int dev = 0, sms = 0;
  cudaGetDevice(&dev);
  cudaDeviceGetAttribute(&sms, cudaDevAttrMultiProcessorCount, dev);
  auto* kernel = sms == 132 ? fused_block_kernel<true> : fused_block_kernel<false>;
  cudaFuncSetAttribute(kernel, cudaFuncAttributeMaxDynamicSharedMemorySize, kSmemBytes);
  kernel<<<132, kThreads, kSmemBytes, cudaStreamPerThread>>>(sc, (const __nv_bfloat16*)d_in[0], (const __nv_bfloat16*)d_in[1],
                                                                  (__nv_bfloat16*)d_out, p);
}
```

```cpp
#include <cuda_runtime.h>
#include <cuda_bf16.h>
#include <cuda.h>
#include <stddef.h>
#include <stdint.h>

namespace {

constexpr int kS = 2048, kD = 1024, kF = 3584;
constexpr int kThreads = 384;

constexpr int kRing = 0;
constexpr int kStage = 163840;
constexpr int kAug = kStage + 16384;
constexpr int kOwn = kStage + 32768;
constexpr int kFill = kStage + 24576;
constexpr int kCs = kStage + 65536;
constexpr int kStat = kCs + 1536;
constexpr int kBars = kStat + 1024;
constexpr int kSmemBytes = kBars + 512;
constexpr int kResBar = 38;
constexpr int kAuxBar = 39;
constexpr int kStgBar = 41;
constexpr int kResFreeBar = 43;
constexpr int kStatBar = 44;
constexpr int kPartBar = 45;
constexpr int kWaveBar = 46;
constexpr int kHalfBar = 49;
constexpr int kSentBar = 51;
constexpr int kLandBar = 52;
constexpr int kNumBars = 58;
static_assert(kNumBars == 4 + 3 * 18, "barrier initialisation is split 4 + 3 x 18");
__host__ __device__ constexpr int bar_count(int i) {
  const int ph = i < 8 ? 0 : i < 18 ? 1 : i < 26 ? 2 : 3, base = ph * 9 - (ph & 1);
  return i < 38 ? (i - base < 4 + (ph & 1) + (ph == 3) ? 2 : ph == 0 ? 16 : 8) : i == kResFreeBar || i == kStatBar || (i >= kHalfBar && i < kLandBar) ? 4 : 1;
}
__host__ __device__ constexpr uint64_t bar_shifts(int first) {
  uint64_t m = 0;
  for (int i = 17; i >= 0; i--) {
    const int n = bar_count(first + i);
    m = m << 3 | (n == 16 ? 4 : n == 8 ? 3 : n >> 1);
  }
  return m;
}
constexpr int kScale = kBars + 464;
constexpr int kPlan = kBars + 472;
constexpr int kOnes = kBars + 480;
constexpr int kZero = kBars + 496;
constexpr int kRole = kBars + 508;
constexpr int kEpoch = kBars + 500;
__device__ __forceinline__ int ring_base(int ph) { return ph * 9 - (ph & 1); }
constexpr int kWide = 25;
constexpr int kFirstShared = 15;
constexpr int kNbOrder = 1;
constexpr int kNbWg = 3;
constexpr int kNbPub = 5;
constexpr int kNbWin = 7;
constexpr int kNbSelf = 13;
constexpr int kNbPart = 11;
constexpr int kNbHalo = 9;

constexpr int kFlO = 0;
constexpr int kFlPace = 1;
constexpr int kFlHH = 3;
constexpr int kFlRow = 32;
constexpr int kNumFlags = 16 * kFlRow;

constexpr int kPauseG1 = 7;
constexpr int kPauseG2 = 0;
constexpr int kAhead = 2;
constexpr int kSplit = 13;
constexpr int kTail = 4;
constexpr int kPartAt = 2;
constexpr int kShare = 5;
constexpr int kMost = 8;
constexpr int kBudget = 328;
constexpr int kStepNs = 167;
constexpr int kRemain = 65500;
constexpr int kDone = 3;
constexpr int kQuietAt = 48;
constexpr int kPfStep = 8;
constexpr int kBackoffNs = 200;
constexpr int kPaceNs = 300;
constexpr int kPartNs = 500;
constexpr int kFillNs = 500;
constexpr int kHaloNs = 150;
constexpr int kGateONs = 150;
constexpr int kGateHNs = 150;
constexpr int kHoldNs = 1200;
constexpr int kSampleNs = 1000;
constexpr int kStatNs = 1500;
constexpr float kBias1 = 512.f, kBias3 = 32768.f;

struct Scratch {
  uint32_t flags[kNumFlags];
  uint32_t epoch[32];
  uint4 stat1[kS];
  uint4 stat2[8 * kS];
  uint4 cs[7 * 8 * 96];
  uint2 finish[128];
  uint2 plan[16];
  uint4 halo[2 * 16 * 8 * 6 * 32];
  uint4 part[128 * 8 * 128];
};
struct Params {
  CUtensorMap x, wqkv, o, wo, h, wg, wu, hh, wd, out;
  CUtensorMap ost, hst, hhst;
  CUtensorMap o16, h16;
  const uint4 *wop, *wgp, *wup;
  uint8_t g1[8][32], g2[8][16], g3[8][64], g4[56], g4in[56];
};

__device__ __align__(256) __nv_bfloat16 g_o[kS * kD];
__device__ __align__(256) __nv_bfloat16 g_h[kS * kD];
__device__ __align__(256) __nv_bfloat16 g_hh[kS * kF];
__device__ __align__(256) Scratch g_scratch;

template <bool BY_SM>
__device__ __forceinline__ int role_id() {
  uint32_t sm;
  asm("mov.u32 %0, %%smid;" : "=r"(sm));
  const int tpc = (BY_SM ? sm : blockIdx.x) >> 1, rank = blockIdx.x & 1;
  if ((tpc | 1) == 61) return 8 + 2 * tpc + rank;
  const int u = tpc - 32, s7 = (u * 37) >> 8;
  const int g = tpc < 32 ? tpc & 7 : tpc < 60 ? 1 + u - 7 * s7 : 0, s = tpc < 32 ? tpc >> 3 : tpc < 60 ? 4 + s7 : tpc - 58;
  return (g * 2 + rank) * 8 + s;
}
#define TS(i) do { } while (0)
#define TSK(i) do { } while (0)
#define TSS(i) do { } while (0)
#define TST(i)
#define TSG(i)

__device__ __forceinline__ uint32_t smem_u32(const void* p) { return (uint32_t)__cvta_generic_to_shared(p); }
template <class T>
__device__ __forceinline__ T* plus(T* p, uint32_t n) {
  uint64_t r;
  asm("{\n.reg .b32 lo, hi;\nmov.b64 {lo, hi}, %1;\nadd.cc.u32 lo, lo, %2;\naddc.u32 hi, hi, 0;\nmov.b64 %0, {lo, hi};\n}\n"
      : "=l"(r) : "l"(p), "r"(n * (uint32_t)sizeof(T)));
  return (T*)r;
}
#define SC_AT(member, n) ((decltype(+sc->member))((char*)plus((decltype(+sc->member))sc, n) + offsetof(Scratch, member)))
__device__ __forceinline__ void mbar_init(uint32_t bar, uint32_t cnt) {
  asm volatile("mbarrier.init.shared::cta.b64 [%0], %1;" ::"r"(bar), "r"(cnt));
}
__device__ __forceinline__ void mbar_expect_tx(uint32_t bar, uint32_t bytes) {
  asm volatile("mbarrier.arrive.expect_tx.shared::cta.b64 _, [%0], %1;" ::"r"(bar), "r"(bytes) : "memory");
}
__device__ __forceinline__ uint32_t map_cta(uint32_t addr, uint32_t cta) {
  uint32_t r;
  asm("mapa.shared::cluster.u32 %0, %1, %2;" : "=r"(r) : "r"(addr), "r"(cta));
  return r;
}
__device__ __forceinline__ void mbar_arrive_cluster_if(uint32_t bar, bool cond) {
  asm volatile("{\n.reg .pred p;\nsetp.ne.u32 p, %1, 0;\n@p mbarrier.arrive.shared::cluster.b64 _, [%0];\n}\n"
               ::"r"(bar), "r"((uint32_t)cond) : "memory");
}
__device__ __forceinline__ void mbar_wait(uint32_t bar, uint32_t parity) {
  asm volatile("{\n.reg .pred p;\nLAB_WAIT:\nmbarrier.try_wait.parity.shared::cta.b64 p, [%0], %1;\n@!p bra LAB_WAIT;\n}\n"
               ::"r"(bar), "r"(parity) : "memory");
  return;
  asm volatile("{\n.reg .pred p;\n.reg .u32 c;\nmov.u32 c, 0;\n"
               "LAB_WAIT:\nmbarrier.try_wait.parity.shared::cta.b64 p, [%0], %1;\n@p bra LAB_DONE;\n"
               "add.u32 c, c, 1;\nsetp.lt.u32 p, c, 2000000;\n@p bra LAB_WAIT;\ntrap;\nLAB_DONE:\n}\n"
               ::"r"(bar), "r"(parity) : "memory");
}
__device__ __forceinline__ void mbar_arrive(uint32_t bar) {
  asm volatile("mbarrier.arrive.shared::cta.b64 _, [%0];" ::"r"(bar) : "memory");
}
__device__ __forceinline__ void flag_signal(uint32_t* flag) {
  asm volatile("red.release.gpu.global.add.u32 [%0], 1;" ::"l"(flag) : "memory");
}
__device__ __forceinline__ void st_b128(uint4* p, uint32_t a, uint32_t b, uint32_t c, uint32_t d) {
  asm volatile("{\n.reg .b128 t;\n.reg .b64 lo, hi;\nmov.b64 lo, {%1,%2};\nmov.b64 hi, {%3,%4};\nmov.b128 t, {lo, hi};\n"
               "st.relaxed.gpu.global.b128 [%0], t;\n}\n" ::"l"(p), "r"(a), "r"(b), "r"(c), "r"(d) : "memory");
}
__device__ __forceinline__ uint4 ld_b128(const uint4* p) {
  uint4 v;
  asm volatile("{\n.reg .b128 t;\n.reg .b64 lo, hi;\nld.relaxed.gpu.global.b128 t, [%4];\nmov.b128 {lo, hi}, t;\n"
               "mov.b64 {%0,%1}, lo;\nmov.b64 {%2,%3}, hi;\n}\n" : "=r"(v.x), "=r"(v.y), "=r"(v.z), "=r"(v.w) : "l"(p) : "memory");
  return v;
}
__device__ __forceinline__ uint32_t ld_epoch(Scratch* sc) {
  uint32_t v;
  asm volatile("ld.relaxed.gpu.global.u32 %0, [%1];" : "=r"(v) : "l"(sc->epoch) : "memory");
  return v + 1;
}
__device__ __forceinline__ void flag_wait(uint32_t* flag, uint32_t target) {
  asm volatile("{\n.reg .pred p;\n.reg .u32 c, v;\nmov.u32 c, 0;\n"
               "LAB_WAIT:\nld.relaxed.gpu.global.u32 v, [%0];\nsub.u32 v, v, %1;\nsetp.ge.s32 p, v, 0;\n@p bra LAB_DONE;\n"
               "add.u32 c, c, 1;\nsetp.lt.u32 p, c, 4000000;\n@p bra LAB_WAIT;\ntrap;\nLAB_DONE:\n}\n"
               ::"l"(flag), "r"(target) : "memory");
}
__device__ __forceinline__ void send_word(uint2* p, uint32_t v, uint32_t tag) {
  asm volatile("{\n.reg .b64 t;\nmov.b64 t, {%1, %2};\nst.relaxed.gpu.global.b64 [%0], t;\n}\n" ::"l"(p), "r"(v), "r"(tag) : "memory");
}
__device__ __forceinline__ uint32_t await_word(const uint2* p, uint32_t tag) {
  uint32_t v;
  asm volatile("{\n.reg .pred p;\n.reg .u32 c, g;\n.reg .b64 t;\nmov.u32 c, 0;\n"
               "LAB_WAIT:\nld.relaxed.gpu.global.b64 t, [%1];\nmov.b64 {%0, g}, t;\nsetp.eq.u32 p, g, %2;\n@p bra LAB_DONE;\n"
               "add.u32 c, c, 1;\nsetp.lt.u32 p, c, 4000000;\n@p bra LAB_WAIT;\ntrap;\nLAB_DONE:\n}\n"
               : "=r"(v) : "l"(p), "r"(tag) : "memory");
  return v;
}
__device__ __forceinline__ uint32_t global_ns() {
  uint32_t v;
  asm volatile("mov.u32 %0, %%globaltimer_lo;" : "=r"(v));
  return v;
}
__device__ __forceinline__ int fresh_tid() {
  int v;
  asm volatile("mov.u32 %0, %%tid.x;" : "=r"(v));
  return v;
}
constexpr uint32_t kPoison = 0xFFFFFFFFu;
__device__ __forceinline__ bool elect_one() {
  uint32_t p;
  asm volatile("{\n.reg .pred P;\nelect.sync _|P, 0xffffffff;\nselp.u32 %0, 1, 0, P;\n}\n" : "=r"(p));
  return p != 0;
}
__device__ __forceinline__ void fence_async() { asm volatile("fence.acquire.gpu;\nfence.proxy.async.global;" ::: "memory"); }
__device__ __forceinline__ void fence_async_smem() { asm volatile("fence.proxy.async.shared::cta;" ::: "memory"); }
__device__ __forceinline__ void nb_sync(int id, int n) { asm volatile("bar.sync %0, %1;" ::"r"(id), "r"(n) : "memory"); }
__device__ __forceinline__ void nb_arrive(int id, int n) { asm volatile("bar.arrive %0, %1;" ::"r"(id), "r"(n) : "memory"); }

__device__ __forceinline__ void tma2d(uint32_t dst, const CUtensorMap* m, int c0, int c1, uint32_t bar) {
  asm volatile("cp.async.bulk.tensor.2d.shared::cluster.global.mbarrier::complete_tx::bytes [%0], [%1, {%3, %4}], [%2];"
               ::"r"(dst), "l"(m), "r"(bar), "r"(c0), "r"(c1) : "memory");
}
__device__ __forceinline__ void tma2d_mc(uint32_t dst, const CUtensorMap* m, int c0, int c1, uint32_t bar) {
  asm volatile("cp.async.bulk.tensor.2d.shared::cluster.global.mbarrier::complete_tx::bytes.multicast::cluster"
               " [%0], [%1, {%3, %4}], [%2], %5;"
               ::"r"(dst), "l"(m), "r"(bar), "r"(c0), "r"(c1), "h"((uint16_t)3) : "memory");
}
__device__ __forceinline__ void tma3d(uint32_t dst, const CUtensorMap* m, int c0, int c1, int c2, uint32_t bar) {
  asm volatile("cp.async.bulk.tensor.3d.shared::cluster.global.mbarrier::complete_tx::bytes [%0], [%1, {%3, %4, %5}], [%2];"
               ::"r"(dst), "l"(m), "r"(bar), "r"(c0), "r"(c1), "r"(c2) : "memory");
}
__device__ __forceinline__ void tma_store2d(const CUtensorMap* m, uint32_t src, int c0, int c1) {
  asm volatile("cp.async.bulk.tensor.2d.global.shared::cta.bulk_group [%0, {%2, %3}], [%1];"
               ::"l"(m), "r"(src), "r"(c0), "r"(c1) : "memory");
}
__device__ __forceinline__ void tma_store3d(const CUtensorMap* m, uint32_t src, int c0, int c1, int c2) {
  asm volatile("cp.async.bulk.tensor.3d.global.shared::cta.bulk_group [%0, {%2, %3, %4}], [%1];"
               ::"l"(m), "r"(src), "r"(c0), "r"(c1), "r"(c2) : "memory");
}
__device__ __forceinline__ void tma_prefetch2d(const CUtensorMap* m, int c0, int c1) {
  asm volatile("cp.async.bulk.prefetch.tensor.2d.L2.global [%0, {%1, %2}];" ::"l"(m), "r"(c0), "r"(c1) : "memory");
}
__device__ __forceinline__ void prefetch_map(const CUtensorMap* m) { asm volatile("prefetch.tensormap [%0];" ::"l"(m) : "memory"); }
__device__ __forceinline__ void bulk_commit() { asm volatile("cp.async.bulk.commit_group;" ::: "memory"); }
__device__ __forceinline__ void bulk_wait_all() { asm volatile("cp.async.bulk.wait_group 0;" ::: "memory"); }
__device__ __forceinline__ void bulk_wait_read() { asm volatile("cp.async.bulk.wait_group.read 0;" ::: "memory"); }
__device__ __forceinline__ void prefetch_l2(const void* p) { asm volatile("prefetch.global.L2 [%0];" ::"l"(p)); }
__device__ __forceinline__ void cluster_arrive() { asm volatile("barrier.cluster.arrive.relaxed.aligned;" ::: "memory"); }
__device__ __forceinline__ void cluster_wait() { asm volatile("barrier.cluster.wait.aligned;" ::: "memory"); }

__device__ __forceinline__ void wg_fence() { asm volatile("wgmma.fence.sync.aligned;" ::: "memory"); }
__device__ __forceinline__ void wg_commit() { asm volatile("wgmma.commit_group.sync.aligned;" ::: "memory"); }
template <int N> __device__ __forceinline__ void wg_wait() { asm volatile("wgmma.wait_group.sync.aligned %0;" ::"n"(N) : "memory"); }
__device__ __forceinline__ uint32_t desc_lo(uint32_t addr, uint32_t lbo) { return ((addr & 0x3FFFF) >> 4) | ((lbo >> 4) << 16); }
__device__ __forceinline__ uint64_t desc(uint32_t lo) { return (uint64_t)lo | (0x40000040ull << 32); }
__device__ __forceinline__ uint64_t desc_kept(uint32_t lo, uint32_t sb) { return (uint64_t)lo | (uint64_t)(0x40000040u | sb >> 31) << 32; }
constexpr int kToB = (16384 >> 4) + ((8192 - 16) >> 4 << 16);

__device__ __forceinline__ void wgmma_n128(float (&d)[96], uint64_t da, uint64_t db, int add = 1) {
  asm volatile(
      "{\n.reg .pred p;\nsetp.ne.b32 p, %66, 0;\n"
      "wgmma.mma_async.sync.aligned.m64n128k16.f32.bf16.bf16 {"
      "%0, %1, %2, %3, %4, %5, %6, %7, %8, %9, %10, %11, %12, %13, %14, %15, "
      "%16, %17, %18, %19, %20, %21, %22, %23, %24, %25, %26, %27, %28, %29, %30, %31, "
      "%32, %33, %34, %35, %36, %37, %38, %39, %40, %41, %42, %43, %44, %45, %46, %47, "
      "%48, %49, %50, %51, %52, %53, %54, %55, %56, %57, %58, %59, %60, %61, %62, %63}, "
      "%64, %65, p, 1, 1, 0, 1;\n}\n"
      :
        "+f"(d[0]), "+f"(d[1]), "+f"(d[2]), "+f"(d[3]), "+f"(d[4]), "+f"(d[5]), "+f"(d[6]), "+f"(d[7]),
        "+f"(d[8]), "+f"(d[9]), "+f"(d[10]), "+f"(d[11]), "+f"(d[12]), "+f"(d[13]), "+f"(d[14]), "+f"(d[15]),
        "+f"(d[16]), "+f"(d[17]), "+f"(d[18]), "+f"(d[19]), "+f"(d[20]), "+f"(d[21]), "+f"(d[22]), "+f"(d[23]),
        "+f"(d[24]), "+f"(d[25]), "+f"(d[26]), "+f"(d[27]), "+f"(d[28]), "+f"(d[29]), "+f"(d[30]), "+f"(d[31]),
        "+f"(d[32]), "+f"(d[33]), "+f"(d[34]), "+f"(d[35]), "+f"(d[36]), "+f"(d[37]), "+f"(d[38]), "+f"(d[39]),
        "+f"(d[40]), "+f"(d[41]), "+f"(d[42]), "+f"(d[43]), "+f"(d[44]), "+f"(d[45]), "+f"(d[46]), "+f"(d[47]),
        "+f"(d[48]), "+f"(d[49]), "+f"(d[50]), "+f"(d[51]), "+f"(d[52]), "+f"(d[53]), "+f"(d[54]), "+f"(d[55]),
        "+f"(d[56]), "+f"(d[57]), "+f"(d[58]), "+f"(d[59]), "+f"(d[60]), "+f"(d[61]), "+f"(d[62]), "+f"(d[63])
      : "l"(da), "l"(db), "r"(add));
}

__device__ __forceinline__ void wgmma_n192(float (&d)[96], uint64_t da, uint64_t db, int add = 1) {
  asm volatile(
      "{\n.reg .pred p;\nsetp.ne.b32 p, %98, 0;\n"
      "wgmma.mma_async.sync.aligned.m64n192k16.f32.bf16.bf16 {"
      "%0, %1, %2, %3, %4, %5, %6, %7, %8, %9, %10, %11, %12, %13, %14, %15, "
      "%16, %17, %18, %19, %20, %21, %22, %23, %24, %25, %26, %27, %28, %29, %30, %31, "
      "%32, %33, %34, %35, %36, %37, %38, %39, %40, %41, %42, %43, %44, %45, %46, %47, "
      "%48, %49, %50, %51, %52, %53, %54, %55, %56, %57, %58, %59, %60, %61, %62, %63, "
      "%64, %65, %66, %67, %68, %69, %70, %71, %72, %73, %74, %75, %76, %77, %78, %79, "
      "%80, %81, %82, %83, %84, %85, %86, %87, %88, %89, %90, %91, %92, %93, %94, %95}, "
      "%96, %97, p, 1, 1, 0, 1;\n}\n"
      :
        "+f"(d[0]), "+f"(d[1]), "+f"(d[2]), "+f"(d[3]), "+f"(d[4]), "+f"(d[5]), "+f"(d[6]), "+f"(d[7]),
        "+f"(d[8]), "+f"(d[9]), "+f"(d[10]), "+f"(d[11]), "+f"(d[12]), "+f"(d[13]), "+f"(d[14]), "+f"(d[15]),
        "+f"(d[16]), "+f"(d[17]), "+f"(d[18]), "+f"(d[19]), "+f"(d[20]), "+f"(d[21]), "+f"(d[22]), "+f"(d[23]),
        "+f"(d[24]), "+f"(d[25]), "+f"(d[26]), "+f"(d[27]), "+f"(d[28]), "+f"(d[29]), "+f"(d[30]), "+f"(d[31]),
        "+f"(d[32]), "+f"(d[33]), "+f"(d[34]), "+f"(d[35]), "+f"(d[36]), "+f"(d[37]), "+f"(d[38]), "+f"(d[39]),
        "+f"(d[40]), "+f"(d[41]), "+f"(d[42]), "+f"(d[43]), "+f"(d[44]), "+f"(d[45]), "+f"(d[46]), "+f"(d[47]),
        "+f"(d[48]), "+f"(d[49]), "+f"(d[50]), "+f"(d[51]), "+f"(d[52]), "+f"(d[53]), "+f"(d[54]), "+f"(d[55]),
        "+f"(d[56]), "+f"(d[57]), "+f"(d[58]), "+f"(d[59]), "+f"(d[60]), "+f"(d[61]), "+f"(d[62]), "+f"(d[63]),
        "+f"(d[64]), "+f"(d[65]), "+f"(d[66]), "+f"(d[67]), "+f"(d[68]), "+f"(d[69]), "+f"(d[70]), "+f"(d[71]),
        "+f"(d[72]), "+f"(d[73]), "+f"(d[74]), "+f"(d[75]), "+f"(d[76]), "+f"(d[77]), "+f"(d[78]), "+f"(d[79]),
        "+f"(d[80]), "+f"(d[81]), "+f"(d[82]), "+f"(d[83]), "+f"(d[84]), "+f"(d[85]), "+f"(d[86]), "+f"(d[87]),
        "+f"(d[88]), "+f"(d[89]), "+f"(d[90]), "+f"(d[91]), "+f"(d[92]), "+f"(d[93]), "+f"(d[94]), "+f"(d[95])
      : "l"(da), "l"(db), "r"(add));
}

__device__ __forceinline__ void wgmma_n192_any(float (&d)[96], uint64_t da, uint64_t db) {
  asm volatile(
      "wgmma.mma_async.sync.aligned.m64n192k16.f32.bf16.bf16 {"
      "%0, %1, %2, %3, %4, %5, %6, %7, %8, %9, %10, %11, %12, %13, %14, %15, "
      "%16, %17, %18, %19, %20, %21, %22, %23, %24, %25, %26, %27, %28, %29, %30, %31, "
      "%32, %33, %34, %35, %36, %37, %38, %39, %40, %41, %42, %43, %44, %45, %46, %47, "
      "%48, %49, %50, %51, %52, %53, %54, %55, %56, %57, %58, %59, %60, %61, %62, %63, "
      "%64, %65, %66, %67, %68, %69, %70, %71, %72, %73, %74, %75, %76, %77, %78, %79, "
      "%80, %81, %82, %83, %84, %85, %86, %87, %88, %89, %90, %91, %92, %93, %94, %95}, "
      "%96, %97, 0, 1, 1, 0, 1;\n"
      :
        "=f"(d[0]), "=f"(d[1]), "=f"(d[2]), "=f"(d[3]), "=f"(d[4]), "=f"(d[5]), "=f"(d[6]), "=f"(d[7]),
        "=f"(d[8]), "=f"(d[9]), "=f"(d[10]), "=f"(d[11]), "=f"(d[12]), "=f"(d[13]), "=f"(d[14]), "=f"(d[15]),
        "=f"(d[16]), "=f"(d[17]), "=f"(d[18]), "=f"(d[19]), "=f"(d[20]), "=f"(d[21]), "=f"(d[22]), "=f"(d[23]),
        "=f"(d[24]), "=f"(d[25]), "=f"(d[26]), "=f"(d[27]), "=f"(d[28]), "=f"(d[29]), "=f"(d[30]), "=f"(d[31]),
        "=f"(d[32]), "=f"(d[33]), "=f"(d[34]), "=f"(d[35]), "=f"(d[36]), "=f"(d[37]), "=f"(d[38]), "=f"(d[39]),
        "=f"(d[40]), "=f"(d[41]), "=f"(d[42]), "=f"(d[43]), "=f"(d[44]), "=f"(d[45]), "=f"(d[46]), "=f"(d[47]),
        "=f"(d[48]), "=f"(d[49]), "=f"(d[50]), "=f"(d[51]), "=f"(d[52]), "=f"(d[53]), "=f"(d[54]), "=f"(d[55]),
        "=f"(d[56]), "=f"(d[57]), "=f"(d[58]), "=f"(d[59]), "=f"(d[60]), "=f"(d[61]), "=f"(d[62]), "=f"(d[63]),
        "=f"(d[64]), "=f"(d[65]), "=f"(d[66]), "=f"(d[67]), "=f"(d[68]), "=f"(d[69]), "=f"(d[70]), "=f"(d[71]),
        "=f"(d[72]), "=f"(d[73]), "=f"(d[74]), "=f"(d[75]), "=f"(d[76]), "=f"(d[77]), "=f"(d[78]), "=f"(d[79]),
        "=f"(d[80]), "=f"(d[81]), "=f"(d[82]), "=f"(d[83]), "=f"(d[84]), "=f"(d[85]), "=f"(d[86]), "=f"(d[87]),
        "=f"(d[88]), "=f"(d[89]), "=f"(d[90]), "=f"(d[91]), "=f"(d[92]), "=f"(d[93]), "=f"(d[94]), "=f"(d[95])
      : "l"(da), "l"(db));
}

__device__ __forceinline__ void wgmma_n192_rs(float (&d)[96], uint32_t a0, uint32_t a1, uint32_t a23, uint64_t db) {
  asm volatile(
      "wgmma.mma_async.sync.aligned.m64n192k16.f32.bf16.bf16 {"
      "%0, %1, %2, %3, %4, %5, %6, %7, %8, %9, %10, %11, %12, %13, %14, %15, "
      "%16, %17, %18, %19, %20, %21, %22, %23, %24, %25, %26, %27, %28, %29, %30, %31, "
      "%32, %33, %34, %35, %36, %37, %38, %39, %40, %41, %42, %43, %44, %45, %46, %47, "
      "%48, %49, %50, %51, %52, %53, %54, %55, %56, %57, %58, %59, %60, %61, %62, %63, "
      "%64, %65, %66, %67, %68, %69, %70, %71, %72, %73, %74, %75, %76, %77, %78, %79, "
      "%80, %81, %82, %83, %84, %85, %86, %87, %88, %89, %90, %91, %92, %93, %94, %95}, "
      "{%96, %97, %98, %98}, %99, 1, 1, 1, 1;\n"
      :
        "+f"(d[0]), "+f"(d[1]), "+f"(d[2]), "+f"(d[3]), "+f"(d[4]), "+f"(d[5]), "+f"(d[6]), "+f"(d[7]),
        "+f"(d[8]), "+f"(d[9]), "+f"(d[10]), "+f"(d[11]), "+f"(d[12]), "+f"(d[13]), "+f"(d[14]), "+f"(d[15]),
        "+f"(d[16]), "+f"(d[17]), "+f"(d[18]), "+f"(d[19]), "+f"(d[20]), "+f"(d[21]), "+f"(d[22]), "+f"(d[23]),
        "+f"(d[24]), "+f"(d[25]), "+f"(d[26]), "+f"(d[27]), "+f"(d[28]), "+f"(d[29]), "+f"(d[30]), "+f"(d[31]),
        "+f"(d[32]), "+f"(d[33]), "+f"(d[34]), "+f"(d[35]), "+f"(d[36]), "+f"(d[37]), "+f"(d[38]), "+f"(d[39]),
        "+f"(d[40]), "+f"(d[41]), "+f"(d[42]), "+f"(d[43]), "+f"(d[44]), "+f"(d[45]), "+f"(d[46]), "+f"(d[47]),
        "+f"(d[48]), "+f"(d[49]), "+f"(d[50]), "+f"(d[51]), "+f"(d[52]), "+f"(d[53]), "+f"(d[54]), "+f"(d[55]),
        "+f"(d[56]), "+f"(d[57]), "+f"(d[58]), "+f"(d[59]), "+f"(d[60]), "+f"(d[61]), "+f"(d[62]), "+f"(d[63]),
        "+f"(d[64]), "+f"(d[65]), "+f"(d[66]), "+f"(d[67]), "+f"(d[68]), "+f"(d[69]), "+f"(d[70]), "+f"(d[71]),
        "+f"(d[72]), "+f"(d[73]), "+f"(d[74]), "+f"(d[75]), "+f"(d[76]), "+f"(d[77]), "+f"(d[78]), "+f"(d[79]),
        "+f"(d[80]), "+f"(d[81]), "+f"(d[82]), "+f"(d[83]), "+f"(d[84]), "+f"(d[85]), "+f"(d[86]), "+f"(d[87]),
        "+f"(d[88]), "+f"(d[89]), "+f"(d[90]), "+f"(d[91]), "+f"(d[92]), "+f"(d[93]), "+f"(d[94]), "+f"(d[95])
      : "r"(a0), "r"(a1), "r"(a23), "l"(db));
}

__device__ __forceinline__ uint32_t pack_bf16(float lo, float hi) {
  uint32_t r;
  asm("cvt.rn.bf16x2.f32 %0, %1, %2;" : "=r"(r) : "f"(hi), "f"(lo));
  return r;
}
__device__ __forceinline__ float bf_lo(uint32_t v) { return __uint_as_float(v << 16); }
__device__ __forceinline__ float bf_hi(uint32_t v) { return __uint_as_float(v & 0xFFFF0000u); }
__device__ __forceinline__ float ex2(float x) { float r; asm("ex2.approx.ftz.f32 %0, %1;" : "=f"(r) : "f"(x)); return r; }
__device__ __forceinline__ float rcp(float x) { float r; asm("rcp.approx.ftz.f32 %0, %1;" : "=f"(r) : "f"(x)); return r; }
__device__ __forceinline__ uint32_t movm(uint32_t a) {
  uint32_t d;
  asm volatile("movmatrix.sync.aligned.m8n8.trans.b16 %0, %1;" : "=r"(d) : "r"(a));
  return d;
}
__device__ __forceinline__ void mma16816(float (&c)[4], uint32_t a0, uint32_t a1, uint32_t a2, uint32_t a3, uint32_t b0, uint32_t b1) {
  asm volatile("mma.sync.aligned.m16n8k16.row.col.f32.bf16.bf16.f32 {%0,%1,%2,%3}, {%4,%5,%6,%7}, {%8,%9}, {%0,%1,%2,%3};"
               : "+f"(c[0]), "+f"(c[1]), "+f"(c[2]), "+f"(c[3]) : "r"(a0), "r"(a1), "r"(a2), "r"(a3), "r"(b0), "r"(b1));
}
__device__ __forceinline__ void mma1688(float (&c)[4], uint32_t a0, uint32_t a1, uint32_t b0) {
  asm volatile("mma.sync.aligned.m16n8k8.row.col.f32.bf16.bf16.f32 {%0,%1,%2,%3}, {%4,%5}, {%6}, {%0,%1,%2,%3};"
               : "+f"(c[0]), "+f"(c[1]), "+f"(c[2]), "+f"(c[3]) : "r"(a0), "r"(a1), "r"(b0));
}
__device__ __forceinline__ void stsm4(uint32_t addr, uint32_t a, uint32_t b, uint32_t c, uint32_t d) {
  asm volatile("stmatrix.sync.aligned.m8n8.x4.shared.b16 [%0], {%1,%2,%3,%4};" ::"r"(addr), "r"(a), "r"(b), "r"(c), "r"(d) : "memory");
}
__device__ __forceinline__ void stsm4_t(uint32_t addr, uint32_t a, uint32_t b, uint32_t c, uint32_t d) {
  asm volatile("stmatrix.sync.aligned.m8n8.x4.trans.shared.b16 [%0], {%1,%2,%3,%4};" ::"r"(addr), "r"(a), "r"(b), "r"(c), "r"(d) : "memory");
}
__device__ __forceinline__ void ldsm4(uint32_t addr, uint32_t (&v)[4]) {
  asm volatile("ldmatrix.sync.aligned.m8n8.x4.shared.b16 {%0,%1,%2,%3}, [%4];"
               : "=r"(v[0]), "=r"(v[1]), "=r"(v[2]), "=r"(v[3]) : "r"(addr) : "memory");
}
__device__ __forceinline__ void sts128(uint32_t addr, uint4 v) {
  asm volatile("st.shared.v4.b32 [%0], {%1,%2,%3,%4};" ::"r"(addr), "r"(v.x), "r"(v.y), "r"(v.z), "r"(v.w) : "memory");
}
__device__ __forceinline__ uint4 lds128(uint32_t addr) {
  uint4 v;
  asm volatile("ld.shared.v4.b32 {%0,%1,%2,%3}, [%4];" : "=r"(v.x), "=r"(v.y), "=r"(v.z), "=r"(v.w) : "r"(addr) : "memory");
  return v;
}
__device__ __forceinline__ void sts64(uint32_t addr, uint32_t a, uint32_t b) {
  asm volatile("st.shared.v2.b32 [%0], {%1,%2};" ::"r"(addr), "r"(a), "r"(b) : "memory");
}
__device__ __forceinline__ void sts32(uint32_t addr, uint32_t a) { asm volatile("st.shared.b32 [%0], %1;" ::"r"(addr), "r"(a) : "memory"); }
__device__ __forceinline__ uint32_t lds32(uint32_t addr) {
  uint32_t v;
  asm volatile("ld.shared.b32 %0, [%1];" : "=r"(v) : "r"(addr) : "memory");
  return v;
}
__device__ __forceinline__ float2 lds64f_const(uint32_t addr) {
  float2 v;
  asm("ld.shared.v2.f32 {%0,%1}, [%2];" : "=f"(v.x), "=f"(v.y) : "r"(addr));
  return v;
}
template <int N, bool PAIR>
__device__ __forceinline__ void load_tagged(uint3 (&out)[N], const uint4* src, int stride, uint32_t tag, const uint4* last = nullptr) {
  uint32_t bad;
  int spins = 0;
#pragma unroll 1
  do {
    if (++spins > 2000000) __trap();
    bad = 0;
#pragma unroll
    for (int i = 0; i < N; i++) {
      const uint4 v = ld_b128(N == 5 && i == 4 ? last : src + i * stride);
      out[i] = make_uint3(v.x, v.y, v.z);
      bad |= (v.w ^ tag) | (PAIR ? v.z ^ tag : 0);
    }
    if (N == 4) bad = __any_sync(~0u, bad != 0);
    if (bad) __nanosleep(kBackoffNs);
  } while (bad);
}
__device__ __forceinline__ void sts64f(uint32_t addr, float2 v) { sts64(addr, __float_as_uint(v.x), __float_as_uint(v.y)); }
__device__ __forceinline__ float bf_rest(float v) { return v - __uint_as_float(__float_as_uint(v) & 0xFFFF0000u); }
__device__ __forceinline__ uint32_t bf_upper(float lo, float hi) { return __byte_perm(__float_as_uint(lo), __float_as_uint(hi), 0x7632); }
__device__ __forceinline__ float low_peak(uint4 v) {
  asm("max.xorsign.abs.bf16x2 %0, %0, %1;" : "+r"(v.x) : "r"(v.y));
  asm("max.xorsign.abs.bf16x2 %0, %0, %1;" : "+r"(v.z) : "r"(v.w));
  asm("max.xorsign.abs.bf16x2 %0, %0, %1;" : "+r"(v.x) : "r"(v.z));
  asm("max.xorsign.abs.bf16x2 %0, %0, %1;" : "+r"(v.x) : "r"(v.x << 16));
  return __uint_as_float(__reduce_min_sync(~0u, v.x & 0x7FFF0000u));
}
__device__ __forceinline__ float bias_at(float v) { return __uint_as_float((__float_as_uint(fminf(v, 1e37f)) & 0x7F800000u) | 0x00400000u); }
struct RowConst {
  float nmean, k0, k1, half;
};
__device__ __forceinline__ float gate_scale(float t, const RowConst& k) {
  float th;
  asm("tanh.approx.f32 %0, %1;" : "=f"(th) : "f"(t * fmaf(t * t, k.k1, k.k0)));
  return fmaf(th, k.half, k.half);
}

template <int N>
__device__ __forceinline__ void mma_k16(float (&acc)[2][96], uint32_t a, uint32_t b, int kk, int add = 1) {
#pragma unroll
  for (int m = 0; m < 2; m++) {
    const uint64_t da = desc(a) + (m * 512 + kk * 2), db = desc(b) + kk * 128;
    if (N == 128) wgmma_n128(acc[m], da, db); else wgmma_n192(acc[m], da, db, add);
  }
}

__device__ __forceinline__ void stage_quarter(const float* acc, uint32_t frag, uint32_t frag_x, int b, const uint4* add = nullptr) {
#pragma unroll
  for (int j = 0; j < 4; j++) {
    const float* v = acc + 8 * j;
    uint32_t h[4] = {pack_bf16(v[0], v[1]), pack_bf16(v[2], v[3]), pack_bf16(v[4], v[5]), pack_bf16(v[6], v[7])};
    if (add) {
      const uint32_t a[4] = {add[j].x, add[j].y, add[j].z, add[j].w};
#pragma unroll
      for (int e = 0; e < 4; e++) asm("add.rn.bf16x2 %0, %0, %1;" : "+r"(h[e]) : "r"(a[e]));
    }
    stsm4(frag + b * 8192 + ((frag_x ^ (j * 2)) << 4), h[0], h[1], h[2], h[3]);
  }
}

inline int g1_block(int j, int c) { return j < 16 ? j : ((j + 12) & 15) ^ (c == 5 && j >= 28 ? 2 : 0); }
inline int g2_block(int j, int c) { return j < 8 ? j : j == 8 ? 8 + c : j - (j - 9 < c); }
inline int g3_tile(int j) { return j < 4 ? j >> 1 : j < 18 ? 0 : j >> 4; }
inline int g3_block(int j, int c) {
  const int i = j < 32 ? (j < 16 ? 0xDCBA976543218080ull : 0x7654321BA9FEDCFEull) >> 4 * (j & 15) : j + (~j >> 2 & 4), o = i & 7;
  return 2 * (j < 32 && (o == c || o == 0) ? c - o : o) + (i >> 3 & 1);
}
__device__ __forceinline__ bool g3_is_up(int tile, int a) { return a == 1 || (a == 2 && tile >= 2); }
__device__ __forceinline__ int g3_atom(int tile, int a, int c) { return c * 7 + (tile & 1) * 3 + (a == 2 ? 1 : tile == 4 ? 6 : tile & 2); }
inline int g4_block(int i) {
  const int n = i * 43 >> 7, j = i - 3 * n, m = j ? n : n + (16 - kFirstShared / 3);
  return i < 48 ? 7 * (m & 7) + 3 * (m >> 3 & 1) + j : 7 * i - 330;
}

constexpr int kInPlace = 16, kInO = 64, kMark = 128;

template <int N, int TAIL>
__device__ __forceinline__ void mainloop(Scratch* sc, float (&acc)[2][96], uint32_t sb, int ph, int j0, int nsteps, int pause_at, bool last,
                                         bool hand_over, bool local, int wg, int own = -1, const CUtensorMap* out = nullptr, int out_col = 0,
                                         int out_row = 0, int warp = 0, __nv_bfloat16* outp = nullptr) {
  constexpr int NSLOT = N == 128 ? 5 : 4, SLOT = N == 128 ? 32768 : 40960;
  const int lane = fresh_tid() & 31;
  const uint32_t full = sb + kBars + 8 * ring_base(ph);
  const uint32_t empty = map_cta(full + 8 * (NSLOT + (ph == 3)), lane & 1);
  const uint32_t ring = desc_lo(sb + kRing, 16);
  int bi = j0 % NSLOT, par = (j0 / NSLOT) & 1;
  const int release_end = lane < (N == 192 && !hand_over ? 4 : 2) ? (last ? nsteps - 1 - NSLOT : nsteps) : 0;
  uint32_t rel = empty;
  const uint32_t special = ph == 0 && wg == 0 ? 3 : pause_at < 0 ? 1 : 1 | 2 << pause_at;
  int i = 0;
#pragma unroll 1
  for (;;) {
    const int end = TAIL <= 0 ? nsteps : !own ? nsteps - TAIL - 1 : i ? i + 2 : kFirstShared;
#pragma unroll 1
    do {
      uint32_t a = ring + bi * (SLOT >> 4), b = a + kToB;
      if (TAIL > 0 ? i == 0 : special >> i & 1) {
        if (i == 0) nb_sync(kNbOrder + wg, ph == 0 && wg == 0 ? 160 : 256);
        else if (ph == 0 && wg == 0) cluster_wait();
        else if (ph < 2) nb_sync(kNbWin + 1, 256);
      }
      if (N == 192 && local) {
        a = ring + ((kStage + i * 16384) >> 4);
        b = ring + bi * (32768 >> 4) + desc_lo(32768, 8192) - desc_lo(0, 16);
      }
      if (ph == 0 && i >> 1 == own) a = ring + ((kOwn + (i & 1) * 16384) >> 4);
      if (ph == 1 && i == 8) a = ring + ((kStage + 32768) >> 4);
      mbar_wait(full + 8 * bi, par);
      if (N == 192 && local) mbar_wait(sb + kBars + 8 * (kHalfBar + i), 0);
      const bool release = (uint32_t)(i - 1) < (uint32_t)release_end;
      wg_fence();
      mma_k16<N>(acc, a, b, 0, ph == 0 ? i | wg : 1);
      mma_k16<N>(acc, a, b, 1);
      wg_commit();
      wg_wait<1>();
      mbar_arrive_cluster_if(rel, release);
      wg_fence();
      mma_k16<N>(acc, a, b, 2);
      mma_k16<N>(acc, a, b, 3);
      wg_commit();
      rel = empty + 8 * bi;
      if (++bi == NSLOT + (TAIL > 0 && i >= kWide - 16)) { bi = 0; par ^= 1; }
      if (ph < 2 && i == pause_at) nb_arrive(kNbWin, 256);
    } while (++i < end);
    if (TAIL <= 0 || own-- == 0) break;
    const uint32_t a = ring + bi * (SLOT >> 4);
    mbar_wait(full + 8 * bi, par);
    wg_fence();
#pragma unroll
    for (int k = 0; k < 4; k++) wgmma_n128(acc[1], desc(a) + (512 + k * 2), desc(a + kToB) + k * 128);
    wg_commit();
    wg_wait<1>();
    mbar_arrive_cluster_if(rel, lane < 2);
    rel = empty + 8 * bi;
    if (++bi == NSLOT + 1) { bi = 0; par ^= 1; }
    i++;
  }
  if (TAIL < 0) return;
  if (TAIL > 0) {
    uint32_t at[TAIL + 2];
    bi = par = 0;
    const int t = fresh_tid() & 127;
    uint32_t frag = sb + kStage + ((t >> 5) * 16 + (t & 15)) * 128, frag_x = ((t >> 4) & 1) ^ (t & 7);
    const uint32_t back = sb + kStage + (t >> 5) * 2048 + ((t >> 3) & 3) * 128, back_x = ((t ^ (t >> 3 & 3)) & 7) << 4;
    outp = plus(outp, (2 * (out_row + (t >> 5) * 16 + ((t >> 3) & 3)) + (blockIdx.x & 1)) * kD + out_col + (t & 7) * 8);
    auto rows = [&](int m, int i0, int i1) {
      wg_fence();
#pragma unroll
      for (int i = 4 * i0; i < 4 * i1; i++)
        wgmma_n128(acc[m], desc_kept(ring, sb) + (at[i >> 2] + m * 512 + (i & 3) * 2), desc_kept(ring, sb) + (at[i >> 2] + kToB + (i & 3) * 128));
      wg_commit();
    };
    uint4 part[8];
#pragma unroll
    for (int i = 0; i <= TAIL; i++) {
      at[i] = bi * (SLOT >> 4);
      mbar_wait(full + 8 * bi, par);
      if (++bi == NSLOT) { bi = 0; par ^= 1; }
      rows(0, i, i + 1);
      if (i == kPartAt) nb_sync(kNbPart, 256);
      if (i == kPartAt || i == kPartAt + 1) {
#pragma unroll
        for (int k = 4 * (i - kPartAt); k < 4 * (i - kPartAt + 1); k++) part[k] = lds128(sb + kStage + 32768 + (t >> 5) * 4096 + (t & 31) * 16 + k * 512);
      }
    }
    rows(1, 0, 2);
#pragma unroll
    for (int b = 0; b < 4; b++) {
      if (b == 0) wg_wait<1>();
      if (b == 1) rows(1, 3, 4);
      if (b == 2) wg_wait<0>();
      if (!(b & 1)) {
#pragma unroll
        for (int i = 0; i < 64; i++) asm volatile("" : "+f"(acc[b >> 1][i])::"memory");
        if (t == 0) TSS(b);
      }
      stage_quarter(&acc[b >> 1][32 * (b & 1)], frag, frag_x, b, b < 2 ? &part[4 * b] : nullptr);
      if (b == 3) {
        __syncwarp();
        uint4 v[4];
#pragma unroll
        for (int i = 0; i < 4; i++) v[i] = lds128(back + b * 8192 + i * 512 + ((i & 1) ? back_x ^ 64 : back_x));
#pragma unroll
        for (int i = 0; i < 4; i++) __stcs((uint4*)(outp + ((b >> 1) * 128 + i * 8) * kD + (b & 1) * 64), v[i]);
        if (t == 0) TSS(4 + b);
        continue;
      }
      if (b < 2) rows(1, 2 + 2 * b, 3 + 2 * b);
      fence_async_smem();
      __syncwarp();
      if (elect_one()) tma_store3d(out, sb + kStage + b * 8192 + warp * 2048, out_col + (b & 1) * 64, out_row + (b >> 1) * 64 + warp * 16, blockIdx.x & 1);
      __syncwarp();
      if (t == 0) TSS(4 + b);
    }
    if (elect_one()) {
      bulk_commit();
      bulk_wait_read();
    }
    if (t == 0) TSS(1);
    return;
  }
  if (hand_over) nb_arrive(kNbOrder + (wg ^ 1), 256);
  if (N == 192 && !local) {
    mbar_wait(sb + kBars + 8 * (kAuxBar + wg), j0 < 32);
    if (j0 < 32) mbar_wait(sb + kBars + 8 * kStatBar, 1);
    mbar_wait(sb + kBars + 8 * (kStgBar + wg), ((j0 >> 5) ^ wg ^ 1) & 1);
  }
  wg_wait<0>();
  mbar_arrive_cluster_if(rel, release_end == nsteps);
#pragma unroll
  for (int i = 0; i < N / 2; i++) asm volatile("" : "+f"(acc[0][i]), "+f"(acc[1][i])::"memory");
}

template <int PH>
struct Ring {
  static constexpr int NSLOT = 4 + (PH & 1), SLOT = PH & 1 ? 32768 : 40960;
  uint32_t full, dst0;
  int j = PH == 0 ? 4 : 0, bi = 0, par = PH == 0 ? 0 : 1;
  __device__ __forceinline__ Ring(uint32_t sb, uint32_t ofs) : full(sb + kBars + 8 * (PH * 9 - (PH & 1))), dst0(sb + kRing + ofs) {}
  __device__ __forceinline__ uint32_t bar() const { return full + 8 * bi; }
  __device__ __forceinline__ uint32_t dst() const { return dst0 + bi * SLOT; }
  __device__ __forceinline__ void acquire_first() const {
    const bool first = j < NSLOT;
    mbar_wait(full + (first ? 8 * min(j, 3) - 32 : 8 * (NSLOT + (PH == 3) + bi)), PH == 2 && first ? 0 : par);
  }
  __device__ __forceinline__ void acquire() const { mbar_wait(full + 8 * (NSLOT + (PH == 3) + bi), par); }
  __device__ __forceinline__ void next() {
    j++;
    if (++bi == NSLOT + (PH == 3 && j > kWide)) { bi = 0; par ^= 1; }
  }
};

__device__ __forceinline__ void check_blocks(const Params& p, Scratch* sc, uint32_t sb, int r, int c, bool g3, uint32_t& par) {
  const int lane = fresh_tid() & 31, nslot = g3 ? 4 : 5, slot_bytes = g3 ? 40960 : 32768;
  const uint32_t mine = (lane >> 2) * 132 + (lane & 3) * 32, ring_end = sb + kRing + kStage + mine;
  const uint32_t to_full = 8 * (kLandBar - (g3 ? ring_base(2) : ring_base(1)));
  uint32_t src = sb + kRing + mine + (g3 ? 0 : 4 * 32768);
  int bi = g3 ? 0 : 4, spins = 0;
#pragma unroll 1
  for (int i = g3 ? 2 : 9; i < 16;) {
    const uint32_t land = sb + kBars + 8 * (kLandBar + bi);
    mbar_wait(land, (par >> bi) & 1);
    uint32_t v[16];
#pragma unroll
    for (int k = 0; k < 16; k++) v[k] = lds32(src + k * 1024);
#pragma unroll
    for (int k = 0; k < 5; k++) v[k] = max(max(v[3 * k + 1], v[3 * k + 2]), k ? v[3 * k] : max(v[0], v[15]));
    const bool again = __any_sync(~0u, max(max(max(v[0], v[1]), v[2]), max(v[3], v[4])) == kPoison);
    asm volatile("{\n.reg .pred p;\nsetp.eq.u32 p, %1, 0;\n@p mbarrier.arrive.shared::cta.b64 _, [%0];\n}\n"
                 ::"r"(land - to_full), "r"(lane + again) : "memory");
    par ^= 1u << bi;
    if (again) {
      if (++spins > 100000) __trap();
      if (elect_one()) {
        mbar_expect_tx(land, 16384);
        tma2d(src - mine, g3 ? &p.h : &p.o, ((g3 ? p.g3[c][i + 2] : p.g2[c][i]) & 15) * 64, r * 128, land);
      }
      nb_sync(kNbSelf + 1, 32);
      continue;
    }
    if (lane == 0 && (i == 2 || i == 3 || (!g3 && (i == 9 || i == 12)))) TS(i < 4 ? 88 + 2 * i : i == 9 ? 120 : 122);
    i++;
    if (++bi == nslot) bi = 0;
    src += slot_bytes;
    if (src == ring_end) src -= kStage;
  }
}

__device__ __forceinline__ void colsum_cta(const Params& p, Scratch* sc, uint32_t sb, int warp, int bid) {
  constexpr int kSlots = 4, kSlot = 49152;
  constexpr int kRows = kMost * 16384, kIn = (kCs - kRows) / 8192;
  const int lane = threadIdx.x & 31, c0 = (bid - 128) * 2;
  const uint32_t full = sb + kBars, empty = full + 8 * kSlots;
  const uint32_t event = full + 64, rfull = full + 128, rempty = full + 256;
  if (threadIdx.x == 0) {
#pragma unroll 1
    for (int i = 0; i < 48; i++) mbar_init(full + 8 * i, i & (i < 16 ? 4 : 32) ? 8 : 1);
    asm volatile("fence.mbarrier_init.release.cluster;" ::: "memory");
  }
  __syncthreads();
  const uint32_t ep = ld_epoch(sc);
  if (warp == 8) {
    if (elect_one()) {
#pragma unroll 1
      for (int n = 0; n < 112 + kSlots; n++) {
        const int u = n >> 4, c = c0 + ((n >> 3) & 1), k0 = (n & 7) * 128, slot = n & (kSlots - 1);
        if (n == kQuietAt) flag_wait(sc->flags + kFlPace, ep);
        const uint32_t bar = full + 8 * slot;
        mbar_wait(empty + 8 * slot, ((n / kSlots) & 1) ^ 1);
        if (n == 108) mbar_arrive(event);
        if (u == 7) continue;
        mbar_expect_tx(bar, u == 6 ? 32768 : 49152);
#pragma unroll
        for (int a = 0; a < 3; a++) {
          if (a == 2 && u == 6) break;
          const CUtensorMap* m = u < 2 ? &p.wqkv : g3_is_up(u - 2, a) ? &p.wu : &p.wg;
          const int col = (u < 2 ? a * 16 + u * 8 + c : g3_atom(u - 2, a, c)) * 64;
          tma2d(sb + slot * kSlot + a * 8192, m, col, k0, bar);
          tma2d(sb + slot * kSlot + a * 8192 + 24576, m, col, k0 + 64, bar);
        }
      }
      mbar_wait(event + 8, 0);
      asm volatile("fence.proxy.async.global;" ::: "memory");
      int slot = 0, par = 1, w = 0;
#pragma unroll 1
      for (int job = 0; job < 32; job++) {
        const int k = lds32(sb + kPlan + (job >> 4) * 4) >> (job & 14) * 2 & 15;
        if (job == 16) {
          mbar_wait(rempty + 8 * (slot ? slot - 1 : kIn - 1), par ^ (slot != 0));
          w = 0;
        }
#pragma unroll 1
        for (int i = 0; i < k; i++) {
          const uint32_t bar = rfull + 8 * slot;
          mbar_wait(bar + 128, par);
          mbar_expect_tx(bar, w < kMost ? 24576 : 8192);
          tma2d(sb + kRows + slot * 8192, &p.ost, i * 64, (job & 15) * 128, bar);
          if (w < kMost) {
#pragma unroll
            for (int a = 0; a < 2; a++)
              tma2d(sb + w * 16384 + a * 8192, &p.wd, ((c0 + (job >> 4)) * 2 + a) * 64, w * (7 * 64), bar);
            w++;
          }
          if (++slot == kIn) { slot = 0; par ^= 1; }
        }
      }
    }
  } else if (warp < 8) {
    uint32_t src[3];
#pragma unroll
    for (int j = 0; j < 3; j++) src[j] = sb + ((warp * 3 + j) >> 3) * 8192 + lane * 128 + ((((warp * 3 + j) & 7) ^ (lane & 7)) << 4);
    const uint32_t ones = 0x3F803F80u;
#pragma unroll 1
    for (int s = 0; s < 112; s++) {
      float a[3][2][4] = {};
#pragma unroll 1
      for (;; s++) {
        const int slot = s & (kSlots - 1);
        mbar_wait(full + 8 * slot, (s / kSlots) & 1);
        uint32_t b[3][4][4];
#pragma unroll
        for (int j = 0; j < 3; j++)
#pragma unroll
          for (int k = 0; k < 4; k++)
            asm volatile("ldmatrix.sync.aligned.m8n8.x4.trans.shared.b16 {%0,%1,%2,%3}, [%4];"
                         : "=r"(b[j][k][0]), "=r"(b[j][k][1]), "=r"(b[j][k][2]), "=r"(b[j][k][3])
                         : "r"(src[j] + slot * kSlot + (k >> 1) * 24576 + (k & 1) * 4096) : "memory");
        __syncwarp();
        if (lane == 0) mbar_arrive(empty + 8 * slot);
#pragma unroll
        for (int k = 0; k < 4; k++)
#pragma unroll
          for (int j = 0; j < 3; j++) {
            mma16816(a[j][0], ones, ones, ones, ones, b[j][k][0], b[j][k][1]);
            mma16816(a[j][1], ones, ones, ones, ones, b[j][k][2], b[j][k][3]);
          }
        if ((s & 7) == 7) break;
      }
      {
        if (lane < 12) {
          const int j = lane >> 2;
          const float x = j == 0 ? a[0][0][0] + a[0][1][0] : j == 1 ? a[1][0][0] + a[1][1][0] : a[2][0][0] + a[2][1][0];
          const float y = j == 0 ? a[0][0][1] + a[0][1][1] : j == 1 ? a[1][0][1] + a[1][1][1] : a[2][0][1] + a[2][1][1];
          const float x1 = bf_rest(x), y1 = bf_rest(y);
          const bool split = s < 32;
          st_b128(SC_AT(cs, ((s >> 4) * 8 + c0 + ((s >> 3) & 1)) * 96 + warp * 12 + lane), split ? bf_upper(x, y) : __float_as_uint(x),
                  split ? bf_upper(x1, y1) : __float_as_uint(y), bf_upper(bf_rest(x1), bf_rest(y1)), ep);
        }
        if (threadIdx.x == 0 && (s & 8)) TSK(s >> 4);
      }
    }
    const int wg = warp >> 2;
    mbar_wait(event + 8, 0);
#pragma unroll 1
    for (int job = wg, first = 0; job < 32; job += 2) {
      const int k = __shfl_sync(~0u, lds32(sb + kPlan + (job >> 4) * 4), 0) >> (job & 14) * 2 & 15;
      if (k == 0) continue;
      float acc[96];
#pragma unroll
      for (int i = 0; i < 64; i++) asm volatile("" : "=f"(acc[i]));
      static_assert(kIn == 12, "");
      int slot = first + wg * k, par = slot * 171 >> 11, i = 0;
      slot -= par * kIn;
      first += 2 * k;
      uint32_t done = 0;
      if (job) nb_sync(kNbOrder + wg, 256);
#pragma unroll 1
      do {
        mbar_wait(rfull + 8 * slot, par & 1);
        wg_fence();
#pragma unroll
        for (int kk = 0; kk < 4; kk++)
          wgmma_n128(acc, desc(desc_lo(sb + kRows, 16) + slot * 512) + kk * 2, desc(desc_lo(sb, 8192) + i * 1024) + kk * 128, kk | i);
        wg_commit();
        wg_wait<1>();
        if (lane < 2 && i) mbar_arrive(done);
        done = rempty + 8 * slot;
        if (++slot == kIn) { slot = 0; par++; }
      } while (++i < k);
      nb_arrive(kNbOrder + (wg ^ 1), 256);
      uint4* dst = SC_AT(part, ((job & 15) * 8 + c0 + (job >> 4)) * 1024 + (warp & 3) * 256 + lane);
      wg_wait<0>();
#pragma unroll
      for (int i = 0; i < 64; i++) asm volatile("" : "+f"(acc[i])::"memory");
      if (lane < 2) mbar_arrive(done);
#pragma unroll
      for (int i = 0; i < 8; i++) {
        const float* v = &acc[8 * i];
        asm volatile("st.relaxed.gpu.global.v4.b32 [%0], {%1, %2, %3, %4};"
                     ::"l"(dst + i * 32),
                     "r"(pack_bf16(v[0], v[1])), "r"(pack_bf16(v[2], v[3])), "r"(pack_bf16(v[4], v[5])), "r"(pack_bf16(v[6], v[7])) : "memory");
      }
    }
    if (threadIdx.x == 128) TSK(7);
  } else if (warp == 10) {
    mbar_wait(event, 0);
    flag_wait(sc->flags + kFlHH + (lane & 15) * kFlRow, ep * 8);
    int late = await_word(sc->finish + (uint32_t)((lane & 15) * 8 + c0 + (lane >> 4)), ep);
    __syncwarp();
    late -= __shfl_sync(~0u, late, 0);
    late = max(late, __shfl_xor_sync(~0u, late, 1));
    late = max(min(late - (__reduce_add_sync(~0u, late) >> 5) + kShare * kStepNs, 4096), -4096);
    int k;
#pragma unroll 1
    do {
      k = min(max((late * (8192 / kStepNs) >> 13) + 1, (lane & 14) == 0), kMost);
      late -= kStepNs / 4;
    } while (__reduce_add_sync(~0u, k ? max(2 * k, k + 4) : 0) > kBudget);
    k <<= (lane & 14) * 2;
#pragma unroll
    for (int o = 2; o < 16; o <<= 1) k |= __shfl_xor_sync(~0u, k, o);
    asm volatile("fence.acquire.gpu;" ::: "memory");
    send_word(sc->plan + (uint32_t)(c0 + (lane >> 4)), k, ep);
    sts32(sb + kPlan + (lane >> 4) * 4, k);
    __syncwarp();
    if (lane == 0) mbar_arrive(event + 8);
  }
}

#define PROF_BEGIN
template <bool BY_SM>
__global__ void __cluster_dims__(2, 1, 1) __launch_bounds__(kThreads, 1) fused_block_kernel(Scratch* sc, const __nv_bfloat16* xp, const __nv_bfloat16* wqkvp, __nv_bfloat16* outp,
                                                                   const __grid_constant__ Params p) {
  extern __shared__ __align__(1024) uint8_t smem_raw[];
  if (threadIdx.x == 256) {
    prefetch_map(&p.x);
    prefetch_map(&p.wqkv);
  }
  if (threadIdx.x < 56) {
    const int l = threadIdx.x & 31, b = blockIdx.x & 127;
    if (threadIdx.x < 32) prefetch_l2(xp + (b * 16 + (l & 15)) * kD + (l >> 4) * 64);
    else prefetch_l2(wqkvp + b * (3 * kD) + (l >> 3) * kD + (l & 7) * 64);
  }
  const uint32_t sb = smem_u32(smem_raw);
  const int bid = role_id<BY_SM>();
  const int r = bid >> 3, c = bid & 7, rank = blockIdx.x & 1;
  auto first_fill = [&](int j) {
    const uint32_t fb = sb + kBars + 8 * j, dst = sb + kRing + j * 40960;
    mbar_expect_tx(fb, 40960);
    tma3d(j >> 1 == c ? sb + kOwn + (j & 1) * 16384 : dst, &p.x, j * 64, (r >> 1) * 128, rank, fb);
#pragma unroll
    for (int a = 0; a < 3; a++) tma2d(dst + 16384 + a * 8192, &p.wqkv, a * kD + c * 64, j * 64, fb);
    mbar_arrive(fb);
  };
  const int tid = threadIdx.x, warp = __shfl_sync(~0u, tid >> 5, 0), wg = warp >> 2;
  if (bid >= 128) {
    if (tid == 0) PROF_BEGIN;
    colsum_cta(p, sc, sb, warp, bid);
    return;
  }
  if (wg == 2) {
    if (warp == 8 && elect_one()) {
      mbar_init(sb + kBars, 2);
      asm volatile("fence.mbarrier_init.release.cluster;" ::: "memory");
      first_fill(0);
#pragma unroll
      for (int j = 1; j < 4; j++) mbar_init(sb + kBars + 8 * j, 2);
      asm volatile("fence.mbarrier_init.release.cluster;" ::: "memory");
      TSS(0);
    }
    __syncwarp();
    if (warp == 8) nb_arrive(kNbOrder, 160);
    asm volatile("setmaxnreg.dec.sync.aligned.u32 40;");
    if (warp == 8) {
      cluster_arrive();
      if (elect_one()) {
#pragma unroll 1
        for (int j = 1; j < 4; j++) first_fill(j);
        TSS(1);
      }
      __syncwarp();
    } else {
      if (elect_one()) {
        uint64_t shifts = warp == 9 ? bar_shifts(4) : warp == 10 ? bar_shifts(22) : bar_shifts(40);
#pragma unroll 1
        for (int i = 0; i < 18; i++, shifts >>= 3) mbar_init(sb + kBars + 8 * (18 * warp - 158 + i), 1u << (shifts & 7));
        if (warp == 10) asm volatile("mbarrier.arrive.shared::cta.b64 _, [%0], 2;" ::"r"(sb + kBars + 8 * 31) : "memory");
        sts32(sb + kZero, 0);
        sts32(sb + kScale + 4, 0);
        sts32(sb + kRole, bid);
        sts128(sb + kOnes, make_uint4(0x3F803F80u, 0, 0, 0x3F803F80u));
        asm volatile("fence.mbarrier_init.release.cluster;" ::: "memory");
      }
      __syncwarp();
      cluster_arrive();
    }
    cluster_wait();
    const uint32_t ep = ld_epoch(sc);
    if (tid == 320) sts32(sb + kEpoch, ep);
    if (tid == 320) PROF_BEGIN;
    const int pw = warp & 3;
    if (pw == 0) {
      if (elect_one()) {
        const int row = r * 128;
        const uint32_t land = sb + kBars + 8 * kLandBar;
#pragma unroll 1
        for (Ring<0> q(sb, 0); q.j < 32; q.next()) {
          q.acquire();
          const int kb = p.g1[c][q.j];
          if (kb & kInPlace) { mbar_arrive(q.bar()); continue; }
          mbar_expect_tx(q.bar(), 16384);
          tma3d(kb >> 1 == c ? sb + kOwn + (kb & 1) * 16384 : q.dst(), &p.x, kb * 64, (r >> 1) * 128, rank, q.bar());
        }
        prefetch_map(&p.o);
        prefetch_map(&p.o16);
        flag_wait(sc->flags + kFlO + r * kFlRow, ep * 8);
        fence_async();
        TS(40);
#pragma unroll 1
        for (Ring<1> q(sb, 0); q.j < 16; q.next()) {
          q.acquire_first();
          if (q.j == 8) {
            prefetch_map(&p.wg);
            prefetch_map(&p.wu);
            prefetch_map(&p.h);
            prefetch_map(&p.h16);
            mbar_wait(sb + kBars + 8 * kSentBar, 0);
            mbar_arrive(q.bar());
            mbar_arrive(sb + kBars + 8 * (kStgBar + 1));
            if (bid == 0) __stcg(sc->flags + kFlPace, ep);
            __nanosleep(kGateONs);
            continue;
          }
          const uint32_t bar = q.j < 8 ? q.bar() : land + 8 * q.bi;
          if (q.j == 9) TS(41);
          mbar_expect_tx(bar, 16384);
          tma2d(q.dst(), &p.o, p.g2[c][q.j] * 64, row, bar);
        }
#pragma unroll 1
        for (Ring<2> q(sb, 0); q.j < 64; q.next()) {
          q.acquire_first();
          const int kb = p.g3[c][q.j];
          if (kb & kInPlace) { mbar_arrive(q.bar()); continue; }
          if (q.j == 4) { __nanosleep(kGateHNs); TS(42); }
          const uint32_t bar = q.j < 18 ? land + 8 * q.bi : q.bar();
          mbar_expect_tx(bar, 16384);
          tma2d(q.dst(), &p.h, (kb & 15) * 64, row, bar);
        }
        prefetch_map(&p.hh);
        prefetch_map(&p.out);
        Ring<3> q(sb, 0);
#pragma unroll 1
        for (; q.j < 16; q.next()) {
          q.acquire_first();
          if (q.j == 0) { mbar_arrive(q.bar()); continue; }
          mbar_expect_tx(q.bar(), 16384);
          tma2d(q.dst(), &p.h, ((q.j + 9) & 15) * 64, row, q.bar());
        }
        uint32_t wave = sb + kBars + 8 * kWaveBar;
        mbar_wait(wave, 0);
        fence_async();
        int share = lds32(sb + kPlan);
#pragma unroll 1
        for (; q.j < 72; q.next()) {
          const int kb = p.g4in[q.j - 16];
          if (kb >> 6 == kMark >> 6) {
            wave += 8;
            mbar_wait(wave, 0);
            fence_async();
          }
          q.acquire();
          const bool half = kb >= (kMark | kInO) && --share >= 0;
          mbar_expect_tx(q.bar(), half ? 8192 : 16384);
          tma2d(q.dst() + half * 8192, half ? &p.ost : kb & kInO ? &p.o : &p.hh, (kb & 63) * 64, row + half * 64, q.bar());
        }
      }
    } else if (pw == 1) {
      if (elect_one()) {
        const int rp = r >> 1;
#pragma unroll 1
        for (Ring<0> q(sb, 16384); q.j < 32; q.next()) {
          q.acquire();
          mbar_expect_tx(q.bar(), 24576);
          const int col = ((q.j >> 4) * 8 + c) * 64, k0 = (p.g1[c][q.j] & 15) * 64;
          tma2d_mc(q.dst() + rank * 8192, &p.wqkv, rank * kD + col, k0, q.bar());
          if ((q.j & 1) == rank) tma2d_mc(q.dst() + 16384, &p.wqkv, 2 * kD + col, k0, q.bar());
          if (q.j == max(r, 4))
            for (int a = 0; a < 3; a++) tma_prefetch2d(&p.wqkv, a * kD + (8 + c) * 64, ((r + 12) & 15) * 64);
          if (q.j >> 1 == rp + 8) tma_prefetch2d(&p.wo, (c * 2 + rank) * 64, (q.j & 15) * 64);
        }
        if (r < 6) tma_prefetch2d(rp == 1 ? &p.wu : &p.wg, (c * 7 + 3 + (rp >> 1)) * 64, (c * 2 + rank) * 64);
#pragma unroll 1
        for (Ring<1> q(sb, 16384 + rank * 8192); q.j < 16; q.next()) {
          q.acquire_first();
          mbar_expect_tx(q.bar(), 16384);
          tma2d_mc(q.dst(), &p.wo, (c * 2 + rank) * 64, p.g2[c][q.j] * 64, q.bar());
        }
        const CUtensorMap* mine = rank ? &p.wu : &p.wg;
#pragma unroll 1
        for (Ring<2> q(sb, 16384); q.j < 64; q.next()) {
          const int kb = p.g3[c][q.j], tile = kb >> 5, f0 = c * 7 + (tile & 1) * 3, fp = f0 + (tile & 2);
          const int k0 = (kb & 15) * 64;
          q.acquire_first();
          mbar_expect_tx(q.bar(), 24576);
          const uint32_t dst = q.j < 4 ? sb + kRing + (q.j + 1) * 32768 : q.dst();
          tma2d_mc(dst + rank * 8192, mine, fp * 64, k0, q.bar());
          if ((q.j & 1) == rank) tma2d_mc(dst + 16384, tile & 2 ? &p.wu : &p.wg, (f0 + 1) * 64, k0, q.bar());
          const int d = q.j - kPfStep - (c & 1) * 5 - (r >> 2);
          if (d == 0 || d == 11 || d == 22) {
            const int f = c * 7 + (d == 0 ? 2 : d == 11 ? 5 : 6);
            tma_prefetch2d(&p.wg, f * 64, r * 64);
            tma_prefetch2d(&p.wu, f * 64, r * 64);
            if (d != 22) tma_prefetch2d(&p.wu, (f - 1) * 64, r * 64);
            else tma_prefetch2d(&p.wd, (c * 2 + rank) * 64, rp * (7 * 64));
          }
        }
        Ring<3> q(sb, 16384 + rank * 8192);
#pragma unroll 1
        for (; q.j < 16; q.next()) {
          q.acquire_first();
          mbar_expect_tx(q.bar(), 16384);
          tma2d_mc(q.dst(), mine, (c * 7 + 6) * 64, ((q.j + 9) & 15) * 64, q.bar());
          if (q.j >> 1 == rp) tma_prefetch2d(&p.wd, (c * 2 + rank) * 64, p.g4[q.j] * 64);
        }
#pragma unroll 1
        for (; q.j < 72; q.next()) {
          q.acquire();
          mbar_expect_tx(q.bar(), 16384);
          tma2d_mc(q.dst(), &p.wd, (c * 2 + rank) * 64, p.g4[q.j - 16] * 64, q.bar());
          if ((q.j & 15) >> 1 == rp && q.j < 56) tma_prefetch2d(&p.wd, (c * 2 + rank) * 64, p.g4[q.j] * 64);
        }
      }
    } else {
      const int cw = pw - 2;
      const uint32_t stg = sb + kStage + cw * 32768, rb = sb + kBars + 8 * kResBar;
      uint32_t land_par = 0;
      sts64(sb + kPlan, global_ns(), clock());
      if (cw == 0) {
#pragma unroll 1
        for (int i = 0; i < 16; i++) sts128(sb + kFill + i * 512 + (tid & 31) * 16, make_uint4(kPoison, kPoison, kPoison, kPoison));
        __nanosleep(kSampleNs);
        const uint32_t l15 = tid & 15;
        const uint4 os = __ldg(plus(p.wop, (tid & 31) * 128 + c * 16 + l15));
        const uint4 gs = __ldg(plus(tid & 16 ? p.wup : p.wgp, l15 * 451 + c * 56));
        const uint4 ws = __ldg(plus((const uint4*)wqkvp, (tid & 7) * 385 + (tid & 24) * 16 + (8 + c) * 8));
        sts64(sb + kScale, __float_as_uint(low_peak(os) * kBias3 * low_peak(gs)), __float_as_uint(low_peak(ws) * kBias1) | 1);
        if (tid == 320) TS(93);
      }
#pragma unroll 1
      for (int ev = -1; ev < 4; ev++) {
        const bool quads = cw == 0 && ev == 1;
        if (ev >= cw && !quads) nb_sync(kNbPub + cw, 160);
        if (ev >= cw && elect_one()) {
          if (quads) {
            mbar_wait(sb + kBars + 8 * (kHalfBar + 1), 0);
#pragma unroll 1
            for (int i = 0; i < 2; i++) {
              __nanosleep(i ? kPaceNs : kHoldNs);
              tma_store2d(&p.hst, stg + 16384 + i * 8192, c * 128 + 64, r * 128 + i * 64);
              TS(100 + i);
            }
            bulk_commit();
            bulk_wait_read();
            mbar_arrive(sb + kBars + 8 * kStgBar);
          } else {
            if (ev == 1) {
              const uint32_t now = global_ns();
              const float left = (float)(now - lds32(sb + kPlan)) * (float)kRemain * rcp((float)((uint32_t)clock() - lds32(sb + kPlan + 4)));
              send_word(sc->finish + (uint32_t)bid, now + (uint32_t)left, ep);
            }
            const int it = ev - 2 + cw, f0 = c * 7 + (1 - cw) * 3, fp = it == 2 ? c * 7 + 6 : it ? f0 + 2 : c + 8 - 8 * cw;
            const bool is_o = ev == 0;
            const CUtensorMap* m = it <= 0 ? &p.ost : &p.hhst;
            const int b0 = is_o ? c : f0 + 1, b1 = fp;
#pragma unroll 1
            for (int i = is_o || it == 1 ? 0 : 2; i < (is_o ? 2 : 4); i++) {
              tma_store2d(m, stg + i * 8192, (i < 2 ? b0 : b1) * 64, r * 128 + (i & 1) * 64);
              if (!is_o) {
                bulk_commit();
                bulk_wait_read();
                __nanosleep(kPaceNs);
              }
            }
            bulk_commit();
            bulk_wait_all();
            mbar_arrive(sb + kBars + 8 * (kStgBar + cw));
            if (ev == 3 + cw) {
#pragma unroll
              for (int i = 0; i < 2; i++) asm volatile("mbarrier.arrive.shared::cluster.b64 _, [%0], 4;" ::"r"(map_cta(sb + kBars + 8 * 37, i)) : "memory");
            }
            flag_signal(SC_AT(flags, kFlHH + ev * 2 - 3 + cw + r * kFlRow));
            TS(44 + cw * 8 + ev);
            if (ev == 2 && cw) {
              sts32(sb + kPlan, await_word(sc->plan + (uint32_t)c, ep) >> (r >> 1) * 4 & 15);
              mbar_expect_tx(rb, 16384);
#pragma unroll 1
              for (int i = 0; i < 2; i++) tma2d(stg + 8192 + i * 16384, &p.hst, c * 128 + i * 64, r * 128 + 64, rb);
            }
          }
        }
        nb_sync(kNbSelf + cw, 32);
        if (ev >= 2 && ev + cw >= 3 && elect_one()) {
          const int wv = cw == 0 ? 3 : ev == 2 ? 0 : 4;
#pragma unroll 1
          for (int i = wv; i <= max(wv, 2); i++) flag_wait(SC_AT(flags, kFlHH + i + r * kFlRow), ep * 8);
          fence_async();
          mbar_arrive(sb + kBars + 8 * (kWaveBar + (wv >> 1)));
          if (wv == 4) {
            mbar_expect_tx(sb + kBars + 8 * kPartBar, 16384);
#pragma unroll 1
            for (int i = 0; i < 2; i++) tma2d(stg + 16384 + i * 8192, &p.hst, c * 128 + i * 64, r * 128, sb + kBars + 8 * kPartBar);
          }
        }
        nb_sync(kNbSelf + cw, 32);
#pragma unroll 1
        for (int sub = 0; ev < 3 && (ev != 0 || cw == 1); sub++) {
          nb_sync(kNbSelf + cw, 32);
          if (ev == 0) check_blocks(p, sc, sb, r, c, sub, land_par);
          const int u = ev < 0 ? cw : 2 * ev + 1 + cw, lane = fresh_tid() & 31;
          if (u == 1 && !sub) {
            uint3 st[5];
            load_tagged<5, true>(st, SC_AT(stat1, r * 128 + lane), 32, ep, SC_AT(stat1, (r < 2 ? r : r - 2) * 128 + (lane & 7)) + 120);
#pragma unroll
            for (int i = 0; i < 4; i++) sts64(sb + kStat + (i * 32 + lane) * 8, st[i].x, st[i].y);
            sts64(sb + kStat - 64 + (lane & 7) * 8, st[4].x, st[4].y);
            nb_sync(kNbSelf + cw, 32);
            if (lane < 4) mbar_arrive(sb + kBars + 8 * kStatBar);
            if (lane == 0) TS(17);
          }
          if (u == 1) {
            const uint4* gh = SC_AT(halo, (sub * 128 + bid) * 192 + lane) - 16 * 192;
            uint4 hv[6] = {};
            nb_sync(kNbHalo, 64);
            uint32_t ns = sub ? kHaloNs : 2 * kBackoffNs;
#pragma unroll 1
            for (int spins = 0; r >= 2; spins++) {
              if (ns) __nanosleep(ns);
              ns = sub ? 0 : kBackoffNs;
              if (spins > 2000000) __trap();
#pragma unroll
              for (int i = 0; i < 6; i++) hv[i] = ld_b128(gh + i * 32);
              uint32_t bad = (hv[5].y ^ ep) | (hv[5].z ^ ep);
#pragma unroll
              for (int i = 0; i < 6; i++) bad |= hv[i].w ^ ep;
              if (!__any_sync(~0u, bad != 0)) break;
            }
            const uint32_t dst = sb + kStage + sub * 32768 + lane * 16;
            sts128(dst, make_uint4(hv[0].x, hv[0].y, hv[0].z, hv[1].x));
            sts128(dst + 512, make_uint4(hv[1].y, hv[1].z, hv[2].x, hv[2].y));
            sts128(dst + 1024, make_uint4(hv[2].z, hv[3].x, hv[3].y, hv[3].z));
            sts128(dst + 1536, make_uint4(hv[4].x, hv[4].y, hv[4].z, hv[5].x));
            nb_arrive(kNbHalo + 1, 64);
            if (lane == 0) TS(123 + sub);
          }
          if (sub) break;
          uint3 v[3];
          load_tagged<3, false>(v, SC_AT(cs, c * 96 + u * 768 + lane), 32, ep);
          if (u < 2) {
#pragma unroll
            for (int i = 0; i < 3; i++)
#pragma unroll
              for (int k = 0; k < 8; k++)
                sts32(sb + kAug + cw * 4096 + i * 1024 + k * 128 + ((lane * 4) ^ (k * 16)), k == 7 ? 0x3F803F80u : k == 4 || k == 6 ? v[i].z : k & 1 && k != 5 ? v[i].y : v[i].x);
            fence_async_smem();
          } else {
#pragma unroll
            for (int i = 0; i < 3; i++) sts64(sb + kCs + cw * 768 + (i * 32 + lane) * 8, v[i].x, v[i].y);
          }
          nb_sync(kNbSelf + cw, 32);
          if (lane == 0) { mbar_arrive(sb + kBars + 8 * (kAuxBar + cw)); TS(104 + u); }
        }
        nb_sync(kNbSelf + cw, 32);
        if (ev < 0 && cw == 0 && elect_one()) {
#pragma unroll 1
          for (int i = 0; i < 6; i++) {
            __nanosleep(i == 0 ? (c >> 1) * (kFillNs / 4) : kFillNs);
            tma_store2d(i < 2 ? &p.ost : &p.hst, sb + kFill, i < 2 ? (8 + c) * 64 : (c * 2 - 1 + (i >> 1)) * 64, r * 128 + (i & 1) * 64);
            bulk_commit();
          }
          uint32_t peer;
          asm volatile("ld.shared::cluster.b32 %0, [%1];" : "=r"(peer) : "r"(map_cta(sb + kRole, rank ^ 1)) : "memory");
          if (peer != (bid ^ 8)) __trap();
          TS(90);
        }
        nb_sync(kNbSelf + cw, 32);
      }
    }
  } else {
    if (tid == 0) TSS(2);
    cluster_arrive();
    float bias = 0.f;
    float sx = 0.f, mx = 0.f;
    asm volatile("setmaxnreg.inc.sync.aligned.u32 232;");
    if (tid == 0) TSS(4);
    int task;
    asm volatile("mov.u32 %0, %1;" : "=r"(task) : "r"(8 - wg));

#pragma unroll 1
    for (task = __shfl_sync(~0u, task, 0);; task++) {
      if (task == 1 + wg || task == 9 - wg) {
        const int t = fresh_tid();
        uint2 scale;
        do asm volatile("ld.volatile.shared.v2.b32 {%0, %1}, [%2];" : "=r"(scale.x), "=r"(scale.y) : "r"(sb + kScale) : "memory");
        while (scale.y == 0);
        __syncwarp();
        bias = bias_at(low_peak(lds128(sb + (task > 5 ? kRing : kStage + wg * 32768) + (t & 126) * 64 + (t & 14) * 8 + (t & 1) * 8192)) *
                       __uint_as_float(task > 5 ? scale.y : scale.x));
        if (t == 128 && task > 5) TS(95);
      }
      if (wg == 0 && (task == 1 || task == 4)) {
        float acc[2][96];
        const int t = fresh_tid() & 127;
        const uint32_t frag = sb + kOwn + ((t >> 5) * 16 + (t & 15)) * 128, frag_x = ((t >> 4) & 1) ^ (t & 7);
        TSG(2);
        if (task == 4) mbar_wait(sb + kBars + 8 * kResBar, 0);
        auto residual = [&](int m) {
#pragma unroll
          for (int i = 0; i < 8; i++) {
            uint32_t v[4];
            ldsm4(frag + (i >> 2) * 16384 + m * 8192 + ((frag_x ^ (i * 2 & 6)) << 4), v);
#pragma unroll
            for (int e = 0; e < 4; e++) {
              float* d = &acc[m][8 * i + 2 * e];
              asm("shl.b32 %0, %1, 16;" : "=f"(d[0]) : "r"(v[e]));
              asm("and.b32 %0, %1, 0xFFFF0000;" : "=f"(d[1]) : "r"(v[e]));
            }
          }
        };
        residual(1);
        if (task == 1) {
          residual(0);
        } else {
#pragma unroll
          for (int i = 0; i < 64; i++) acc[0][i] = 0.f;
        }
        __syncwarp();
        if ((t & 31) == 0) mbar_arrive(sb + kBars + 8 * kResFreeBar);
        TSG(4);
        if ((tid & 127) == 0) TS(task == 1 ? 6 : 14);
        if (task == 4) {
          mainloop<128, kTail>(sc, acc, sb, 3, 16, 56, -2, true, false, false, 0, __shfl_sync(~0u, lds32(sb + kPlan), 0), &p.out, c * 128, (r >> 1) * 128, warp, outp);
          if ((tid & 127) == 0) TSK(15);
          if (fresh_tid() == 0) {
            if (bid == 0) __stcg(sc->epoch, lds32(sb + kEpoch));
            TSK(19);
          }
          break;
        }
        mainloop<128, -1>(sc, acc, sb, 1, 0, 15, kPauseG2, false, true, false, 0);
        const int t2 = fresh_tid() & 127;
        const uint32_t frag2 = sb + kStage + ((t2 >> 5) * 16 + (t2 & 15)) * 128, frag2_x = ((t2 >> 4) & 1) ^ (t2 & 7);
        const uint32_t empty = map_cta(sb + kBars + 8 * (ring_base(1) + 5), t2 & 1);
        mbar_wait(sb + kBars + 8 * kStgBar, 0);
        mbar_wait(sb + kBars + 8 * ring_base(1), 1);
#pragma unroll
        for (int m = 0; m < 2; m++) {
          const uint32_t a = desc_lo(sb + kRing, 16);
          wg_fence();
#pragma unroll
          for (int k = 0; k < 4; k++) wgmma_n128(acc[m], desc_kept(a, sb) + (m * 512 + k * 2), desc_kept(a, sb) + (kToB + k * 128));
          wg_commit();
          if (m) nb_arrive(kNbOrder + 1, 256);
          wg_wait<1>();
          if (!m) mbar_arrive_cluster_if(empty + 8 * 4, (t2 & 31) < 2);
        }
#pragma unroll
        for (int b = 0; b < 4; b++) {
          if (b == 1) {
            wg_wait<0>();
            if (t2 == 0) TSK(7);
          }
          if (b < 2) {
#pragma unroll
            for (int i = 0; i < 64; i++) asm volatile("" : "+f"(acc[b][i])::"memory");
          }
          stage_quarter(&acc[b & 1][32 * (b >> 1)], frag2, frag2_x, b);
          if (b & 1) {
            fence_async_smem();
            __syncwarp();
            if (elect_one()) {
              mbar_arrive(sb + kBars + 8 * (kHalfBar + (b >> 1)));
#pragma unroll
              for (int m = 0; m < 2; m++)
                if (b == 1) tma_store2d(&p.h16, sb + kStage + m * 8192 + warp * 2048, c * 128, r * 128 + m * 64 + warp * 16);
            }
            __syncwarp();
          }
        }
        if (t2 == 0) TS(8);
        sx = mx = 0.f;
        continue;
      }
      float acc[2][96];
      if (task == 8 + wg) {
        wg_fence();
#pragma unroll
        for (int m = 0; m < 2; m++) wgmma_n192_any(acc[m], desc(64 + m), desc(64 + m));
        wg_commit();
        wg_wait<0>();
#pragma unroll
        for (int i = 0; i < 96; i++) asm volatile("" : "+f"(acc[0][i]), "+f"(acc[1][i])::"memory");
      } else {
        const uint32_t z = fresh_tid() >> 10;
#pragma unroll
        for (int i = 0; i < 96; i++) {
#pragma unroll
          for (int m = 0; m < 2; m++)
            asm("{\n.reg .b32 t;\nlop3.b32 t, %1, %2, %3, 0xEA;\nmov.b32 %0, t;\n}\n" : "=f"(acc[m][i]) : "r"(z), "r"(2 * i + m + 1), "r"(__float_as_uint(bias)));
        }
      }
      if (task > 5) {
        if (wg) {
          if (task == 7) cluster_wait();
          if (tid == 128 && task == 7) { TSS(5); TSK(69); }
          const int t = fresh_tid() & 127, lr = c * 16 + (t >> 3);
          uint32_t pf = t < 64 ? (bid * 16 + (t >> 2)) * kD + (t & 3) * 64 : (r * 48 + t - 64) * kD + c * 64;
          const uint32_t src = sb + kRing + lr * 128 + (((t ^ lr) & 7) << 4), empty = map_cta(sb + kBars + 8 * 4, t & 1), zero = fresh_tid() >> 10;
#pragma unroll 1
          for (int j = task == 7 ? 0 : kSplit; j < (task == 7 ? kSplit : 16); j++) {
            mbar_wait(sb + kBars + 8 * (j & 3), (j >> 2) & 1);
            if (j < 2 && t == 0) TS(102 + j);
            const uint4 v = lds128(src + (j >> 1 == c ? kOwn + (j & 1) * 16384 : (j & 3) * 40960));
            __syncwarp();
            mbar_arrive_cluster_if(empty + 8 * (j & 3) + (v.x & zero), (t & 31) < 2);
            if ((j == 0 || j == 3 || j == 6) && t < 112) { pf += t < 64 ? 256 : 256 * 3 * kD; prefetch_l2(plus(t < 64 ? xp : wqkvp, pf)); }
            const uint32_t u[4] = {v.x, v.y, v.z, v.w};
#pragma unroll
            for (int e = 0; e < 4; e++) {
              const float d0 = bf_lo(u[e]), d1 = bf_hi(u[e]);
              sx += d0 + d1;
              mx = fmaf(d1, d1, fmaf(d0, d0, mx));
            }
          }
          if (task == 7) {
            if (t == 0) TS(96);
            continue;
          }
#pragma unroll
          for (int o = 4; o > 0; o >>= 1) { sx += __shfl_xor_sync(~0u, sx, o); mx += __shfl_xor_sync(~0u, mx, o); }
          const float mean = sx * (1.f / kD);
          float rstd;
          asm("rsqrt.approx.ftz.f32 %0, %1;" : "=f"(rstd) : "f"(fmaxf(mx * (1.f / kD) - mean * mean, 0.f) + 1e-5f));
          const uint32_t ep = lds32(sb + kEpoch);
          const int t2 = fresh_tid();
          if ((t2 & 7) == 0) st_b128(SC_AT(stat1, bid * 16 + (t2 >> 3 & 15)), __float_as_uint(rstd), __float_as_uint(-mean), ep, ep);
          if (t == 0) TS(16);
        }
        if (tid == 0) TSS(6);
        mainloop<192, -1>(sc, acc, sb, 0, wg * 16, wg ? 16 - kAhead : 16, wg ? kPauseG1 : -2, false, wg == 0, false, wg,
                          wg ? min((c + 2) & 7, 6) : c);
        int t = fresh_tid() & 127, lane = t & 31, g = lane >> 2, q = lane & 3;
        const int w = warp & 3;
        const uint32_t stg = sb + kStage + wg * 32768;
        auto tail = [&](int m, int k0, int k1) {
          wg_fence();
#pragma unroll
          for (int k = k0; k < k1; k++) {
            const uint64_t a = desc_kept(desc_lo(sb + kRing, 16), sb) + (4 - kAhead + (k >> 2)) * (40960 >> 4);
            wgmma_n192(acc[m], a + (m * 512 + (k & 3) * 2), a + (kToB + (k & 3) * 128));
          }
        };
        auto release = [&](int j, bool cond) { mbar_arrive_cluster_if(map_cta(sb + kBars + 8 * (4 + (j & 3)), lane & 1), cond); };
        if (wg) {
#pragma unroll
          for (int j = 32 - kAhead; j < 32; j++) {
            TST(2 * (j & 1));
            mbar_wait(sb + kBars + 8 * (j & 3), 1);
            TST(2 * (j & 1) + 1);
            tail(1, 4 * (j - 32 + kAhead), 4 * (j - 31 + kAhead));
            wg_commit();
            if (j == 32 - kAhead) {
              wg_wait<1>();
              release(j - 1, lane < 4);
              mbar_wait(sb + kBars + 8 * kResFreeBar, 0);
            }
          }
        } else {
          nb_arrive(kNbOrder + 1, 256);
          wg_wait<0>();
          release(15, lane < 2);
          if (t == 0) TSK(1);
        }
        TST(4);
        mbar_wait(sb + kBars + 8 * (kAuxBar + wg), 0);
        mbar_wait(sb + kBars + 8 * kStatBar, 0);
        {
          uint32_t am[4];
#pragma unroll
          for (int i = 0; i < 4; i++) {
            const float m1 = __uint_as_float(lds32(sb + kStat + (w * 16 + g) * 8 + 4 + (i >> 1) * 512 + (i & 1) * 64));
            const float m2 = bf_rest(m1), lo = q & 1 ? m2 : m1;
            am[i] = bf_upper(lo, q == 3 ? -bias : q == 2 ? bf_rest(m2) : lo);
          }
          const uint64_t db = (uint64_t)desc_lo(sb + kAug + wg * 4096, 1024) | (0x40000000ull << 32);
          TST(5);
          wg_fence();
          wgmma_n192_rs(acc[1], am[2], am[3], 0u, db);
          wg_commit();
          TST(6);
          wg_fence();
          wgmma_n192_rs(acc[0], am[0], am[1], 0u, db);
          wg_commit();
          if (wg) {
            tail(0, 0, 4 * kAhead);
            wg_commit();
            wg_wait<2>();
          } else {
            wg_wait<1>();
          }
          TST(8);
#pragma unroll
          for (int i = 0; i < 96; i++) asm volatile("" : "+f"(acc[1][i])::"memory");
        }
        t = fresh_tid() & 127, lane = t & 31;
        const uint32_t ep = lds32(sb + kEpoch);
        uint32_t pk[2][48];
        auto fold = [&](int pp, int jn, int hf) {
          const uint32_t v = pack_bf16(acc[pp][4 * jn + 2 * hf], acc[pp][4 * jn + 2 * hf + 1]);
          pk[pp][2 * jn + hf] = jn >= 16 ? movm(v) : v;
        };
        if (t == 96) TS(115 + wg);
#pragma unroll
        for (int jn = 8; jn < 24; jn++) fold(1, jn, 1);
        if (w < 3) {
#pragma unroll
          for (int i = 0; i < 4; i++)
            sts128(stg + (w + 5) * 2048 + i * 512 + lane * 16, make_uint4(pk[1][17 + 8 * i], pk[1][19 + 8 * i], pk[1][21 + 8 * i], pk[1][23 + 8 * i]));
        } else if (r < 14) {
          uint4* gh = SC_AT(halo, (wg * 128 + bid) * 192 + lane);
#pragma unroll
          for (int i = 0; i < 6; i++) st_b128(gh + i * 32, pk[1][17 + 6 * i], i < 5 ? pk[1][(19 + 6 * i) % 48] : ep, i < 5 ? pk[1][(21 + 6 * i) % 48] : ep, ep);
          if (wg == 0) {
#pragma unroll 1
            for (int i = 0; i < 6; i++, gh += 32) st_b128(gh + 128 * 192, 0, 0, 0, ep - 1);
          }
        }
        if (w == 3) nb_arrive(kNbHalo, 64);
        if (wg) nb_arrive(kNbOrder, 256);
        TST(9);
        if (t == 96) TS(111 + wg);
#pragma unroll
        for (int jn = 23; jn >= 0; jn--) {
          fold(1, jn, 0);
          if (jn < 8) fold(1, jn, 1);
        }
        t = fresh_tid() & 127, lane = t & 31, g = lane >> 2, q = lane & 3;
        const bool sel0 = 2 * q > g, sel1 = 2 * q + 1 > g, no_prev = (r < 2 && w == 0);
        const uint4 ones = lds128(sb + kOnes);
        const uint32_t lowmask = (sel0 ? 0x0000FFFFu : 0u) | (sel1 ? 0xFFFF0000u : 0u) | ones.y;
        float rs[4][2], rk[4][2];
#pragma unroll
        for (int i = 0; i < 4; i++) {
          const uint32_t a = sb + kStat + w * 128 + (i >> 1) * 512 + (i & 1) * 64;
          const float rq = __uint_as_float(lds32(a + g * 8)) * (0.17677669529663687f * 1.4426950408889634f);
          rk[i][0] = __uint_as_float(lds32(a + q * 16 - (sel0 ? 64 : 0)));
          rk[i][1] = __uint_as_float(lds32(a + q * 16 + 8 - (sel1 ? 64 : 0)));
          rs[i][0] = rk[i][0] * rq;
          rs[i][1] = rk[i][1] * rq;
        }
        {
          uint32_t all = ~0u;
#pragma unroll
          for (int i = 0; i < 48; i++) if (i < 16 || !(i & 1)) all &= pk[1][i];
          if (all == kPoison) sts32(sb + kZero + 8, 0);
        }
        TST(10);
        wg_wait<0>();
        TST(11);
#pragma unroll
        for (int j = 32 - kAhead; j < 32; j++) release(j, lane < 4 * wg && (w != 0 || j < 31));
#pragma unroll
        for (int i = 0; i < 96; i++) asm volatile("" : "+f"(acc[0][i])::"memory");
        if (t == 0 && wg) TSK(21);
#pragma unroll
        for (int jn = 8; jn < 24; jn++) fold(0, jn, 1);
#pragma unroll
        for (int i = 0; i < 4; i++)
          sts128(stg + (w + 1) * 2048 + i * 512 + lane * 16, make_uint4(pk[0][17 + 8 * i], pk[0][19 + 8 * i], pk[0][21 + 8 * i], pk[0][23 + 8 * i]));
#pragma unroll
        for (int jn = 23; jn >= 0; jn--) {
          fold(0, jn, 0);
          if (jn < 8) fold(0, jn, 1);
        }
        if (t == 0) TS(113 + wg);
        nb_sync(kNbWg + wg, 128);
        uint32_t hal[2][16];
        auto load_halo = [&](int m) {
#pragma unroll
          for (int i = 0; i < 4; i++) {
            const uint4 v = lds128(stg + w * 2048 + m * 8192 + i * 512 + lane * 16);
            uint32_t* h = &hal[m][i * 4];
            h[0] = v.x; h[1] = v.y; h[2] = v.z; h[3] = v.w;
          }
        };
        load_halo(1);
        if (w == 0) {
          nb_sync(kNbHalo + 1, 64);
          release(31, lane < 4 * wg);
        }
        load_halo(0);
        __syncwarp();
        if (t == 0) TS(2 + wg * 20);
        {
          uint32_t all = lowmask;
#pragma unroll
          for (int i = 0; i < 32; i++) if (i < 16 || !(i & 1)) all &= pk[0][i];
#pragma unroll
          for (int i = 0; i < 8; i++) all &= __float_as_uint(rs[i >> 1][i & 1]);
          if (all == kPoison) sts32(sb + kZero + 8, 0);
        }
        nb_sync(kNbWin, 256);
        if (t == 0) TS(9 + wg * 20);
        const uint32_t zero = lds32(sb + kZero);
        float s0[4][4], s1[4][4], s2[4][4];
#pragma unroll
        for (int k = 0; k < 4; k++) {
          pk[k >> 1][8 * (k & 1)] |= zero;
#pragma unroll
          for (int e = 0; e < 4; e++) s0[k][e] = s1[k][e] = s2[k][e] = 0.f;
        }
#pragma unroll
        for (int ks = 0; ks < 2; ks++)
#pragma unroll
          for (int k = 0; k < 4; k++) {
            const uint32_t* qf = &pk[k >> 1][8 * (k & 1) + 4 * ks];
            const uint32_t* kf = &pk[k >> 1][16 + 8 * (k & 1) + 4 * ks];
            const uint32_t* hf = &hal[k >> 1][4 * (k & 1) + 2 * ks];
            mma16816(s0[k], qf[0], qf[1], qf[2], qf[3], hf[0], hf[1]);
            mma16816(s1[k], qf[0], qf[1], qf[2], qf[3], kf[0], kf[2]);
            mma16816(s2[k], qf[0], qf[1], qf[2], qf[3], kf[1], kf[3]);
          }
        float ea[4][2], eb[4][2], ma[4], mb[4];
#pragma unroll
        for (int k = 0; k < 4; k++) {
          const float *ra = rs[k & 2], *rb = rs[(k & 2) + 1];
          if (no_prev && k < 2) s0[k][0] = s0[k][1] = -INFINITY;
          ea[k][0] = (sel0 ? s0[k][0] : s1[k][0]) * ra[0]; ea[k][1] = (sel1 ? s0[k][1] : s1[k][1]) * ra[1];
          eb[k][0] = (sel0 ? s1[k][2] : s2[k][2]) * rb[0]; eb[k][1] = (sel1 ? s1[k][3] : s2[k][3]) * rb[1];
          ma[k] = fmaxf(ea[k][0], ea[k][1]); mb[k] = fmaxf(eb[k][0], eb[k][1]);
        }
#pragma unroll
        for (int o = 1; o < 4; o <<= 1)
#pragma unroll
          for (int k = 0; k < 4; k++) {
            ma[k] = fmaxf(ma[k], __shfl_xor_sync(~0u, ma[k], o));
            mb[k] = fmaxf(mb[k], __shfl_xor_sync(~0u, mb[k], o));
          }
        float ov[4][4][4], ls[4][4];
        uint32_t all = 0;
#pragma unroll
        for (int k = 0; k < 4; k++) {
          const float *ra = rk[k & 2], *rb = rk[(k & 2) + 1];
          ea[k][0] = ex2(ea[k][0] - ma[k]); ea[k][1] = ex2(ea[k][1] - ma[k]);
          eb[k][0] = ex2(eb[k][0] - mb[k]); eb[k][1] = ex2(eb[k][1] - mb[k]);
          const uint32_t pa = pack_bf16(ea[k][0] * ra[0], ea[k][1] * ra[1]), pb = pack_bf16(eb[k][0] * rb[0], eb[k][1] * rb[1]);
          const uint32_t* vf = &pk[k >> 1][32 + 8 * (k & 1)];
          const uint32_t* hf = &hal[k >> 1][8 + 4 * (k & 1)];
#pragma unroll
          for (int d2 = 0; d2 < 2; d2++) {
#pragma unroll
            for (int e = 0; e < 4; e++) ov[k][d2][e] = ov[k][2 + d2][e] = 0.f;
            mma1688(ov[k][d2], hf[2 * d2], hf[2 * d2 + 1], pa & lowmask);
            mma1688(ov[k][2 + d2], vf[4 * d2], vf[4 * d2 + 2], pb & lowmask);
          }
#pragma unroll
          for (int d2 = 0; d2 < 2; d2++) {
            mma1688(ov[k][d2], vf[4 * d2], vf[4 * d2 + 2], pa & ~lowmask);
            mma1688(ov[k][2 + d2], vf[4 * d2 + 1], vf[4 * d2 + 3], pb & ~lowmask);
          }
          ls[k][0] = ls[k][1] = ls[k][2] = ls[k][3] = 0.f;
          mma16816(ls[k], ones.x, ones.y, ones.z, ones.w, pack_bf16(ea[k][0], ea[k][1]), pack_bf16(eb[k][0], eb[k][1]));
          if (k >= kDone) all |= pa & pb;
        }
#pragma unroll
        for (int k = 0; k < 4; k++) {
          if (k == kDone) {
            if (all == 0xFFFFFFFFu) sts32(sb + kZero + 8, 0);
            nb_arrive(kNbWin + 1, 256);
            all = 0;
          }
          all |= (__float_as_uint(ov[k][0][0]) & __float_as_uint(ov[k][1][0]) & __float_as_uint(ov[k][2][0])) &
                 (__float_as_uint(ov[k][3][0]) & __float_as_uint(ls[k][0]));
        }
        const uint32_t nil = lds32(sb + kZero);
        const uint32_t frag = stg + (w * 16 + (lane & 15)) * 128, frag_x = (lane >> 4) ^ (lane & 7);
        uint32_t after = all;
#pragma unroll
        for (int k = 0; k < 4; k++) {
          uint32_t h[2][4];
#pragma unroll
          for (int hf = 0; hf < 2; hf++) {
            const float i0 = rcp(__uint_as_float(__float_as_uint(ls[k][2 * hf]) | (after & nil)));
            const float i1 = rcp(__uint_as_float(__float_as_uint(ls[k][2 * hf + 1]) | (after & nil)));
#pragma unroll
            for (int e = 0; e < 4; e++) h[e >> 1][2 * (e & 1) + hf] = pack_bf16(ov[k][2 * hf + (e >> 1)][2 * (e & 1)] * i0, ov[k][2 * hf + (e >> 1)][2 * (e & 1) + 1] * i1);
            after = h[0][hf];
          }
#pragma unroll
          for (int d2 = 0; d2 < 2; d2++) stsm4_t(frag + (k >> 1) * 8192 + ((frag_x ^ ((k & 1) * 4 + d2 * 2)) << 4), h[d2][0], h[d2][1], h[d2][2], h[d2][3]);
        }
        fence_async_smem();
        if (wg) {
          __syncwarp();
          if (elect_one()) {
            tma_store2d(&p.o16, stg + w * 2048, (8 + c) * 64, r * 128 + w * 16);
            tma_store2d(&p.o16, stg + 8192 + w * 2048, (8 + c) * 64, r * 128 + 64 + w * 16);
            bulk_commit();
            bulk_wait_read();
            mbar_arrive(sb + kBars + 8 * kSentBar);
          }
          __syncwarp();
        } else {
          nb_arrive(kNbPub, 160);
        }
        if (t == 0) TS(3 + wg * 20);
        task = wg;
        sx = mx = bias = 0.f;
        continue;
      }

      {
#pragma unroll 1
        for (int part = task != 2; part < 2; part++) {
          if ((tid & 127) == 0) TS(6 + 2 * task + wg * 20);
          if (task + part == 5) {
            mainloop<128, 0>(sc, acc, sb, 3, 0, 16, -2, false, true, false, 1);
            continue;
          }
          const int j0 = task == 3 ? 48 - wg * 16 : part == 0 ? 2 - 2 * wg : 18 - 14 * wg;
          mainloop<192, 0>(sc, acc, sb, 2, j0, task != 2 ? 16 : part == 0 ? 2 : 14, -2, false, true, part == 0, wg);
          if (part == 0 && wg == 0) {
            const int t = fresh_tid() & 127;
            const uint32_t ep = lds32(sb + kEpoch);
            {
              float s = 0.f, ss = 0.f;
#pragma unroll 1
              for (int i = 0; i < 16; i++) {
                const uint4 v = lds128(sb + kStage + t * 128 + (i >> 3) * 16384 + (((i ^ t) & 7) << 4));
                const uint32_t u[4] = {v.x, v.y, v.z, v.w};
#pragma unroll
                for (int e = 0; e < 4; e++) {
                  const float d0 = bf_lo(u[e]), d1 = bf_hi(u[e]);
                  s = (s + d0) + d1;
                  ss = fmaf(d1, d1, fmaf(d0, d0, ss));
                }
              }
              st_b128(SC_AT(stat2, c * kS + r * 128 + t), __float_as_uint(s), __float_as_uint(ss), ep, ep);
            }
            __nanosleep(kStatNs);
            float2 sum = make_float2(0.f, 0.f);
#pragma unroll 1
            for (int i = 0; i < 2; i++) {
              uint3 a[4];
              load_tagged<4, true>(a, SC_AT(stat2, i * 4 * kS + r * 128 + t), kS, ep);
              sum.x += (__uint_as_float(a[0].x) + __uint_as_float(a[1].x)) + (__uint_as_float(a[2].x) + __uint_as_float(a[3].x));
              sum.y += (__uint_as_float(a[0].y) + __uint_as_float(a[1].y)) + (__uint_as_float(a[2].y) + __uint_as_float(a[3].y));
            }
            const float mean = sum.x * (1.f / kD);
            sts64f(sb + kStat + t * 8, make_float2(fmaxf(sum.y * (1.f / kD) - mean * mean, 0.f) + 1e-5f, -mean));
            __syncwarp();
            if (elect_one()) {
              bulk_commit();
              bulk_wait_read();
              mbar_arrive(sb + kBars + 8 * kStatBar);
            }
            __syncwarp();
            if (t == 0) TS(37);
          }
        }
      }
      const int t = fresh_tid() & 127, w = warp & 3, lane = t & 31, g = lane >> 2, q = lane & 3;
      const uint32_t stg = sb + kStage + wg * 32768;
      uint32_t csv = sb + kCs + wg * 768 + q * 8;
      uint32_t statv = sb + kStat + (w * 16 + g) * 8;
      const uint32_t frag = stg + (w * 16 + (lane & 15)) * 128;
      const uint32_t frag_x = (lane >> 4) ^ (lane & 7);
      const uint32_t priv = stg + (t & 96) * 64 + lane * 16;
      if (t == 0) TSK(7 + 2 * task + wg * 20);

      if (task == 4) {
        mbar_wait(sb + kBars + 8 * (kAuxBar + 1), 1);
        mbar_wait(sb + kBars + 8 * kResFreeBar, 1);
        mbar_wait(sb + kBars + 8 * (kStgBar + 1), 0);
      }
      asm volatile("" : "+r"(csv), "+r"(statv)::"memory");

      {
#pragma unroll
        for (int i = 0; i < 96; i++) asm volatile("sub.f32 %0, %0, %1;" : "+f"(acc[0][i]) : "f"(bias));
        auto next_rows = [&](int i) { asm volatile("sub.f32 %0, %1, %2;" : "=f"(acc[0][i]) : "f"(acc[1][i]), "f"(bias)); };
#pragma unroll 1
        for (int pp = 0; pp < 2; pp++) {
          TSG(pp);
          RowConst rc[2];
#pragma unroll
          for (int hf = 0; hf < 2; hf++) {
            const float2 st = lds64f_const(statv + pp * 512 + hf * 64);
            float rstd;
            asm("rsqrt.approx.ftz.f32 %0, %1;" : "=f"(rstd) : "f"(st.x));
            rc[hf] = {st.y, 0.7978845608f * rstd, 0.0356774081f * rstd * rstd * rstd, 0.5f * rstd * rstd};
          }
#pragma unroll
          for (int j2 = 0; j2 < 4; j2++) {
            uint32_t hv[4];
#pragma unroll
            for (int jj = 0; jj < 2; jj++) {
              const int jn = 2 * j2 + jj;
              const float2 cg = lds64f_const(csv + jn * 32), cu = lds64f_const(csv + 256 + jn * 32);
#pragma unroll
              for (int hf = 0; hf < 2; hf++) {
                const float nm = rc[hf].nmean;
                const float g0 = fmaf(nm, cg.x, acc[0][4 * jn + 2 * hf]), g1 = fmaf(nm, cg.y, acc[0][4 * jn + 2 * hf + 1]);
                const float u0 = fmaf(nm, cu.x, acc[0][32 + 4 * jn + 2 * hf]), u1 = fmaf(nm, cu.y, acc[0][33 + 4 * jn + 2 * hf]);
                hv[2 * jj + hf] = pack_bf16(g0 * u0 * gate_scale(g0, rc[hf]), g1 * u1 * gate_scale(g1, rc[hf]));
              }
            }
            stsm4(frag + 16384 + pp * 8192 + ((frag_x ^ (j2 * 2)) << 4), hv[0], hv[1], hv[2], hv[3]);
          }
          if (task < 4) {
            if (task == 2) {
#pragma unroll
              for (int j2 = 0; j2 < 4; j2++) {
                uint32_t hv[4];
#pragma unroll
                for (int jj = 0; jj < 2; jj++) {
                  const int jn = 16 + 2 * j2 + jj;
                  const float2 cs = lds64f_const(csv + jn * 32);
#pragma unroll
                  for (int hf = 0; hf < 2; hf++) {
                    const float nm = rc[hf].nmean;
                    const float t0 = fmaf(nm, cs.x, acc[0][4 * jn + 2 * hf]), t1 = fmaf(nm, cs.y, acc[0][4 * jn + 2 * hf + 1]);
                    hv[2 * jj + hf] = pack_bf16(t0 * gate_scale(t0, rc[hf]), t1 * gate_scale(t1, rc[hf]));
                  }
                }
                sts128(priv + pp * 8192 + j2 * 512, make_uint4(hv[0], hv[1], hv[2], hv[3]));
              }
            } else {
              uint4 park[4];
#pragma unroll
              for (int j2 = 0; j2 < 4; j2++) park[j2] = lds128(priv + pp * 8192 + j2 * 512);
              __syncwarp();
#pragma unroll
              for (int j2 = 0; j2 < 4; j2++) {
                const uint32_t pv[4] = {park[j2].x, park[j2].y, park[j2].z, park[j2].w};
                uint32_t hv[4];
#pragma unroll
                for (int jj = 0; jj < 2; jj++) {
                  const int jn = 16 + 2 * j2 + jj;
                  const float2 cs = lds64f_const(csv + jn * 32);
#pragma unroll
                  for (int hf = 0; hf < 2; hf++) {
                    const float nm = rc[hf].nmean;
                    const float t0 = fmaf(nm, cs.x, acc[0][4 * jn + 2 * hf]), t1 = fmaf(nm, cs.y, acc[0][4 * jn + 2 * hf + 1]);
                    asm("mul.rn.bf16x2 %0, %1, %2;" : "=r"(hv[2 * jj + hf]) : "r"(pack_bf16(t0, t1)), "r"(pv[2 * jj + hf]));
                  }
                }
                stsm4(frag + pp * 8192 + ((frag_x ^ (j2 * 2)) << 4), hv[0], hv[1], hv[2], hv[3]);
              }
            }
            if (pp == 1) break;
#pragma unroll
            for (int i = 64; i < 96; i++) next_rows(i);
          }
          if (pp == 1) break;
#pragma unroll
          for (int i = 0; i < 64; i++) next_rows(i);
        }
      }
      const int t3 = fresh_tid() & 127;
      uint4* part = SC_AT(part, bid * 1024 + (t3 & 96) * 8 + (t3 & 31));
      if (task == 2 && wg) {
#pragma unroll
        for (int k = 0; k < 8; k++) st_b128(part + k * 32, kPoison, kPoison, kPoison, kPoison);
      }
      fence_async_smem();
      nb_arrive(kNbPub + wg, 160);
      if (t == 0) TS(task == 4 ? 57 : 56 + task + wg * 2);
      if (task == 4) {
        mbar_wait(sb + kBars + 8 * kPartBar, 0);
        const bool none = lds32(sb + kPlan) == 0;
#pragma unroll 1
        for (int b = 1, spins = 0; b >= 0;) {
          uint4 v[4] = {};
          uint32_t top = 0;
          if (!none) {
#pragma unroll
            for (int k = 0; k < 4; k++) v[k] = ld_b128(part + (128 + k * 32));
          }
#pragma unroll
          for (int k = 0; k < 4; k++) {
            top = max(max(top, v[k].x), max(v[k].y, max(v[k].z, v[k].w)));
          }
          if (__any_sync(~0u, top == kPoison)) {
            if (++spins > 100000) __trap();
            __nanosleep(kPartNs);
            continue;
          }
#pragma unroll
          for (int k = 0; k < 4; k++) {
            uint32_t h[4];
            ldsm4(frag + 16384 + b * 8192 + ((frag_x ^ (k * 2)) << 4), h);
            asm("add.rn.bf16x2 %0, %0, %1;" : "+r"(v[k].x) : "r"(h[0]));
            asm("add.rn.bf16x2 %0, %0, %1;" : "+r"(v[k].y) : "r"(h[1]));
            asm("add.rn.bf16x2 %0, %0, %1;" : "+r"(v[k].z) : "r"(h[2]));
            asm("add.rn.bf16x2 %0, %0, %1;" : "+r"(v[k].w) : "r"(h[3]));
            sts128(stg + (t3 & 96) * 128 + (t3 & 31) * 16 + b * 2048 + k * 512, v[k]);
          }
          b--;
          part -= 128;
        }
        if (t == 0) TSK(56);
        nb_arrive(kNbPart, 256);
        break;
      }
      sx = mx = 0.f;
    }
  }
}

typedef CUresult (*EncodeTiledFn)(CUtensorMap*, CUtensorMapDataType, cuuint32_t, void*, const cuuint64_t*, const cuuint64_t*,
                                  const cuuint32_t*, const cuuint32_t*, CUtensorMapInterleave, CUtensorMapSwizzle,
                                  CUtensorMapL2promotion, CUtensorMapFloatOOBfill);

void encode(EncodeTiledFn fn, CUtensorMap* m, const void* base, int rank, cuuint64_t d0, cuuint64_t d1, cuuint64_t d2,
            cuuint64_t s1, cuuint64_t s2, cuuint32_t b2, cuuint32_t b1 = 64) {
  const cuuint64_t dims[3] = {d0, d1, d2}, strides[2] = {s1, s2};
  const cuuint32_t box[3] = {64, b1, b2}, es[3] = {1, 1, 1};
  fn(m, CU_TENSOR_MAP_DATA_TYPE_BFLOAT16, rank, const_cast<void*>(base), dims, strides, box, es, CU_TENSOR_MAP_INTERLEAVE_NONE,
     CU_TENSOR_MAP_SWIZZLE_128B, CU_TENSOR_MAP_L2_PROMOTION_L2_128B, CU_TENSOR_MAP_FLOAT_OOB_FILL_NONE);
}

}

extern "C" void kernel_launch(void* const* d_in, const int* in_sizes, int n_in, void* d_out, int out_size) {
  void* fnp = nullptr;
  cudaDriverEntryPointQueryResult qr;
  cudaGetDriverEntryPoint("cuTensorMapEncodeTiled", &fnp, cudaEnableDefault, &qr);
  EncodeTiledFn fn = (EncodeTiledFn)fnp;
  void *o, *h, *hh;
  cudaGetSymbolAddress(&o, g_o);
  cudaGetSymbolAddress(&h, g_h);
  cudaGetSymbolAddress(&hh, g_hh);

  Params p;
  Scratch* sc;
  cudaGetSymbolAddress((void**)&sc, g_scratch);
  encode(fn, &p.x, d_in[0], 3, kD, kS / 2, 2, 4 * kD, 2 * kD, 1, 128);
  encode(fn, &p.out, d_out, 3, kD, kS / 2, 2, 4 * kD, 2 * kD, 1, 16);
  encode(fn, &p.wqkv, d_in[1], 2, 3 * kD, kD, 1, 6 * kD, 0, 1);
  encode(fn, &p.wo, d_in[2], 2, kD, kD, 1, 2 * kD, 0, 1);
  encode(fn, &p.wd, d_in[6], 2, kD, kF, 1, 2 * kD, 0, 1);
  encode(fn, &p.wg, d_in[4], 2, kF, kD, 1, 2 * kF, 0, 1);
  encode(fn, &p.wu, d_in[5], 2, kF, kD, 1, 2 * kF, 0, 1);
  encode(fn, &p.o, o, 2, kD, kS, 1, 2 * kD, 0, 1, 128);
  encode(fn, &p.h, h, 2, kD, kS, 1, 2 * kD, 0, 1, 128);
  encode(fn, &p.hh, hh, 2, kF, kS, 1, 2 * kF, 0, 1, 128);
  encode(fn, &p.ost, o, 2, kD, kS, 1, 2 * kD, 0, 1);
  encode(fn, &p.o16, o, 2, kD, kS, 1, 2 * kD, 0, 1, 16);
  encode(fn, &p.h16, h, 2, kD, kS, 1, 2 * kD, 0, 1, 16);
  encode(fn, &p.hst, h, 2, kD, kS, 1, 2 * kD, 0, 1);
  encode(fn, &p.hhst, hh, 2, kF, kS, 1, 2 * kF, 0, 1);
  for (int c = 0; c < 8; c++) {
    for (int j = 0; j < 32; j++) p.g1[c][j] = g1_block(j, c) | (j >= 16 && (j < 20 || g1_block(j, c) >> 1 == c) ? kInPlace : 0);
    for (int j = 0; j < 16; j++) p.g2[c][j] = g2_block(j, c);
    for (int j = 0; j < 64; j++)
      p.g3[c][j] = g3_block(j, c) | ((0x000F000F003C000Full >> j & 1) && j != 28 + c ? kInPlace : 0) | g3_tile(j) << 5;
  }
  for (int i = 0; i < 56; i++) {
    const int b = p.g4[i] = g4_block(i);
    p.g4in[i] = b % 7 == 0 ? b / 7 | kInO | kMark : b % 7 == 3 ? (8 + b / 7) | kInO : b | (b == 4 || b == 6 ? kMark : 0);
  }
  p.wop = (const uint4*)d_in[2];
  p.wgp = (const uint4*)d_in[4];
  p.wup = (const uint4*)d_in[5];

  int dev = 0, sms = 0;
  cudaGetDevice(&dev);
  cudaDeviceGetAttribute(&sms, cudaDevAttrMultiProcessorCount, dev);
  auto* kernel = sms == 132 ? fused_block_kernel<true> : fused_block_kernel<false>;
  cudaFuncSetAttribute(kernel, cudaFuncAttributeMaxDynamicSharedMemorySize, kSmemBytes);
  kernel<<<132, kThreads, kSmemBytes, cudaStreamPerThread>>>(sc, (const __nv_bfloat16*)d_in[0], (const __nv_bfloat16*)d_in[1],
                                                                  (__nv_bfloat16*)d_out, p);
}
```

```cpp
#include <cuda_runtime.h>
#include <cuda_bf16.h>
#include <cuda.h>
#include <stddef.h>
#include <stdint.h>

namespace {

constexpr int kS = 2048, kD = 1024, kF = 3584;
constexpr int kThreads = 384;

constexpr int kRing = 0;
constexpr int kStage = 163840;
constexpr int kAug = kStage + 16384;
constexpr int kOwn = kStage + 32768;
constexpr int kFill = kStage + 24576;
constexpr int kCs = kStage + 65536;
constexpr int kStat = kCs + 1536;
constexpr int kBars = kStat + 1024;
constexpr int kSmemBytes = kBars + 512;
constexpr int kResBar = 38;
constexpr int kAuxBar = 39;
constexpr int kStgBar = 41;
constexpr int kResFreeBar = 43;
constexpr int kStatBar = 44;
constexpr int kPartBar = 45;
constexpr int kWaveBar = 46;
constexpr int kHalfBar = 49;
constexpr int kSentBar = 51;
constexpr int kLandBar = 52;
constexpr int kRowBar = 57;
constexpr int kNumBars = 58;
static_assert(kNumBars == 4 + 3 * 18, "barrier initialisation is split 4 + 3 x 18");
__host__ __device__ constexpr int bar_count(int i) {
  const int ph = i < 8 ? 0 : i < 18 ? 1 : i < 26 ? 2 : 3, base = ph * 9 - (ph & 1);
  return i < 38 ? (i - base < 4 + (ph & 1) + (ph == 3) ? 2 : ph == 0 ? 16 : 8) : i == kResFreeBar || i == kStatBar || (i >= kHalfBar && i < kLandBar) ? 4 : 1;
}
__host__ __device__ constexpr uint64_t bar_shifts(int first) {
  uint64_t m = 0;
  for (int i = 17; i >= 0; i--) {
    const int n = bar_count(first + i);
    m = m << 3 | (n == 16 ? 4 : n == 8 ? 3 : n >> 1);
  }
  return m;
}
constexpr int kScale = kCs + 512;
constexpr int kPlan = kBars + 472;
constexpr int kOnes = kBars + 480;
constexpr int kZero = kBars + 496;
constexpr int kRole = kBars + 508;
constexpr int kEpoch = kBars + 500;
__device__ __forceinline__ int ring_base(int ph) { return ph * 9 - (ph & 1); }
constexpr int kWide = 25;
constexpr int kFirstShared = 15;
constexpr int kNbOrder = 1;
constexpr int kNbWg = 3;
constexpr int kNbPub = 5;
constexpr int kNbWin = 7;
constexpr int kNbSelf = 13;
constexpr int kNbMean = 12;
constexpr int kNbPart = 11;
constexpr int kNbHalo = 9;

constexpr int kFlO = 0;
constexpr int kFlHH = 3;
constexpr int kFlRow = 32;
constexpr int kNumFlags = 16 * kFlRow;

constexpr int kPauseG1 = 7;
constexpr int kPauseG2 = 0;
constexpr int kAhead = 2;
constexpr int kSplit = 13;
constexpr int kTail = 4;
constexpr int kPartAt = 2;
constexpr int kShare = 5;
constexpr int kMost = 8;
constexpr int kBudget = 376;
constexpr int kStepNs = 167;
constexpr int kRemain = 65500;
constexpr int kDone = 3;
constexpr int kPfG1 = 14, kPfG3 = 18;
constexpr int kBackoffNs = 200;
constexpr int kPaceNs = 300;
constexpr int kPartNs = 500;
constexpr int kFillNs = 500;
constexpr int kHaloNs = 150;
constexpr int kGateONs = 150;
constexpr int kGateHNs = 150;
constexpr int kHoldNs = 1200;
constexpr int kSampleNs = 1000;
constexpr int kStatNs = 1500;
constexpr int kGather = 8;
constexpr int kRowNs = 800;
constexpr float kBias1 = 512.f, kBias2 = 512.f, kBias3 = 32768.f;

struct Scratch {
  uint32_t flags[kNumFlags];
  uint32_t epoch[32];
  uint4 stat1[kS];
  uint2 stat2[8 * kS];
  uint4 cs[2 * 8 * 96];
  uint2 wmean[8 * 128];
  uint2 dot[16 * 16 * 128];
  uint2 finish[128];
  uint2 plan[16];
  uint4 halo[2 * 16 * 8 * 6 * 32];
  uint4 part[128 * 8 * 128];
};
struct Params {
  CUtensorMap x, wqkv, o, wo, h, wg, wu, hh, wd, out;
  CUtensorMap ost, hst, hhst;
  CUtensorMap o16, h16;
  const uint4 *wop, *wgp, *wup;
  uint8_t g1[8][32], g2[8][16], g3[8][64], g4[56], g4in[56];
};

__device__ __align__(256) __nv_bfloat16 g_o[kS * kD];
__device__ __align__(256) __nv_bfloat16 g_h[kS * kD];
__device__ __align__(256) __nv_bfloat16 g_hh[kS * kF];
__device__ __align__(256) Scratch g_scratch;

template <bool BY_SM>
__device__ __forceinline__ int role_id() {
  uint32_t sm;
  asm("mov.u32 %0, %%smid;" : "=r"(sm));
  const int tpc = (BY_SM ? sm : blockIdx.x) >> 1, rank = blockIdx.x & 1;
  if ((tpc | 1) == 61) return 8 + 2 * tpc + rank;
  const int u = tpc - 32, s7 = (u * 37) >> 8;
  const int g = tpc < 32 ? tpc & 7 : tpc < 60 ? 1 + u - 7 * s7 : 0, s = tpc < 32 ? tpc >> 3 : tpc < 60 ? 4 + s7 : tpc - 58;
  return (g * 2 + rank) * 8 + s;
}
#define TS(i) do { } while (0)
#define TSK(i) do { } while (0)
#define TSS(i) do { } while (0)
#define TST(i)
#define TSG(i)

__device__ __forceinline__ uint32_t smem_u32(const void* p) { return (uint32_t)__cvta_generic_to_shared(p); }
template <class T>
__device__ __forceinline__ T* plus(T* p, uint32_t n) {
  uint64_t r;
  asm("{\n.reg .b32 lo, hi;\nmov.b64 {lo, hi}, %1;\nadd.cc.u32 lo, lo, %2;\naddc.u32 hi, hi, 0;\nmov.b64 %0, {lo, hi};\n}\n"
      : "=l"(r) : "l"(p), "r"(n * (uint32_t)sizeof(T)));
  return (T*)r;
}
#define SC_AT(member, n) ((decltype(+sc->member))((char*)plus((decltype(+sc->member))sc, n) + offsetof(Scratch, member)))
__device__ __forceinline__ void mbar_init(uint32_t bar, uint32_t cnt) {
  asm volatile("mbarrier.init.shared::cta.b64 [%0], %1;" ::"r"(bar), "r"(cnt));
}
__device__ __forceinline__ void mbar_expect_tx(uint32_t bar, uint32_t bytes) {
  asm volatile("mbarrier.arrive.expect_tx.shared::cta.b64 _, [%0], %1;" ::"r"(bar), "r"(bytes) : "memory");
}
__device__ __forceinline__ uint32_t map_cta(uint32_t addr, uint32_t cta) {
  uint32_t r;
  asm("mapa.shared::cluster.u32 %0, %1, %2;" : "=r"(r) : "r"(addr), "r"(cta));
  return r;
}
__device__ __forceinline__ void mbar_arrive_cluster_if(uint32_t bar, bool cond) {
  asm volatile("{\n.reg .pred p;\nsetp.ne.u32 p, %1, 0;\n@p mbarrier.arrive.shared::cluster.b64 _, [%0];\n}\n"
               ::"r"(bar), "r"((uint32_t)cond) : "memory");
}
__device__ __forceinline__ void mbar_wait(uint32_t bar, uint32_t parity) {
  asm volatile("{\n.reg .pred p;\nLAB_WAIT:\nmbarrier.try_wait.parity.shared::cta.b64 p, [%0], %1;\n@!p bra LAB_WAIT;\n}\n"
               ::"r"(bar), "r"(parity) : "memory");
  return;
  asm volatile("{\n.reg .pred p;\n.reg .u32 c;\nmov.u32 c, 0;\n"
               "LAB_WAIT:\nmbarrier.try_wait.parity.shared::cta.b64 p, [%0], %1;\n@p bra LAB_DONE;\n"
               "add.u32 c, c, 1;\nsetp.lt.u32 p, c, 2000000;\n@p bra LAB_WAIT;\ntrap;\nLAB_DONE:\n}\n"
               ::"r"(bar), "r"(parity) : "memory");
}
__device__ __forceinline__ void mbar_arrive(uint32_t bar) {
  asm volatile("mbarrier.arrive.shared::cta.b64 _, [%0];" ::"r"(bar) : "memory");
}
__device__ __forceinline__ void flag_signal(uint32_t* flag) {
  asm volatile("red.release.gpu.global.add.u32 [%0], 1;" ::"l"(flag) : "memory");
}
__device__ __forceinline__ void st_b128(uint4* p, uint32_t a, uint32_t b, uint32_t c, uint32_t d) {
  asm volatile("{\n.reg .b128 t;\n.reg .b64 lo, hi;\nmov.b64 lo, {%1,%2};\nmov.b64 hi, {%3,%4};\nmov.b128 t, {lo, hi};\n"
               "st.relaxed.gpu.global.b128 [%0], t;\n}\n" ::"l"(p), "r"(a), "r"(b), "r"(c), "r"(d) : "memory");
}
__device__ __forceinline__ uint4 ld_b128(const uint4* p) {
  uint4 v;
  asm volatile("{\n.reg .b128 t;\n.reg .b64 lo, hi;\nld.relaxed.gpu.global.b128 t, [%4];\nmov.b128 {lo, hi}, t;\n"
               "mov.b64 {%0,%1}, lo;\nmov.b64 {%2,%3}, hi;\n}\n" : "=r"(v.x), "=r"(v.y), "=r"(v.z), "=r"(v.w) : "l"(p) : "memory");
  return v;
}
__device__ __forceinline__ uint32_t ld_epoch(Scratch* sc) {
  uint32_t v;
  asm volatile("ld.relaxed.gpu.global.u32 %0, [%1];" : "=r"(v) : "l"(sc->epoch) : "memory");
  return v + 1;
}
__device__ __forceinline__ void flag_wait(uint32_t* flag, uint32_t target) {
  asm volatile("{\n.reg .pred p;\n.reg .u32 c, v;\nmov.u32 c, 0;\n"
               "LAB_WAIT:\nld.relaxed.gpu.global.u32 v, [%0];\nsub.u32 v, v, %1;\nsetp.ge.s32 p, v, 0;\n@p bra LAB_DONE;\n"
               "add.u32 c, c, 1;\nsetp.lt.u32 p, c, 4000000;\n@p bra LAB_WAIT;\ntrap;\nLAB_DONE:\n}\n"
               ::"l"(flag), "r"(target) : "memory");
}
__device__ __forceinline__ void send_word(uint2* p, uint32_t v, uint32_t tag) {
  asm volatile("{\n.reg .b64 t;\nmov.b64 t, {%1, %2};\nst.relaxed.gpu.global.b64 [%0], t;\n}\n" ::"l"(p), "r"(v), "r"(tag) : "memory");
}
template <int NS = 0>
__device__ __forceinline__ uint32_t await_word(const uint2* p, uint32_t tag) {
  uint32_t v;
  asm volatile("{\n.reg .pred p;\n.reg .u32 c, g;\n.reg .b64 t;\nmov.u32 c, 0;\n"
               "LAB_WAIT:\nld.relaxed.gpu.global.b64 t, [%1];\nmov.b64 {%0, g}, t;\nsetp.eq.u32 p, g, %2;\n@p bra LAB_DONE;\n"
               "nanosleep.u32 %3;\nadd.u32 c, c, 1;\nsetp.lt.u32 p, c, 4000000;\n@p bra LAB_WAIT;\ntrap;\nLAB_DONE:\n}\n"
               : "=r"(v) : "l"(p), "r"(tag), "n"(NS) : "memory");
  return v;
}
template <int N>
__device__ __forceinline__ float sum_words(const uint2* src, int stride, uint32_t tag) {
  float sum;
#pragma unroll 1
  for (int spins = 0;; spins++) {
    uint32_t bad = 0;
    sum = 0.f;
#pragma unroll
    for (int i = 0; i < N; i++) {
      uint32_t v, g;
      asm volatile("{\n.reg .b64 t;\nld.relaxed.gpu.global.b64 t, [%2];\nmov.b64 {%0, %1}, t;\n}\n" : "=r"(v), "=r"(g) : "l"(src + i * stride) : "memory");
      sum += __uint_as_float(v);
      bad |= g ^ tag;
    }
    if (!__any_sync(~0u, bad != 0)) return sum;
    if (spins > 2000000) __trap();
    __nanosleep(kBackoffNs);
  }
}
__device__ __forceinline__ uint32_t global_ns() {
  uint32_t v;
  asm volatile("mov.u32 %0, %%globaltimer_lo;" : "=r"(v));
  return v;
}
__device__ __forceinline__ int fresh_tid() {
  int v;
  asm volatile("mov.u32 %0, %%tid.x;" : "=r"(v));
  return v;
}
constexpr uint32_t kPoison = 0xFFFFFFFFu;
__device__ __forceinline__ bool elect_one() {
  uint32_t p;
  asm volatile("{\n.reg .pred P;\nelect.sync _|P, 0xffffffff;\nselp.u32 %0, 1, 0, P;\n}\n" : "=r"(p));
  return p != 0;
}
__device__ __forceinline__ void fence_async() { asm volatile("fence.acquire.gpu;\nfence.proxy.async.global;" ::: "memory"); }
__device__ __forceinline__ void fence_async_smem() { asm volatile("fence.proxy.async.shared::cta;" ::: "memory"); }
__device__ __forceinline__ void nb_sync(int id, int n) { asm volatile("bar.sync %0, %1;" ::"r"(id), "r"(n) : "memory"); }
__device__ __forceinline__ void nb_arrive(int id, int n) { asm volatile("bar.arrive %0, %1;" ::"r"(id), "r"(n) : "memory"); }

__device__ __forceinline__ void tma2d(uint32_t dst, const CUtensorMap* m, int c0, int c1, uint32_t bar) {
  asm volatile("cp.async.bulk.tensor.2d.shared::cluster.global.mbarrier::complete_tx::bytes [%0], [%1, {%3, %4}], [%2];"
               ::"r"(dst), "l"(m), "r"(bar), "r"(c0), "r"(c1) : "memory");
}
__device__ __forceinline__ void tma2d_mc(uint32_t dst, const CUtensorMap* m, int c0, int c1, uint32_t bar) {
  asm volatile("cp.async.bulk.tensor.2d.shared::cluster.global.mbarrier::complete_tx::bytes.multicast::cluster"
               " [%0], [%1, {%3, %4}], [%2], %5;"
               ::"r"(dst), "l"(m), "r"(bar), "r"(c0), "r"(c1), "h"((uint16_t)3) : "memory");
}
__device__ __forceinline__ void tma3d(uint32_t dst, const CUtensorMap* m, int c0, int c1, int c2, uint32_t bar) {
  asm volatile("cp.async.bulk.tensor.3d.shared::cluster.global.mbarrier::complete_tx::bytes [%0], [%1, {%3, %4, %5}], [%2];"
               ::"r"(dst), "l"(m), "r"(bar), "r"(c0), "r"(c1), "r"(c2) : "memory");
}
__device__ __forceinline__ void tma_store2d(const CUtensorMap* m, uint32_t src, int c0, int c1) {
  asm volatile("cp.async.bulk.tensor.2d.global.shared::cta.bulk_group [%0, {%2, %3}], [%1];"
               ::"l"(m), "r"(src), "r"(c0), "r"(c1) : "memory");
}
__device__ __forceinline__ void tma_store3d(const CUtensorMap* m, uint32_t src, int c0, int c1, int c2) {
  asm volatile("cp.async.bulk.tensor.3d.global.shared::cta.bulk_group [%0, {%2, %3, %4}], [%1];"
               ::"l"(m), "r"(src), "r"(c0), "r"(c1), "r"(c2) : "memory");
}
__device__ __forceinline__ void tma_prefetch2d(const CUtensorMap* m, int c0, int c1) {
  asm volatile("cp.async.bulk.prefetch.tensor.2d.L2.global [%0, {%1, %2}];" ::"l"(m), "r"(c0), "r"(c1) : "memory");
}
__device__ __forceinline__ void prefetch_map(const CUtensorMap* m) { asm volatile("prefetch.tensormap [%0];" ::"l"(m) : "memory"); }
__device__ __forceinline__ void bulk_commit() { asm volatile("cp.async.bulk.commit_group;" ::: "memory"); }
__device__ __forceinline__ void bulk_wait_all() { asm volatile("cp.async.bulk.wait_group 0;" ::: "memory"); }
__device__ __forceinline__ void bulk_wait_read() { asm volatile("cp.async.bulk.wait_group.read 0;" ::: "memory"); }
__device__ __forceinline__ void prefetch_l2(const void* p) { asm volatile("prefetch.global.L2 [%0];" ::"l"(p)); }
__device__ __forceinline__ void cluster_arrive() { asm volatile("barrier.cluster.arrive.relaxed.aligned;" ::: "memory"); }
__device__ __forceinline__ void cluster_wait() { asm volatile("barrier.cluster.wait.aligned;" ::: "memory"); }

__device__ __forceinline__ void wg_fence() { asm volatile("wgmma.fence.sync.aligned;" ::: "memory"); }
__device__ __forceinline__ void wg_commit() { asm volatile("wgmma.commit_group.sync.aligned;" ::: "memory"); }
template <int N> __device__ __forceinline__ void wg_wait() { asm volatile("wgmma.wait_group.sync.aligned %0;" ::"n"(N) : "memory"); }
__device__ __forceinline__ uint32_t desc_lo(uint32_t addr, uint32_t lbo) { return ((addr & 0x3FFFF) >> 4) | ((lbo >> 4) << 16); }
__device__ __forceinline__ uint64_t desc(uint32_t lo) { return (uint64_t)lo | (0x40000040ull << 32); }
__device__ __forceinline__ uint64_t desc_kept(uint32_t lo, uint32_t sb) { return (uint64_t)lo | (uint64_t)(0x40000040u | sb >> 31) << 32; }
constexpr int kToB = (16384 >> 4) + ((8192 - 16) >> 4 << 16);

__device__ __forceinline__ void wgmma_n128(float (&d)[96], uint64_t da, uint64_t db, int add = 1) {
  asm volatile(
      "{\n.reg .pred p;\nsetp.ne.b32 p, %66, 0;\n"
      "wgmma.mma_async.sync.aligned.m64n128k16.f32.bf16.bf16 {"
      "%0, %1, %2, %3, %4, %5, %6, %7, %8, %9, %10, %11, %12, %13, %14, %15, "
      "%16, %17, %18, %19, %20, %21, %22, %23, %24, %25, %26, %27, %28, %29, %30, %31, "
      "%32, %33, %34, %35, %36, %37, %38, %39, %40, %41, %42, %43, %44, %45, %46, %47, "
      "%48, %49, %50, %51, %52, %53, %54, %55, %56, %57, %58, %59, %60, %61, %62, %63}, "
      "%64, %65, p, 1, 1, 0, 1;\n}\n"
      :
        "+f"(d[0]), "+f"(d[1]), "+f"(d[2]), "+f"(d[3]), "+f"(d[4]), "+f"(d[5]), "+f"(d[6]), "+f"(d[7]),
        "+f"(d[8]), "+f"(d[9]), "+f"(d[10]), "+f"(d[11]), "+f"(d[12]), "+f"(d[13]), "+f"(d[14]), "+f"(d[15]),
        "+f"(d[16]), "+f"(d[17]), "+f"(d[18]), "+f"(d[19]), "+f"(d[20]), "+f"(d[21]), "+f"(d[22]), "+f"(d[23]),
        "+f"(d[24]), "+f"(d[25]), "+f"(d[26]), "+f"(d[27]), "+f"(d[28]), "+f"(d[29]), "+f"(d[30]), "+f"(d[31]),
        "+f"(d[32]), "+f"(d[33]), "+f"(d[34]), "+f"(d[35]), "+f"(d[36]), "+f"(d[37]), "+f"(d[38]), "+f"(d[39]),
        "+f"(d[40]), "+f"(d[41]), "+f"(d[42]), "+f"(d[43]), "+f"(d[44]), "+f"(d[45]), "+f"(d[46]), "+f"(d[47]),
        "+f"(d[48]), "+f"(d[49]), "+f"(d[50]), "+f"(d[51]), "+f"(d[52]), "+f"(d[53]), "+f"(d[54]), "+f"(d[55]),
        "+f"(d[56]), "+f"(d[57]), "+f"(d[58]), "+f"(d[59]), "+f"(d[60]), "+f"(d[61]), "+f"(d[62]), "+f"(d[63])
      : "l"(da), "l"(db), "r"(add));
}

__device__ __forceinline__ void wgmma_n192(float (&d)[96], uint64_t da, uint64_t db, int add = 1) {
  asm volatile(
      "{\n.reg .pred p;\nsetp.ne.b32 p, %98, 0;\n"
      "wgmma.mma_async.sync.aligned.m64n192k16.f32.bf16.bf16 {"
      "%0, %1, %2, %3, %4, %5, %6, %7, %8, %9, %10, %11, %12, %13, %14, %15, "
      "%16, %17, %18, %19, %20, %21, %22, %23, %24, %25, %26, %27, %28, %29, %30, %31, "
      "%32, %33, %34, %35, %36, %37, %38, %39, %40, %41, %42, %43, %44, %45, %46, %47, "
      "%48, %49, %50, %51, %52, %53, %54, %55, %56, %57, %58, %59, %60, %61, %62, %63, "
      "%64, %65, %66, %67, %68, %69, %70, %71, %72, %73, %74, %75, %76, %77, %78, %79, "
      "%80, %81, %82, %83, %84, %85, %86, %87, %88, %89, %90, %91, %92, %93, %94, %95}, "
      "%96, %97, p, 1, 1, 0, 1;\n}\n"
      :
        "+f"(d[0]), "+f"(d[1]), "+f"(d[2]), "+f"(d[3]), "+f"(d[4]), "+f"(d[5]), "+f"(d[6]), "+f"(d[7]),
        "+f"(d[8]), "+f"(d[9]), "+f"(d[10]), "+f"(d[11]), "+f"(d[12]), "+f"(d[13]), "+f"(d[14]), "+f"(d[15]),
        "+f"(d[16]), "+f"(d[17]), "+f"(d[18]), "+f"(d[19]), "+f"(d[20]), "+f"(d[21]), "+f"(d[22]), "+f"(d[23]),
        "+f"(d[24]), "+f"(d[25]), "+f"(d[26]), "+f"(d[27]), "+f"(d[28]), "+f"(d[29]), "+f"(d[30]), "+f"(d[31]),
        "+f"(d[32]), "+f"(d[33]), "+f"(d[34]), "+f"(d[35]), "+f"(d[36]), "+f"(d[37]), "+f"(d[38]), "+f"(d[39]),
        "+f"(d[40]), "+f"(d[41]), "+f"(d[42]), "+f"(d[43]), "+f"(d[44]), "+f"(d[45]), "+f"(d[46]), "+f"(d[47]),
        "+f"(d[48]), "+f"(d[49]), "+f"(d[50]), "+f"(d[51]), "+f"(d[52]), "+f"(d[53]), "+f"(d[54]), "+f"(d[55]),
        "+f"(d[56]), "+f"(d[57]), "+f"(d[58]), "+f"(d[59]), "+f"(d[60]), "+f"(d[61]), "+f"(d[62]), "+f"(d[63]),
        "+f"(d[64]), "+f"(d[65]), "+f"(d[66]), "+f"(d[67]), "+f"(d[68]), "+f"(d[69]), "+f"(d[70]), "+f"(d[71]),
        "+f"(d[72]), "+f"(d[73]), "+f"(d[74]), "+f"(d[75]), "+f"(d[76]), "+f"(d[77]), "+f"(d[78]), "+f"(d[79]),
        "+f"(d[80]), "+f"(d[81]), "+f"(d[82]), "+f"(d[83]), "+f"(d[84]), "+f"(d[85]), "+f"(d[86]), "+f"(d[87]),
        "+f"(d[88]), "+f"(d[89]), "+f"(d[90]), "+f"(d[91]), "+f"(d[92]), "+f"(d[93]), "+f"(d[94]), "+f"(d[95])
      : "l"(da), "l"(db), "r"(add));
}

__device__ __forceinline__ void wgmma_n192_any(float (&d)[96], uint64_t da, uint64_t db) {
  asm volatile(
      "wgmma.mma_async.sync.aligned.m64n192k16.f32.bf16.bf16 {"
      "%0, %1, %2, %3, %4, %5, %6, %7, %8, %9, %10, %11, %12, %13, %14, %15, "
      "%16, %17, %18, %19, %20, %21, %22, %23, %24, %25, %26, %27, %28, %29, %30, %31, "
      "%32, %33, %34, %35, %36, %37, %38, %39, %40, %41, %42, %43, %44, %45, %46, %47, "
      "%48, %49, %50, %51, %52, %53, %54, %55, %56, %57, %58, %59, %60, %61, %62, %63, "
      "%64, %65, %66, %67, %68, %69, %70, %71, %72, %73, %74, %75, %76, %77, %78, %79, "
      "%80, %81, %82, %83, %84, %85, %86, %87, %88, %89, %90, %91, %92, %93, %94, %95}, "
      "%96, %97, 0, 1, 1, 0, 1;\n"
      :
        "=f"(d[0]), "=f"(d[1]), "=f"(d[2]), "=f"(d[3]), "=f"(d[4]), "=f"(d[5]), "=f"(d[6]), "=f"(d[7]),
        "=f"(d[8]), "=f"(d[9]), "=f"(d[10]), "=f"(d[11]), "=f"(d[12]), "=f"(d[13]), "=f"(d[14]), "=f"(d[15]),
        "=f"(d[16]), "=f"(d[17]), "=f"(d[18]), "=f"(d[19]), "=f"(d[20]), "=f"(d[21]), "=f"(d[22]), "=f"(d[23]),
        "=f"(d[24]), "=f"(d[25]), "=f"(d[26]), "=f"(d[27]), "=f"(d[28]), "=f"(d[29]), "=f"(d[30]), "=f"(d[31]),
        "=f"(d[32]), "=f"(d[33]), "=f"(d[34]), "=f"(d[35]), "=f"(d[36]), "=f"(d[37]), "=f"(d[38]), "=f"(d[39]),
        "=f"(d[40]), "=f"(d[41]), "=f"(d[42]), "=f"(d[43]), "=f"(d[44]), "=f"(d[45]), "=f"(d[46]), "=f"(d[47]),
        "=f"(d[48]), "=f"(d[49]), "=f"(d[50]), "=f"(d[51]), "=f"(d[52]), "=f"(d[53]), "=f"(d[54]), "=f"(d[55]),
        "=f"(d[56]), "=f"(d[57]), "=f"(d[58]), "=f"(d[59]), "=f"(d[60]), "=f"(d[61]), "=f"(d[62]), "=f"(d[63]),
        "=f"(d[64]), "=f"(d[65]), "=f"(d[66]), "=f"(d[67]), "=f"(d[68]), "=f"(d[69]), "=f"(d[70]), "=f"(d[71]),
        "=f"(d[72]), "=f"(d[73]), "=f"(d[74]), "=f"(d[75]), "=f"(d[76]), "=f"(d[77]), "=f"(d[78]), "=f"(d[79]),
        "=f"(d[80]), "=f"(d[81]), "=f"(d[82]), "=f"(d[83]), "=f"(d[84]), "=f"(d[85]), "=f"(d[86]), "=f"(d[87]),
        "=f"(d[88]), "=f"(d[89]), "=f"(d[90]), "=f"(d[91]), "=f"(d[92]), "=f"(d[93]), "=f"(d[94]), "=f"(d[95])
      : "l"(da), "l"(db));
}

__device__ __forceinline__ void wgmma_n192_rs(float (&d)[96], uint32_t a0, uint32_t a1, uint32_t a23, uint64_t db) {
  asm volatile(
      "wgmma.mma_async.sync.aligned.m64n192k16.f32.bf16.bf16 {"
      "%0, %1, %2, %3, %4, %5, %6, %7, %8, %9, %10, %11, %12, %13, %14, %15, "
      "%16, %17, %18, %19, %20, %21, %22, %23, %24, %25, %26, %27, %28, %29, %30, %31, "
      "%32, %33, %34, %35, %36, %37, %38, %39, %40, %41, %42, %43, %44, %45, %46, %47, "
      "%48, %49, %50, %51, %52, %53, %54, %55, %56, %57, %58, %59, %60, %61, %62, %63, "
      "%64, %65, %66, %67, %68, %69, %70, %71, %72, %73, %74, %75, %76, %77, %78, %79, "
      "%80, %81, %82, %83, %84, %85, %86, %87, %88, %89, %90, %91, %92, %93, %94, %95}, "
      "{%96, %97, %98, %98}, %99, 1, 1, 1, 1;\n"
      :
        "+f"(d[0]), "+f"(d[1]), "+f"(d[2]), "+f"(d[3]), "+f"(d[4]), "+f"(d[5]), "+f"(d[6]), "+f"(d[7]),
        "+f"(d[8]), "+f"(d[9]), "+f"(d[10]), "+f"(d[11]), "+f"(d[12]), "+f"(d[13]), "+f"(d[14]), "+f"(d[15]),
        "+f"(d[16]), "+f"(d[17]), "+f"(d[18]), "+f"(d[19]), "+f"(d[20]), "+f"(d[21]), "+f"(d[22]), "+f"(d[23]),
        "+f"(d[24]), "+f"(d[25]), "+f"(d[26]), "+f"(d[27]), "+f"(d[28]), "+f"(d[29]), "+f"(d[30]), "+f"(d[31]),
        "+f"(d[32]), "+f"(d[33]), "+f"(d[34]), "+f"(d[35]), "+f"(d[36]), "+f"(d[37]), "+f"(d[38]), "+f"(d[39]),
        "+f"(d[40]), "+f"(d[41]), "+f"(d[42]), "+f"(d[43]), "+f"(d[44]), "+f"(d[45]), "+f"(d[46]), "+f"(d[47]),
        "+f"(d[48]), "+f"(d[49]), "+f"(d[50]), "+f"(d[51]), "+f"(d[52]), "+f"(d[53]), "+f"(d[54]), "+f"(d[55]),
        "+f"(d[56]), "+f"(d[57]), "+f"(d[58]), "+f"(d[59]), "+f"(d[60]), "+f"(d[61]), "+f"(d[62]), "+f"(d[63]),
        "+f"(d[64]), "+f"(d[65]), "+f"(d[66]), "+f"(d[67]), "+f"(d[68]), "+f"(d[69]), "+f"(d[70]), "+f"(d[71]),
        "+f"(d[72]), "+f"(d[73]), "+f"(d[74]), "+f"(d[75]), "+f"(d[76]), "+f"(d[77]), "+f"(d[78]), "+f"(d[79]),
        "+f"(d[80]), "+f"(d[81]), "+f"(d[82]), "+f"(d[83]), "+f"(d[84]), "+f"(d[85]), "+f"(d[86]), "+f"(d[87]),
        "+f"(d[88]), "+f"(d[89]), "+f"(d[90]), "+f"(d[91]), "+f"(d[92]), "+f"(d[93]), "+f"(d[94]), "+f"(d[95])
      : "r"(a0), "r"(a1), "r"(a23), "l"(db));
}

__device__ __forceinline__ uint32_t pack_bf16(float lo, float hi) {
  uint32_t r;
  asm("cvt.rn.bf16x2.f32 %0, %1, %2;" : "=r"(r) : "f"(hi), "f"(lo));
  return r;
}
__device__ __forceinline__ float bf_lo(uint32_t v) { return __uint_as_float(v << 16); }
__device__ __forceinline__ float bf_hi(uint32_t v) { return __uint_as_float(v & 0xFFFF0000u); }
__device__ __forceinline__ float ex2(float x) { float r; asm("ex2.approx.ftz.f32 %0, %1;" : "=f"(r) : "f"(x)); return r; }
__device__ __forceinline__ float rcp(float x) { float r; asm("rcp.approx.ftz.f32 %0, %1;" : "=f"(r) : "f"(x)); return r; }
__device__ __forceinline__ uint32_t movm(uint32_t a) {
  uint32_t d;
  asm volatile("movmatrix.sync.aligned.m8n8.trans.b16 %0, %1;" : "=r"(d) : "r"(a));
  return d;
}
__device__ __forceinline__ void mma16816(float (&c)[4], uint32_t a0, uint32_t a1, uint32_t a2, uint32_t a3, uint32_t b0, uint32_t b1) {
  asm volatile("mma.sync.aligned.m16n8k16.row.col.f32.bf16.bf16.f32 {%0,%1,%2,%3}, {%4,%5,%6,%7}, {%8,%9}, {%0,%1,%2,%3};"
               : "+f"(c[0]), "+f"(c[1]), "+f"(c[2]), "+f"(c[3]) : "r"(a0), "r"(a1), "r"(a2), "r"(a3), "r"(b0), "r"(b1));
}
__device__ __forceinline__ void mma1688(float (&c)[4], uint32_t a0, uint32_t a1, uint32_t b0) {
  asm volatile("mma.sync.aligned.m16n8k8.row.col.f32.bf16.bf16.f32 {%0,%1,%2,%3}, {%4,%5}, {%6}, {%0,%1,%2,%3};"
               : "+f"(c[0]), "+f"(c[1]), "+f"(c[2]), "+f"(c[3]) : "r"(a0), "r"(a1), "r"(b0));
}
__device__ __forceinline__ void stsm4(uint32_t addr, uint32_t a, uint32_t b, uint32_t c, uint32_t d) {
  asm volatile("stmatrix.sync.aligned.m8n8.x4.shared.b16 [%0], {%1,%2,%3,%4};" ::"r"(addr), "r"(a), "r"(b), "r"(c), "r"(d) : "memory");
}
__device__ __forceinline__ void stsm4_t(uint32_t addr, uint32_t a, uint32_t b, uint32_t c, uint32_t d) {
  asm volatile("stmatrix.sync.aligned.m8n8.x4.trans.shared.b16 [%0], {%1,%2,%3,%4};" ::"r"(addr), "r"(a), "r"(b), "r"(c), "r"(d) : "memory");
}
__device__ __forceinline__ void ldsm4(uint32_t addr, uint32_t (&v)[4]) {
  asm volatile("ldmatrix.sync.aligned.m8n8.x4.shared.b16 {%0,%1,%2,%3}, [%4];"
               : "=r"(v[0]), "=r"(v[1]), "=r"(v[2]), "=r"(v[3]) : "r"(addr) : "memory");
}
__device__ __forceinline__ void sts128(uint32_t addr, uint4 v) {
  asm volatile("st.shared.v4.b32 [%0], {%1,%2,%3,%4};" ::"r"(addr), "r"(v.x), "r"(v.y), "r"(v.z), "r"(v.w) : "memory");
}
__device__ __forceinline__ uint4 lds128(uint32_t addr) {
  uint4 v;
  asm volatile("ld.shared.v4.b32 {%0,%1,%2,%3}, [%4];" : "=r"(v.x), "=r"(v.y), "=r"(v.z), "=r"(v.w) : "r"(addr) : "memory");
  return v;
}
__device__ __forceinline__ void sts64(uint32_t addr, uint32_t a, uint32_t b) {
  asm volatile("st.shared.v2.b32 [%0], {%1,%2};" ::"r"(addr), "r"(a), "r"(b) : "memory");
}
__device__ __forceinline__ void sts32(uint32_t addr, uint32_t a) { asm volatile("st.shared.b32 [%0], %1;" ::"r"(addr), "r"(a) : "memory"); }
__device__ __forceinline__ uint32_t lds32(uint32_t addr) {
  uint32_t v;
  asm volatile("ld.shared.b32 %0, [%1];" : "=r"(v) : "r"(addr) : "memory");
  return v;
}
__device__ __forceinline__ float2 lds64f_const(uint32_t addr) {
  float2 v;
  asm("ld.shared.v2.f32 {%0,%1}, [%2];" : "=f"(v.x), "=f"(v.y) : "r"(addr));
  return v;
}
template <int N, bool PAIR>
__device__ __forceinline__ void load_tagged(uint3 (&out)[N], const uint4* src, int stride, uint32_t tag, const uint4* last = nullptr) {
  uint32_t bad;
  int spins = 0;
#pragma unroll 1
  do {
    if (++spins > 2000000) __trap();
    bad = 0;
#pragma unroll
    for (int i = 0; i < N; i++) {
      const uint4 v = ld_b128(N == 5 && i == 4 ? last : src + i * stride);
      out[i] = make_uint3(v.x, v.y, v.z);
      bad |= (v.w ^ tag) | (PAIR ? v.z ^ tag : 0);
    }
    if (N == 4) bad = __any_sync(~0u, bad != 0);
    if (bad) __nanosleep(kBackoffNs);
  } while (bad);
}
__device__ __forceinline__ void sts64f(uint32_t addr, float2 v) { sts64(addr, __float_as_uint(v.x), __float_as_uint(v.y)); }
__device__ __forceinline__ float bf_rest(float v) { return v - __uint_as_float(__float_as_uint(v) & 0xFFFF0000u); }
__device__ __forceinline__ uint32_t bf_upper(float lo, float hi) { return __byte_perm(__float_as_uint(lo), __float_as_uint(hi), 0x7632); }
__device__ __forceinline__ float low_peak(uint4 v) {
  asm("max.xorsign.abs.bf16x2 %0, %0, %1;" : "+r"(v.x) : "r"(v.y));
  asm("max.xorsign.abs.bf16x2 %0, %0, %1;" : "+r"(v.z) : "r"(v.w));
  asm("max.xorsign.abs.bf16x2 %0, %0, %1;" : "+r"(v.x) : "r"(v.z));
  asm("max.xorsign.abs.bf16x2 %0, %0, %1;" : "+r"(v.x) : "r"(v.x << 16));
  return __uint_as_float(__reduce_min_sync(~0u, v.x & 0x7FFF0000u));
}
__device__ __forceinline__ float bias_at(float v) { return __uint_as_float((__float_as_uint(fminf(v, 1e37f)) & 0x7F800000u) | 0x00400000u); }
__device__ __forceinline__ float copy_of(uint32_t v, uint32_t zero, int id) {
  float r;
  asm("{\n.reg .b32 t;\nlop3.b32 t, %1, %2, %3, 0xEA;\nmov.b32 %0, t;\n}\n" : "=f"(r) : "r"(zero), "r"(id + 1), "r"(v));
  return r;
}
struct RowConst {
  float k0, k1, half;
};
__device__ __forceinline__ float gate_scale(float t, const RowConst& k) {
  float th;
  asm("tanh.approx.f32 %0, %1;" : "=f"(th) : "f"(t * fmaf(t * t, k.k1, k.k0)));
  return fmaf(th, k.half, k.half);
}

template <int N>
__device__ __forceinline__ void mma_k16(float (&acc)[2][96], uint32_t a, uint32_t b, int kk, int add = 1) {
#pragma unroll
  for (int m = 0; m < 2; m++) {
    const uint64_t da = desc(a) + (m * 512 + kk * 2), db = desc(b) + kk * 128;
    if (N == 128) wgmma_n128(acc[m], da, db); else wgmma_n192(acc[m], da, db, add);
  }
}

__device__ __forceinline__ void stage_quarter(const float* acc, uint32_t frag, uint32_t frag_x, int b, const uint4* add = nullptr) {
#pragma unroll
  for (int j = 0; j < 4; j++) {
    const float* v = acc + 8 * j;
    uint32_t h[4] = {pack_bf16(v[0], v[1]), pack_bf16(v[2], v[3]), pack_bf16(v[4], v[5]), pack_bf16(v[6], v[7])};
    if (add) {
      const uint32_t a[4] = {add[j].x, add[j].y, add[j].z, add[j].w};
#pragma unroll
      for (int e = 0; e < 4; e++) asm("add.rn.bf16x2 %0, %0, %1;" : "+r"(h[e]) : "r"(a[e]));
    }
    stsm4(frag + b * 8192 + ((frag_x ^ (j * 2)) << 4), h[0], h[1], h[2], h[3]);
  }
}

inline int g1_block(int j, int c) { return j < 16 ? j : ((j + 12) & 15) ^ (c == 5 && j >= 28 ? 2 : 0); }
inline int g2_block(int j, int c) { return j < 8 ? j : j == 8 ? 8 + c : j - (j - 9 < c); }
inline int g3_tile(int j) { return j < 4 ? j >> 1 : j < 18 ? 0 : j >> 4; }
inline int g3_block(int j, int c) {
  const int i = j < 32 ? (j < 16 ? 0xDCBA976543218080ull : 0x7654321BA9FEDCFEull) >> 4 * (j & 15) : j + (~j >> 2 & 4), o = i & 7;
  return 2 * (j < 32 && (o == c || o == 0) ? c - o : o) + (i >> 3 & 1);
}
inline int g4_block(int i) {
  const int n = i * 43 >> 7, j = i - 3 * n, m = j ? n : n + (16 - kFirstShared / 3);
  return i < 48 ? 7 * (m & 7) + 3 * (m >> 3 & 1) + j : 7 * i - 330;
}

constexpr int kInPlace = 16, kInO = 64, kMark = 128;

template <int N, int TAIL>
__device__ __forceinline__ void mainloop(Scratch* sc, float (&acc)[2][96], uint32_t sb, int ph, int j0, int nsteps, int pause_at, bool last,
                                         bool hand_over, bool local, int wg, int own = -1, const CUtensorMap* out = nullptr, int out_col = 0,
                                         int out_row = 0, int warp = 0, __nv_bfloat16* outp = nullptr) {
  constexpr int NSLOT = N == 128 ? 5 : 4, SLOT = N == 128 ? 32768 : 40960;
  const int lane = fresh_tid() & 31;
  const uint32_t full = sb + kBars + 8 * ring_base(ph);
  const uint32_t empty = map_cta(full + 8 * (NSLOT + (ph == 3)), lane & 1);
  const uint32_t ring = desc_lo(sb + kRing, 16);
  int bi = j0 % NSLOT, par = (j0 / NSLOT) & 1;
  const int release_end = lane < (N == 192 && !hand_over ? 4 : 2) ? (last ? nsteps - 1 - NSLOT : nsteps) : 0;
  uint32_t rel = empty;
  const uint32_t special = ph == 0 && wg == 0 ? 3 : pause_at < 0 ? 1 : 1 | 2 << pause_at;
  int i = 0;
#pragma unroll 1
  for (;;) {
    const int end = TAIL <= 0 ? nsteps : !own ? nsteps - TAIL - 1 : i ? i + 2 : kFirstShared;
#pragma unroll 1
    do {
      uint32_t a = ring + bi * (SLOT >> 4), b = a + kToB;
      if (TAIL > 0 ? i == 0 : special >> i & 1) {
        if (i == 0) nb_sync(kNbOrder + wg, ph == 0 && wg == 0 ? 160 : 256);
        else if (ph == 0 && wg == 0) cluster_wait();
        else if (ph < 2) nb_sync(kNbWin + 1, 256);
      }
      if (N == 192 && local) {
        a = ring + ((kStage + i * 16384) >> 4);
        b = ring + bi * (32768 >> 4) + desc_lo(32768, 8192) - desc_lo(0, 16);
      }
      if (ph == 0 && i >> 1 == own) a = ring + ((kOwn + (i & 1) * 16384) >> 4);
      if (ph == 1 && i == 8) a = ring + ((kStage + 32768) >> 4);
      mbar_wait(full + 8 * bi, par);
      if (N == 192 && local) mbar_wait(sb + kBars + 8 * (kHalfBar + i), 0);
      const bool release = (uint32_t)(i - 1) < (uint32_t)release_end;
      wg_fence();
      mma_k16<N>(acc, a, b, 0, ph == 0 ? i | wg : 1);
      mma_k16<N>(acc, a, b, 1);
      wg_commit();
      wg_wait<1>();
      mbar_arrive_cluster_if(rel, release);
      wg_fence();
      mma_k16<N>(acc, a, b, 2);
      mma_k16<N>(acc, a, b, 3);
      wg_commit();
      rel = empty + 8 * bi;
      if (++bi == NSLOT + (TAIL > 0 && i >= kWide - 16)) { bi = 0; par ^= 1; }
      if (ph < 2 && i == pause_at) nb_arrive(kNbWin, 256);
    } while (++i < end);
    if (TAIL <= 0 || own-- == 0) break;
    const uint32_t a = ring + bi * (SLOT >> 4);
    mbar_wait(full + 8 * bi, par);
    wg_fence();
#pragma unroll
    for (int k = 0; k < 4; k++) wgmma_n128(acc[1], desc(a) + (512 + k * 2), desc(a + kToB) + k * 128);
    wg_commit();
    wg_wait<1>();
    mbar_arrive_cluster_if(rel, lane < 2);
    rel = empty + 8 * bi;
    if (++bi == NSLOT + 1) { bi = 0; par ^= 1; }
    i++;
  }
  if (TAIL < 0) return;
  if (TAIL > 0) {
    uint32_t at[TAIL + 2];
    bi = par = 0;
    const int t = fresh_tid() & 127;
    uint32_t frag = sb + kStage + ((t >> 5) * 16 + (t & 15)) * 128, frag_x = ((t >> 4) & 1) ^ (t & 7);
    const uint32_t back = sb + kStage + (t >> 5) * 2048 + ((t >> 3) & 3) * 128, back_x = ((t ^ (t >> 3 & 3)) & 7) << 4;
    outp = plus(outp, (2 * (out_row + (t >> 5) * 16 + ((t >> 3) & 3)) + (blockIdx.x & 1)) * kD + out_col + (t & 7) * 8);
    auto rows = [&](int m, int i0, int i1) {
      wg_fence();
#pragma unroll
      for (int i = 4 * i0; i < 4 * i1; i++)
        wgmma_n128(acc[m], desc_kept(ring, sb) + (at[i >> 2] + m * 512 + (i & 3) * 2), desc_kept(ring, sb) + (at[i >> 2] + kToB + (i & 3) * 128));
      wg_commit();
    };
    uint4 part[8];
#pragma unroll
    for (int i = 0; i <= TAIL; i++) {
      at[i] = bi * (SLOT >> 4);
      mbar_wait(full + 8 * bi, par);
      if (++bi == NSLOT) { bi = 0; par ^= 1; }
      rows(0, i, i + 1);
      if (i == kPartAt) nb_sync(kNbPart, 256);
      if (i == kPartAt || i == kPartAt + 1) {
#pragma unroll
        for (int k = 4 * (i - kPartAt); k < 4 * (i - kPartAt + 1); k++) part[k] = lds128(sb + kStage + 32768 + (t >> 5) * 4096 + (t & 31) * 16 + k * 512);
      }
    }
    rows(1, 0, 2);
#pragma unroll
    for (int b = 0; b < 4; b++) {
      if (b == 0) wg_wait<1>();
      if (b == 1) rows(1, 3, 4);
      if (b == 2) wg_wait<0>();
      if (!(b & 1)) {
#pragma unroll
        for (int i = 0; i < 64; i++) asm volatile("" : "+f"(acc[b >> 1][i])::"memory");
        if (t == 0) TSS(b);
      }
      stage_quarter(&acc[b >> 1][32 * (b & 1)], frag, frag_x, b, b < 2 ? &part[4 * b] : nullptr);
      if (b == 3) {
        __syncwarp();
        uint4 v[4];
#pragma unroll
        for (int i = 0; i < 4; i++) v[i] = lds128(back + b * 8192 + i * 512 + ((i & 1) ? back_x ^ 64 : back_x));
#pragma unroll
        for (int i = 0; i < 4; i++) __stcs((uint4*)(outp + ((b >> 1) * 128 + i * 8) * kD + (b & 1) * 64), v[i]);
        if (t == 0) TSS(4 + b);
        continue;
      }
      if (b < 2) rows(1, 2 + 2 * b, 3 + 2 * b);
      fence_async_smem();
      __syncwarp();
      if (elect_one()) tma_store3d(out, sb + kStage + b * 8192 + warp * 2048, out_col + (b & 1) * 64, out_row + (b >> 1) * 64 + warp * 16, blockIdx.x & 1);
      __syncwarp();
      if (t == 0) TSS(4 + b);
    }
    if (elect_one()) {
      bulk_commit();
      bulk_wait_read();
    }
    if (t == 0) TSS(1);
    return;
  }
  if (hand_over) nb_arrive(kNbOrder + (wg ^ 1), 256);
  if (N == 192 && !local) {
    if (j0 < 32) mbar_wait(sb + kBars + 8 * kStatBar, 1);
    mbar_wait(sb + kBars + 8 * (kStgBar + wg), ((j0 >> 5) ^ wg ^ 1) & 1);
  }
  wg_wait<0>();
  mbar_arrive_cluster_if(rel, release_end == nsteps);
#pragma unroll
  for (int i = 0; i < N / 2; i++) asm volatile("" : "+f"(acc[0][i]), "+f"(acc[1][i])::"memory");
}

template <int PH>
struct Ring {
  static constexpr int NSLOT = 4 + (PH & 1), SLOT = PH & 1 ? 32768 : 40960;
  uint32_t full, dst0;
  int j = PH == 0 ? 4 : 0, bi = 0, par = PH == 0 ? 0 : 1;
  __device__ __forceinline__ Ring(uint32_t sb, uint32_t ofs) : full(sb + kBars + 8 * (PH * 9 - (PH & 1))), dst0(sb + kRing + ofs) {}
  __device__ __forceinline__ uint32_t bar() const { return full + 8 * bi; }
  __device__ __forceinline__ uint32_t dst() const { return dst0 + bi * SLOT; }
  __device__ __forceinline__ void acquire_first() const {
    const bool first = j < NSLOT;
    mbar_wait(full + (first ? 8 * min(j, 3) - 32 : 8 * (NSLOT + (PH == 3) + bi)), PH == 2 && first ? 0 : par);
  }
  __device__ __forceinline__ void acquire() const { mbar_wait(full + 8 * (NSLOT + (PH == 3) + bi), par); }
  __device__ __forceinline__ void next() {
    j++;
    if (++bi == NSLOT + (PH == 3 && j > kWide)) { bi = 0; par ^= 1; }
  }
};

__device__ __forceinline__ void check_blocks(const Params& p, Scratch* sc, uint32_t sb, int r, int c, bool g3, uint32_t& par) {
  const int lane = fresh_tid() & 31, nslot = g3 ? 4 : 5, slot_bytes = g3 ? 40960 : 32768;
  const uint32_t mine = (lane >> 2) * 132 + (lane & 3) * 32, ring_end = sb + kRing + kStage + mine;
  const uint32_t to_full = 8 * (kLandBar - (g3 ? ring_base(2) : ring_base(1)));
  uint32_t src = sb + kRing + mine + (g3 ? 0 : 4 * 32768);
  int bi = g3 ? 0 : 4, spins = 0;
#pragma unroll 1
  for (int i = g3 ? 2 : 9; i < 16;) {
    const uint32_t land = sb + kBars + 8 * (kLandBar + bi);
    mbar_wait(land, (par >> bi) & 1);
    uint32_t v[16];
#pragma unroll
    for (int k = 0; k < 16; k++) v[k] = lds32(src + k * 1024);
#pragma unroll
    for (int k = 0; k < 5; k++) v[k] = max(max(v[3 * k + 1], v[3 * k + 2]), k ? v[3 * k] : max(v[0], v[15]));
    const bool again = __any_sync(~0u, max(max(max(v[0], v[1]), v[2]), max(v[3], v[4])) == kPoison);
    asm volatile("{\n.reg .pred p;\nsetp.eq.u32 p, %1, 0;\n@p mbarrier.arrive.shared::cta.b64 _, [%0];\n}\n"
                 ::"r"(land - to_full), "r"(lane + again) : "memory");
    par ^= 1u << bi;
    if (again) {
      if (++spins > 100000) __trap();
      if (elect_one()) {
        mbar_expect_tx(land, 16384);
        tma2d(src - mine, g3 ? &p.h : &p.o, ((g3 ? p.g3[c][i + 2] : p.g2[c][i]) & 15) * 64, r * 128, land);
      }
      nb_sync(kNbSelf + 1, 32);
      continue;
    }
    if (lane == 0 && (i == 2 || i == 3 || (!g3 && (i == 9 || i == 12)))) TS(i < 4 ? 88 + 2 * i : i == 9 ? 120 : 122);
    i++;
    if (++bi == nslot) bi = 0;
    src += slot_bytes;
    if (src == ring_end) src -= kStage;
  }
}

__device__ __forceinline__ void colsum_cta(const Params& p, Scratch* sc, uint32_t sb, int warp, int bid) {
  constexpr int kSlots = 4, kSlot = 49152;
  constexpr int kRows = kMost * 16384, kIn = (kCs - kRows) / 8192;
  const int lane = threadIdx.x & 31, c0 = (bid - 128) * 2;
  const uint32_t full = sb + kBars, empty = full + 8 * kSlots;
  const uint32_t event = full + 64, rfull = full + 128, rempty = full + 256;
  if (threadIdx.x == 0) {
#pragma unroll 1
    for (int i = 0; i < 48; i++) mbar_init(full + 8 * i, i & (i < 16 ? 4 : 32) ? 8 : 1);
    asm volatile("fence.mbarrier_init.release.cluster;" ::: "memory");
  }
  __syncthreads();
  const uint32_t ep = ld_epoch(sc);
  if (warp == 8) {
    if (elect_one()) {
#pragma unroll 1
      for (int n = 0; n < 32 + kSlots; n++) {
        const int u = n >> 4, c = c0 + ((n >> 3) & 1), k0 = (n & 7) * 128, slot = n & (kSlots - 1);
        const uint32_t bar = full + 8 * slot;
        mbar_wait(empty + 8 * slot, ((n / kSlots) & 1) ^ 1);
        if (u == 2) continue;
        mbar_expect_tx(bar, 49152);
#pragma unroll
        for (int a = 0; a < 6; a++) tma2d(sb + slot * kSlot + a * 8192, &p.wqkv, ((a % 3) * 16 + u * 8 + c) * 64, k0 + (a / 3) * 64, bar);
      }
      mbar_arrive(event);
#pragma unroll 1
      for (int i = 0; i < 4 * kMost; i++) tma_prefetch2d(&p.wd, (c0 * 2 + (i & 3)) * 64, (i >> 2) * (7 * 64));
      mbar_wait(event + 8, 0);
      asm volatile("fence.proxy.async.global;" ::: "memory");
      int slot = 0, par = 1, w = 0;
#pragma unroll 1
      for (int job = 0; job < 32; job++) {
        const int k = lds32(sb + kPlan + (job >> 4) * 4) >> (job & 14) * 2 & 15;
        if (job == 16) {
          mbar_wait(rempty + 8 * (slot ? slot - 1 : kIn - 1), par ^ (slot != 0));
          w = 0;
        }
#pragma unroll 1
        for (int i = 0; i < k; i++) {
          const uint32_t bar = rfull + 8 * slot;
          mbar_wait(bar + 128, par);
          mbar_expect_tx(bar, w < kMost ? 24576 : 8192);
          tma2d(sb + kRows + slot * 8192, &p.ost, i * 64, (job & 15) * 128, bar);
          if (w < kMost) {
#pragma unroll
            for (int a = 0; a < 2; a++)
              tma2d(sb + w * 16384 + a * 8192, &p.wd, ((c0 + (job >> 4)) * 2 + a) * 64, w * (7 * 64), bar);
            w++;
          }
          if (++slot == kIn) { slot = 0; par ^= 1; }
        }
      }
    }
  } else if (warp < 8) {
    uint32_t src[3];
#pragma unroll
    for (int j = 0; j < 3; j++) src[j] = sb + ((warp * 3 + j) >> 3) * 8192 + lane * 128 + ((((warp * 3 + j) & 7) ^ (lane & 7)) << 4);
    const uint32_t ones = 0x3F803F80u;
#pragma unroll 1
    for (int s = 0; s < 32; s++) {
      float a[3][2][4] = {};
#pragma unroll 1
      for (;; s++) {
        const int slot = s & (kSlots - 1);
        mbar_wait(full + 8 * slot, (s / kSlots) & 1);
        uint32_t b[3][4][4];
#pragma unroll
        for (int j = 0; j < 3; j++)
#pragma unroll
          for (int k = 0; k < 4; k++)
            asm volatile("ldmatrix.sync.aligned.m8n8.x4.trans.shared.b16 {%0,%1,%2,%3}, [%4];"
                         : "=r"(b[j][k][0]), "=r"(b[j][k][1]), "=r"(b[j][k][2]), "=r"(b[j][k][3])
                         : "r"(src[j] + slot * kSlot + (k >> 1) * 24576 + (k & 1) * 4096) : "memory");
        __syncwarp();
        if (lane == 0) mbar_arrive(empty + 8 * slot);
#pragma unroll
        for (int k = 0; k < 4; k++)
#pragma unroll
          for (int j = 0; j < 3; j++) {
            mma16816(a[j][0], ones, ones, ones, ones, b[j][k][0], b[j][k][1]);
            mma16816(a[j][1], ones, ones, ones, ones, b[j][k][2], b[j][k][3]);
          }
        if ((s & 7) == 7) break;
      }
      {
        if (lane < 12) {
          const int j = lane >> 2;
          const float x = j == 0 ? a[0][0][0] + a[0][1][0] : j == 1 ? a[1][0][0] + a[1][1][0] : a[2][0][0] + a[2][1][0];
          const float y = j == 0 ? a[0][0][1] + a[0][1][1] : j == 1 ? a[1][0][1] + a[1][1][1] : a[2][0][1] + a[2][1][1];
          const float x1 = bf_rest(x), y1 = bf_rest(y);
          st_b128(SC_AT(cs, ((s >> 4) * 8 + c0 + ((s >> 3) & 1)) * 96 + warp * 12 + lane), bf_upper(x, y),
                  bf_upper(x1, y1), bf_upper(bf_rest(x1), bf_rest(y1)), ep);
        }
        if (threadIdx.x == 0 && (s & 8)) TSK(s >> 4);
      }
    }
    const int wg = warp >> 2;
    mbar_wait(event + 8, 0);
#pragma unroll 1
    for (int job = wg, first = 0; job < 32; job += 2) {
      const int k = __shfl_sync(~0u, lds32(sb + kPlan + (job >> 4) * 4), 0) >> (job & 14) * 2 & 15;
      if (k == 0) continue;
      float acc[96];
#pragma unroll
      for (int i = 0; i < 64; i++) asm volatile("" : "=f"(acc[i]));
      static_assert(kIn == 12, "");
      int slot = first + wg * k, par = slot * 171 >> 11, i = 0;
      slot -= par * kIn;
      first += 2 * k;
      uint32_t done = 0;
      if (job) nb_sync(kNbOrder + wg, 256);
#pragma unroll 1
      do {
        mbar_wait(rfull + 8 * slot, par & 1);
        wg_fence();
#pragma unroll
        for (int kk = 0; kk < 4; kk++)
          wgmma_n128(acc, desc(desc_lo(sb + kRows, 16) + slot * 512) + kk * 2, desc(desc_lo(sb, 8192) + i * 1024) + kk * 128, kk | i);
        wg_commit();
        wg_wait<1>();
        if (lane < 2 && i) mbar_arrive(done);
        done = rempty + 8 * slot;
        if (++slot == kIn) { slot = 0; par++; }
      } while (++i < k);
      nb_arrive(kNbOrder + (wg ^ 1), 256);
      uint4* dst = SC_AT(part, ((job & 15) * 8 + c0 + (job >> 4)) * 1024 + (warp & 3) * 256 + lane);
      wg_wait<0>();
#pragma unroll
      for (int i = 0; i < 64; i++) asm volatile("" : "+f"(acc[i])::"memory");
      if (lane < 2) mbar_arrive(done);
#pragma unroll
      for (int i = 0; i < 8; i++) {
        const float* v = &acc[8 * i];
        asm volatile("st.relaxed.gpu.global.v4.b32 [%0], {%1, %2, %3, %4};"
                     ::"l"(dst + i * 32),
                     "r"(pack_bf16(v[0], v[1])), "r"(pack_bf16(v[2], v[3])), "r"(pack_bf16(v[4], v[5])), "r"(pack_bf16(v[6], v[7])) : "memory");
      }
    }
    if (threadIdx.x == 128) TSK(7);
  } else if (warp == 10) {
    mbar_wait(event, 0);
    int late = await_word<500>(sc->finish + (uint32_t)((lane & 15) * 8 + c0 + (lane >> 4)), ep);
    __nanosleep(1000);
    flag_wait(sc->flags + kFlHH + (lane & 15) * kFlRow, ep * 8);
    __syncwarp();
    late -= __shfl_sync(~0u, late, 0);
    late = max(late, __shfl_xor_sync(~0u, late, 1));
    late = max(min(late - (__reduce_add_sync(~0u, late) >> 5) + kShare * kStepNs, 4096), -4096);
    int k;
#pragma unroll 1
    do {
      k = min(max((late * (8192 / kStepNs) >> 13) + 1, (lane & 14) == 0), kMost);
      late -= kStepNs / 4;
    } while (__reduce_add_sync(~0u, k ? max(2 * k, k + 4) : 0) > kBudget);
    k <<= (lane & 14) * 2;
#pragma unroll
    for (int o = 2; o < 16; o <<= 1) k |= __shfl_xor_sync(~0u, k, o);
    asm volatile("fence.acquire.gpu;" ::: "memory");
    send_word(sc->plan + (uint32_t)(c0 + (lane >> 4)), k, ep);
    sts32(sb + kPlan + (lane >> 4) * 4, k);
    __syncwarp();
    if (lane == 0) mbar_arrive(event + 8);
  }
}

#define PROF_BEGIN
template <bool BY_SM>
__global__ void __cluster_dims__(2, 1, 1) __launch_bounds__(kThreads, 1) fused_block_kernel(Scratch* sc, const __nv_bfloat16* xp, const __nv_bfloat16* wqkvp, __nv_bfloat16* outp,
                                                                   const __grid_constant__ Params p) {
  extern __shared__ __align__(1024) uint8_t smem_raw[];
  if (threadIdx.x == 256) {
    prefetch_map(&p.x);
    prefetch_map(&p.wqkv);
  }
  if (threadIdx.x < 56) {
    const int l = threadIdx.x & 31, b = blockIdx.x & 127;
    if (threadIdx.x < 32) prefetch_l2(xp + (b * 16 + (l & 15)) * kD + (l >> 4) * 64);
    else prefetch_l2(wqkvp + b * (3 * kD) + (l >> 3) * kD + (l & 7) * 64);
  }
  const uint32_t sb = smem_u32(smem_raw);
  const int bid = role_id<BY_SM>();
  const int r = bid >> 3, c = bid & 7, rank = blockIdx.x & 1;
  auto first_fill = [&](int j) {
    const uint32_t fb = sb + kBars + 8 * j, dst = sb + kRing + j * 40960;
    mbar_expect_tx(fb, 40960);
    tma3d(j >> 1 == c ? sb + kOwn + (j & 1) * 16384 : dst, &p.x, j * 64, (r >> 1) * 128, rank, fb);
#pragma unroll
    for (int a = 0; a < 3; a++) tma2d(dst + 16384 + a * 8192, &p.wqkv, a * kD + c * 64, j * 64, fb);
    mbar_arrive(fb);
  };
  const int tid = threadIdx.x, warp = __shfl_sync(~0u, tid >> 5, 0), wg = warp >> 2;
  if (bid >= 128) {
    if (tid == 0) PROF_BEGIN;
    colsum_cta(p, sc, sb, warp, bid);
    return;
  }
  if (wg == 2) {
    if (warp == 8 && elect_one()) {
      mbar_init(sb + kBars, 2);
      asm volatile("fence.mbarrier_init.release.cluster;" ::: "memory");
      first_fill(0);
#pragma unroll
      for (int j = 1; j < 4; j++) mbar_init(sb + kBars + 8 * j, 2);
      asm volatile("fence.mbarrier_init.release.cluster;" ::: "memory");
      TSS(0);
    }
    __syncwarp();
    if (warp == 8) nb_arrive(kNbOrder, 160);
    asm volatile("setmaxnreg.dec.sync.aligned.u32 40;");
    if (warp == 8) {
      cluster_arrive();
      if (elect_one()) {
#pragma unroll 1
        for (int j = 1; j < 4; j++) first_fill(j);
        TSS(1);
      }
      __syncwarp();
    } else {
      if (elect_one()) {
        uint64_t shifts = warp == 9 ? bar_shifts(4) : warp == 10 ? bar_shifts(22) : bar_shifts(40);
#pragma unroll 1
        for (int i = 0; i < 18; i++, shifts >>= 3) mbar_init(sb + kBars + 8 * (18 * warp - 158 + i), 1u << (shifts & 7));
        if (warp == 10) asm volatile("mbarrier.arrive.shared::cta.b64 _, [%0], 2;" ::"r"(sb + kBars + 8 * 31) : "memory");
        sts32(sb + kZero, 0);
        sts32(sb + kScale + 4, 0);
        sts32(sb + kRole, bid);
        sts128(sb + kOnes, make_uint4(0x3F803F80u, 0, 0, 0x3F803F80u));
        asm volatile("fence.mbarrier_init.release.cluster;" ::: "memory");
      }
      __syncwarp();
      cluster_arrive();
    }
    cluster_wait();
    const uint32_t ep = ld_epoch(sc);
    if (tid == 320) sts32(sb + kEpoch, ep);
    if (tid == 320) PROF_BEGIN;
    const int pw = warp & 3;
    if (pw == 0) {
      if (elect_one()) {
        const int row = r * 128;
        const uint32_t land = sb + kBars + 8 * kLandBar;
#pragma unroll 1
        for (Ring<0> q(sb, 0); q.j < 32; q.next()) {
          q.acquire();
          const int kb = p.g1[c][q.j];
          if (kb & kInPlace) { mbar_arrive(q.bar()); continue; }
          mbar_expect_tx(q.bar(), 16384);
          tma3d(kb >> 1 == c ? sb + kOwn + (kb & 1) * 16384 : q.dst(), &p.x, kb * 64, (r >> 1) * 128, rank, q.bar());
        }
        prefetch_map(&p.o);
        prefetch_map(&p.o16);
        flag_wait(sc->flags + kFlO + r * kFlRow, ep * 8);
        fence_async();
        TS(40);
#pragma unroll 1
        for (Ring<1> q(sb, 0); q.j < 16; q.next()) {
          q.acquire_first();
          if (q.j == 8) {
            prefetch_map(&p.wg);
            prefetch_map(&p.wu);
            prefetch_map(&p.h);
            prefetch_map(&p.h16);
            mbar_wait(sb + kBars + 8 * kSentBar, 0);
            mbar_arrive(q.bar());
            mbar_arrive(sb + kBars + 8 * (kStgBar + 1));
            __nanosleep(kGateONs);
            continue;
          }
          const uint32_t bar = q.j < 8 ? q.bar() : land + 8 * q.bi;
          if (q.j == 9) TS(41);
          mbar_expect_tx(bar, 16384);
          tma2d(q.dst(), &p.o, p.g2[c][q.j] * 64, row, bar);
        }
#pragma unroll 1
        for (Ring<2> q(sb, 0); q.j < 64; q.next()) {
          q.acquire_first();
          const int kb = p.g3[c][q.j];
          if (kb & kInPlace) { mbar_arrive(q.bar()); continue; }
          if (q.j == 4) { __nanosleep(kGateHNs); TS(42); }
          const uint32_t bar = q.j < 18 ? land + 8 * q.bi : q.bar();
          mbar_expect_tx(bar, 16384);
          tma2d(q.dst(), &p.h, (kb & 15) * 64, row, bar);
        }
        prefetch_map(&p.hh);
        prefetch_map(&p.out);
        Ring<3> q(sb, 0);
#pragma unroll 1
        for (; q.j < 16; q.next()) {
          q.acquire_first();
          if (q.j == 0) { mbar_arrive(q.bar()); continue; }
          mbar_expect_tx(q.bar(), 16384);
          tma2d(q.dst(), &p.h, ((q.j + 9) & 15) * 64, row, q.bar());
        }
        uint32_t wave = sb + kBars + 8 * kWaveBar;
        mbar_wait(wave, 0);
        fence_async();
        int share = lds32(sb + kPlan);
#pragma unroll 1
        for (; q.j < 72; q.next()) {
          const int kb = p.g4in[q.j - 16];
          if (kb >> 6 == kMark >> 6) {
            wave += 8;
            mbar_wait(wave, 0);
            fence_async();
          }
          q.acquire();
          const bool half = kb >= (kMark | kInO) && --share >= 0;
          mbar_expect_tx(q.bar(), half ? 8192 : 16384);
          tma2d(q.dst() + half * 8192, half ? &p.ost : kb & kInO ? &p.o : &p.hh, (kb & 63) * 64, row + half * 64, q.bar());
        }
      }
    } else if (pw == 1) {
      if (elect_one()) {
        const int rp = r >> 1;
#pragma unroll 1
        for (Ring<0> q(sb, 16384); q.j < 32; q.next()) {
          q.acquire();
          mbar_expect_tx(q.bar(), 24576);
          const int col = ((q.j >> 4) * 8 + c) * 64, k0 = (p.g1[c][q.j] & 15) * 64;
          tma2d_mc(q.dst() + rank * 8192, &p.wqkv, rank * kD + col, k0, q.bar());
          if ((q.j & 1) == rank) tma2d_mc(q.dst() + 16384, &p.wqkv, 2 * kD + col, k0, q.bar());
          if (q.j == max(r, 4))
            for (int a = 0; a < 3; a++) tma_prefetch2d(&p.wqkv, a * kD + (8 + c) * 64, ((r + 12) & 15) * 64);
          const int d = q.j - kPfG1 - (r >> 2);
          if (d == 0 || d == 6) {
            const int f = c * 7 + (d >> 1);
            tma_prefetch2d(&p.wg, f * 64, r * 64);
            tma_prefetch2d(&p.wu, f * 64, r * 64);
            tma_prefetch2d(&p.wg, (f + 1) * 64, r * 64);
          }
        }
#pragma unroll 1
        for (Ring<1> q(sb, 16384 + rank * 8192); q.j < 16; q.next()) {
          q.acquire_first();
          mbar_expect_tx(q.bar(), 16384);
          tma2d_mc(q.dst(), &p.wo, (c * 2 + rank) * 64, p.g2[c][q.j] * 64, q.bar());
        }
        const CUtensorMap* mine = rank ? &p.wu : &p.wg;
#pragma unroll 1
        for (Ring<2> q(sb, 16384); q.j < 64; q.next()) {
          const int kb = p.g3[c][q.j], tile = kb >> 5, f0 = c * 7 + (tile & 1) * 3, fp = f0 + (tile & 2);
          const int k0 = (kb & 15) * 64;
          q.acquire_first();
          mbar_expect_tx(q.bar(), 24576);
          const uint32_t dst = q.j < 4 ? sb + kRing + (q.j + 1) * 32768 : q.dst();
          tma2d_mc(dst + rank * 8192, mine, fp * 64, k0, q.bar());
          if ((q.j & 1) == rank) tma2d_mc(dst + 16384, tile & 2 ? &p.wu : &p.wg, (f0 + 1) * 64, k0, q.bar());
          const int d = q.j - kPfG3 - (r >> 2);
          if (d >= 0 && !(d & 15)) {
            const int f = c * 7 + (d == 0 ? 2 : d == 16 ? 5 : 6);
            tma_prefetch2d(&p.wg, f * 64, r * 64);
            tma_prefetch2d(&p.wu, f * 64, r * 64);
            if (d != 32) tma_prefetch2d(&p.wu, (f - 1) * 64, r * 64);
          }
        }
        Ring<3> q(sb, 16384 + rank * 8192);
#pragma unroll 1
        for (; q.j < 16; q.next()) {
          q.acquire_first();
          mbar_expect_tx(q.bar(), 16384);
          tma2d_mc(q.dst(), mine, (c * 7 + 6) * 64, ((q.j + 9) & 15) * 64, q.bar());
          if (q.j >> 1 == rp) tma_prefetch2d(&p.wd, (c * 2 + rank) * 64, p.g4[q.j] * 64);
        }
#pragma unroll 1
        for (; q.j < 72; q.next()) {
          q.acquire();
          mbar_expect_tx(q.bar(), 16384);
          tma2d_mc(q.dst(), &p.wd, (c * 2 + rank) * 64, p.g4[q.j - 16] * 64, q.bar());
          if ((q.j & 15) >> 1 == rp && q.j < 56) tma_prefetch2d(&p.wd, (c * 2 + rank) * 64, p.g4[q.j] * 64);
        }
      }
    } else {
      const int cw = pw - 2;
      const uint32_t stg = sb + kStage + cw * 32768, rb = sb + kBars + 8 * kResBar;
      uint32_t land_par = 0;
      sts64(sb + kPlan, global_ns(), clock());
      if (cw == 0) {
#pragma unroll 1
        for (int i = 0; i < 16; i++) sts128(sb + kFill + i * 512 + (tid & 31) * 16, make_uint4(kPoison, kPoison, kPoison, kPoison));
        __nanosleep(kSampleNs);
        const uint32_t l15 = tid & 15;
        const uint4 os = __ldg(plus(p.wop, (tid & 31) * 128 + c * 16 + l15));
        const uint4 gs = __ldg(plus(tid & 16 ? p.wup : p.wgp, l15 * 451 + c * 56));
        const uint4 ws = __ldg(plus((const uint4*)wqkvp, (tid & 7) * 385 + (tid & 24) * 16 + (8 + c) * 8));
        const float wo = low_peak(os);
        sts128(sb + kScale, make_uint4(__float_as_uint(wo * kBias3 * low_peak(gs)), __float_as_uint(low_peak(ws) * kBias1) | 1, __float_as_uint(wo * kBias2), 0));
        if (tid == 320) TS(93);
        if (elect_one()) {
          const uint4* rows = plus(p.wop, (c * 64 + (r & 7) * 8 + (r >> 3) * 512) * 128);
          asm volatile("cp.async.bulk.prefetch.L2.global [%0], 16384;" ::"l"(rows) : "memory");
          __nanosleep(kRowNs);
          mbar_expect_tx(sb + kBars + 8 * kRowBar, 16384);
          asm volatile("cp.async.bulk.shared::cluster.global.mbarrier::complete_tx::bytes [%0], [%1], 16384, [%2];"
                       ::"r"(stg), "l"(rows), "r"(sb + kBars + 8 * kRowBar) : "memory");
        }
        nb_sync(kNbSelf, 32);
      }
      {
        mbar_wait(sb + kBars + 8 * kRowBar, 0);
        float s = 0.f;
#pragma unroll 1
        for (int i = 0; i < 16; i++) {
          const uint4 v = lds128(sb + kStage + (tid & 56) * 256 + (tid & 7) * 16 + i * 128);
          s += ((bf_lo(v.x) + bf_hi(v.x)) + (bf_lo(v.y) + bf_hi(v.y))) + ((bf_lo(v.z) + bf_hi(v.z)) + (bf_lo(v.w) + bf_hi(v.w)));
        }
#pragma unroll
        for (int o = 1; o < 8; o <<= 1) s += __shfl_xor_sync(~0u, s, o);
        send_word(SC_AT(wmean, c * 128 + r * 8 + (tid >> 3 & 7)), __float_as_uint(s * (1.f / kD)), ep);
        if (tid == 320) TS(109);
      }
#pragma unroll 1
      for (int ev = -1; ev < 4; ev++) {
        const bool quads = cw == 0 && ev == 1;
        if (ev >= cw && !quads) nb_sync(kNbPub + cw, 160);
        if (ev >= cw && elect_one()) {
          if (quads) {
            mbar_wait(sb + kBars + 8 * (kHalfBar + 1), 0);
#pragma unroll 1
            for (int i = 0; i < 2; i++) {
              __nanosleep(i ? kPaceNs : kHoldNs);
              tma_store2d(&p.hst, stg + 16384 + i * 8192, c * 128 + 64, r * 128 + i * 64);
              TS(100 + i);
            }
            bulk_commit();
            bulk_wait_read();
            mbar_arrive(sb + kBars + 8 * kStgBar);
          } else {
            if (ev == 1) {
              const uint32_t now = global_ns();
              const float left = (float)(now - lds32(sb + kPlan)) * (float)kRemain * rcp((float)((uint32_t)clock() - lds32(sb + kPlan + 4)));
              send_word(sc->finish + (uint32_t)bid, now + (uint32_t)left, ep);
            }
            const int it = ev - 2 + cw, f0 = c * 7 + (1 - cw) * 3, fp = it == 2 ? c * 7 + 6 : it ? f0 + 2 : c + 8 - 8 * cw;
            const bool is_o = ev == 0;
            const CUtensorMap* m = it <= 0 ? &p.ost : &p.hhst;
            const int b0 = is_o ? c : f0 + 1, b1 = fp;
#pragma unroll 1
            for (int i = is_o || it == 1 ? 0 : 2; i < (is_o ? 2 : 4); i++) {
              tma_store2d(m, stg + i * 8192, (i < 2 ? b0 : b1) * 64, r * 128 + (i & 1) * 64);
              if (!is_o) {
                bulk_commit();
                bulk_wait_read();
                __nanosleep(kPaceNs);
              }
            }
            bulk_commit();
            bulk_wait_all();
            mbar_arrive(sb + kBars + 8 * (kStgBar + cw));
            if (ev == 3 + cw) {
#pragma unroll
              for (int i = 0; i < 2; i++) asm volatile("mbarrier.arrive.shared::cluster.b64 _, [%0], 4;" ::"r"(map_cta(sb + kBars + 8 * 37, i)) : "memory");
            }
            flag_signal(SC_AT(flags, kFlHH + ev * 2 - 3 + cw + r * kFlRow));
            TS(44 + cw * 8 + ev);
            if (ev == 2 && cw) {
              sts32(sb + kPlan, await_word(sc->plan + (uint32_t)c, ep) >> (r >> 1) * 4 & 15);
              mbar_expect_tx(rb, 16384);
#pragma unroll 1
              for (int i = 0; i < 2; i++) tma2d(stg + 8192 + i * 16384, &p.hst, c * 128 + i * 64, r * 128 + 64, rb);
            }
          }
        }
        nb_sync(kNbSelf + cw, 32);
        if (ev >= 2 && ev + cw >= 3 && elect_one()) {
          const int wv = cw == 0 ? 3 : ev == 2 ? 0 : 4;
#pragma unroll 1
          for (int i = wv; i <= max(wv, 2); i++) flag_wait(SC_AT(flags, kFlHH + i + r * kFlRow), ep * 8);
          fence_async();
          mbar_arrive(sb + kBars + 8 * (kWaveBar + (wv >> 1)));
          if (wv == 4) {
            mbar_expect_tx(sb + kBars + 8 * kPartBar, 16384);
#pragma unroll 1
            for (int i = 0; i < 2; i++) tma2d(stg + 16384 + i * 8192, &p.hst, c * 128 + i * 64, r * 128, sb + kBars + 8 * kPartBar);
          }
        }
        nb_sync(kNbSelf + cw, 32);
#pragma unroll 1
        for (int sub = 0; ev < cw; sub++) {
          nb_sync(kNbSelf + cw, 32);
          if (ev == 0) check_blocks(p, sc, sb, r, c, sub, land_par);
          const int u = ev < 0 ? cw : 2, lane = fresh_tid() & 31;
          if (u == 1 && !sub) {
            uint3 st[5];
            load_tagged<5, true>(st, SC_AT(stat1, r * 128 + lane), 32, ep, SC_AT(stat1, (r < 2 ? r : r - 2) * 128 + (lane & 7)) + 120);
#pragma unroll
            for (int i = 0; i < 4; i++) sts64(sb + kStat + (i * 32 + lane) * 8, st[i].x, st[i].y);
            sts64(sb + kStat - 64 + (lane & 7) * 8, st[4].x, st[4].y);
            nb_sync(kNbSelf + cw, 32);
            if (lane < 4) mbar_arrive(sb + kBars + 8 * kStatBar);
            if (lane == 0) TS(17);
          }
          if (u == 1) {
            const uint4* gh = SC_AT(halo, (sub * 128 + bid) * 192 + lane) - 16 * 192;
            uint4 hv[6] = {};
            nb_sync(kNbHalo, 64);
            uint32_t ns = sub ? kHaloNs : 2 * kBackoffNs;
#pragma unroll 1
            for (int spins = 0; r >= 2; spins++) {
              if (ns) __nanosleep(ns);
              ns = sub ? 0 : kBackoffNs;
              if (spins > 2000000) __trap();
#pragma unroll
              for (int i = 0; i < 6; i++) hv[i] = ld_b128(gh + i * 32);
              uint32_t bad = (hv[5].y ^ ep) | (hv[5].z ^ ep);
#pragma unroll
              for (int i = 0; i < 6; i++) bad |= hv[i].w ^ ep;
              if (!__any_sync(~0u, bad != 0)) break;
            }
            const uint32_t dst = sb + kStage + sub * 32768 + lane * 16;
            sts128(dst, make_uint4(hv[0].x, hv[0].y, hv[0].z, hv[1].x));
            sts128(dst + 512, make_uint4(hv[1].y, hv[1].z, hv[2].x, hv[2].y));
            sts128(dst + 1024, make_uint4(hv[2].z, hv[3].x, hv[3].y, hv[3].z));
            sts128(dst + 1536, make_uint4(hv[4].x, hv[4].y, hv[4].z, hv[5].x));
            nb_arrive(kNbHalo + 1, 64);
            if (lane == 0) TS(123 + sub);
          }
          if (sub) break;
          if (ev == 0) continue;
          uint3 v[3];
          load_tagged<3, false>(v, SC_AT(cs, c * 96 + u * 768 + lane), 32, ep);
#pragma unroll
          for (int i = 0; i < 3; i++)
#pragma unroll
            for (int k = 0; k < 8; k++)
              sts32(sb + kAug + cw * 4096 + i * 1024 + k * 128 + ((lane * 4) ^ (k * 16)), k == 7 ? 0x3F803F80u : k == 4 || k == 6 ? v[i].z : k & 1 && k != 5 ? v[i].y : v[i].x);
          fence_async_smem();
          nb_sync(kNbSelf + cw, 32);
          if (lane == 0) { mbar_arrive(sb + kBars + 8 * (kAuxBar + cw)); TS(104 + u); }
        }
        nb_sync(kNbSelf + cw, 32);
        if (ev < 0 && cw == 0 && elect_one()) {
#pragma unroll 1
          for (int i = 0; i < 6; i++) {
            __nanosleep(i == 0 ? (c >> 1) * (kFillNs / 4) : kFillNs);
            tma_store2d(i < 2 ? &p.ost : &p.hst, sb + kFill, i < 2 ? (8 + c) * 64 : (c * 2 - 1 + (i >> 1)) * 64, r * 128 + (i & 1) * 64);
            bulk_commit();
          }
          uint32_t peer;
          asm volatile("ld.shared::cluster.b32 %0, [%1];" : "=r"(peer) : "r"(map_cta(sb + kRole, rank ^ 1)) : "memory");
          if (peer != (bid ^ 8)) __trap();
          TS(90);
        }
        nb_sync(kNbSelf + cw, 32);
      }
    }
  } else {
    if (tid == 0) TSS(2);
    cluster_arrive();
    float bias = 0.f;
    float sx = 0.f, mx = 0.f;
    asm volatile("setmaxnreg.inc.sync.aligned.u32 232;");
    if (tid == 0) TSS(4);
    int task;
    asm volatile("mov.u32 %0, %1;" : "=r"(task) : "r"(8 - wg));

#pragma unroll 1
    for (task = __shfl_sync(~0u, task, 0);; task++) {
      if (task == 1 + wg || task == 9 - wg) {
        const int t = fresh_tid();
        uint4 scale;
        do scale = lds128(sb + kScale);
        while (scale.y == 0);
        __syncwarp();
        const float peak = low_peak(lds128(sb + (task > 5 ? kRing : kStage + wg * 32768) + (t & 126) * 64 + (t & 14) * 8 + (t & 1) * 8192));
        bias = bias_at(peak * __uint_as_float(task > 5 ? scale.y : scale.x));
        sts32(sb + kScale + 16 + warp * 4, __float_as_uint(bias_at(peak * __uint_as_float(scale.z))));
        __syncwarp();
        if (t == 128 && task > 5) TS(95);
      }
      if (wg == 0 && (task == 1 || task == 4)) {
        float acc[2][96];
        const int t = fresh_tid() & 127;
        const uint32_t frag = sb + kOwn + ((t >> 5) * 16 + (t & 15)) * 128, frag_x = ((t >> 4) & 1) ^ (t & 7);
        TSG(2);
        if (task == 4) mbar_wait(sb + kBars + 8 * kResBar, 0);
        const uint32_t means = sb + kStat + ((t >> 5) * 16 + (t >> 2 & 7)) * 8 + 4;
        float add[2];
#pragma unroll
        for (int i = 0; i < 2; i++) add[i] = __uint_as_float(lds32(task == 1 ? sb + kScale + 16 + warp * 4 : means + 512 + i * 64));
        auto residual = [&](int m) {
#pragma unroll
          for (int i = 0; i < 8; i++) {
            uint32_t v[4];
            ldsm4(frag + (i >> 2) * 16384 + m * 8192 + ((frag_x ^ (i * 2 & 6)) << 4), v);
#pragma unroll
            for (int e = 0; e < 4; e++) {
              float* d = &acc[m][8 * i + 2 * e];
              asm("shl.b32 %0, %1, 16;" : "=f"(d[0]) : "r"(v[e]));
              asm("and.b32 %0, %1, 0xFFFF0000;" : "=f"(d[1]) : "r"(v[e]));
              asm("add.f32 %0, %0, %1;" : "+f"(d[0]) : "f"(add[e & 1]));
              asm("add.f32 %0, %0, %1;" : "+f"(d[1]) : "f"(add[e & 1]));
            }
          }
        };
        residual(1);
        if (task == 1) {
          residual(0);
        } else {
          const uint32_t m0 = lds32(means), m1 = lds32(means + 64), z = fresh_tid() >> 10;
#pragma unroll
          for (int i = 0; i < 64; i++) acc[0][i] = copy_of(i & 2 ? m1 : m0, z, i);
        }
        __syncwarp();
        if ((t & 31) == 0) mbar_arrive(sb + kBars + 8 * kResFreeBar);
        TSG(4);
        if ((tid & 127) == 0) TS(task == 1 ? 6 : 14);
        if (task == 4) {
          mainloop<128, kTail>(sc, acc, sb, 3, 16, 56, -2, true, false, false, 0, __shfl_sync(~0u, lds32(sb + kPlan), 0), &p.out, c * 128, (r >> 1) * 128, warp, outp);
          if ((tid & 127) == 0) TSK(15);
          if (fresh_tid() == 0) {
            if (bid == 0) __stcg(sc->epoch, lds32(sb + kEpoch));
            TSK(19);
          }
          break;
        }
        mainloop<128, -1>(sc, acc, sb, 1, 0, 15, kPauseG2, false, true, false, 0);
        const int t2 = fresh_tid() & 127;
        const uint32_t frag2 = sb + kStage + ((t2 >> 5) * 16 + (t2 & 15)) * 128, frag2_x = ((t2 >> 4) & 1) ^ (t2 & 7);
        const uint32_t empty = map_cta(sb + kBars + 8 * (ring_base(1) + 5), t2 & 1);
        mbar_wait(sb + kBars + 8 * kStgBar, 0);
        float sub[4];
        mbar_wait(sb + kBars + 8 * ring_base(1), 1);
#pragma unroll
        for (int m = 0; m < 2; m++) {
          const uint32_t a = desc_lo(sb + kRing, 16);
          wg_fence();
#pragma unroll
          for (int k = 0; k < 4; k++) wgmma_n128(acc[m], desc_kept(a, sb) + (m * 512 + k * 2), desc_kept(a, sb) + (kToB + k * 128));
          wg_commit();
          if (m) {
            nb_arrive(kNbOrder + 1, 256);
            if (t2 == 0) TS(107);
            nb_sync(kNbMean, 256);
            if (t2 == 0) TS(108);
            const float bias2 = __uint_as_float(lds32(sb + kScale + 16 + warp * 4));
#pragma unroll
            for (int i = 0; i < 4; i++) sub[i] = __uint_as_float(lds32(sb + kStat + ((t2 >> 5) * 16 + (t2 >> 2 & 7)) * 8 + 4 + (i >> 1) * 512 + (i & 1) * 64)) + bias2;
          }
          wg_wait<1>();
          if (!m) mbar_arrive_cluster_if(empty + 8 * 4, (t2 & 31) < 2);
        }
#pragma unroll
        for (int b = 0; b < 4; b++) {
          if (b == 1) {
            wg_wait<0>();
            if (t2 == 0) TSK(7);
          }
          if (b < 2) {
#pragma unroll
            for (int i = 0; i < 64; i++) asm volatile("" : "+f"(acc[b][i])::"memory");
          }
#pragma unroll
          for (int i = 32 * (b >> 1); i < 32 * (b >> 1) + 32; i++) acc[b & 1][i] -= sub[(b & 1) * 2 + (i >> 1 & 1)];
          stage_quarter(&acc[b & 1][32 * (b >> 1)], frag2, frag2_x, b);
          if (b & 1) {
            fence_async_smem();
            __syncwarp();
            if (elect_one()) {
              mbar_arrive(sb + kBars + 8 * (kHalfBar + (b >> 1)));
#pragma unroll
              for (int m = 0; m < 2; m++)
                if (b == 1) tma_store2d(&p.h16, sb + kStage + m * 8192 + warp * 2048, c * 128, r * 128 + m * 64 + warp * 16);
            }
            __syncwarp();
          }
        }
        if (t2 == 0) TS(8);
        sx = mx = 0.f;
        continue;
      }
      float acc[2][96];
      if (task == 8 + wg) {
        wg_fence();
#pragma unroll
        for (int m = 0; m < 2; m++) wgmma_n192_any(acc[m], desc(64 + m), desc(64 + m));
        wg_commit();
        wg_wait<0>();
#pragma unroll
        for (int i = 0; i < 96; i++) asm volatile("" : "+f"(acc[0][i]), "+f"(acc[1][i])::"memory");
      } else {
        const uint32_t z = fresh_tid() >> 10;
#pragma unroll
        for (int i = 0; i < 96; i++) {
#pragma unroll
          for (int m = 0; m < 2; m++)
            acc[m][i] = copy_of(__float_as_uint(bias), z, 2 * i + m);
        }
      }
      if (task > 5) {
        if (wg) {
          if (task == 7) cluster_wait();
          if (tid == 128 && task == 7) { TSS(5); TSK(69); }
          const int t = fresh_tid() & 127, lr = c * 16 + (t >> 3);
          uint32_t pf = t < 64 ? (bid * 16 + (t >> 2)) * kD + (t & 3) * 64 : (r * 48 + t - 64) * kD + c * 64;
          const uint32_t src = sb + kRing + lr * 128 + (((t ^ lr) & 7) << 4), empty = map_cta(sb + kBars + 8 * 4, t & 1), zero = fresh_tid() >> 10;
#pragma unroll 1
          for (int j = task == 7 ? 0 : kSplit; j < (task == 7 ? kSplit : 16); j++) {
            mbar_wait(sb + kBars + 8 * (j & 3), (j >> 2) & 1);
            if (j < 2 && t == 0) TS(102 + j);
            const uint4 v = lds128(src + (j >> 1 == c ? kOwn + (j & 1) * 16384 : (j & 3) * 40960));
            __syncwarp();
            mbar_arrive_cluster_if(empty + 8 * (j & 3) + (v.x & zero), (t & 31) < 2);
            if ((j == 0 || j == 3 || j == 6) && t < 112) { pf += t < 64 ? 256 : 256 * 3 * kD; prefetch_l2(plus(t < 64 ? xp : wqkvp, pf)); }
            const uint32_t u[4] = {v.x, v.y, v.z, v.w};
#pragma unroll
            for (int e = 0; e < 4; e++) {
              const float d0 = bf_lo(u[e]), d1 = bf_hi(u[e]);
              sx += d0 + d1;
              mx = fmaf(d1, d1, fmaf(d0, d0, mx));
            }
          }
          if (task == 7) {
            if (t == 0) TS(96);
            continue;
          }
#pragma unroll
          for (int o = 4; o > 0; o >>= 1) { sx += __shfl_xor_sync(~0u, sx, o); mx += __shfl_xor_sync(~0u, mx, o); }
          const float mean = sx * (1.f / kD);
          float rstd;
          asm("rsqrt.approx.ftz.f32 %0, %1;" : "=f"(rstd) : "f"(fmaxf(mx * (1.f / kD) - mean * mean, 0.f) + 1e-5f));
          const uint32_t ep = lds32(sb + kEpoch);
          const int t2 = fresh_tid();
          if ((t2 & 7) == 0) st_b128(SC_AT(stat1, bid * 16 + (t2 >> 3 & 15)), __float_as_uint(rstd), __float_as_uint(-mean), ep, ep);
          if (t == 0) TS(16);
        }
        if (tid == 0) TSS(6);
        mainloop<192, -1>(sc, acc, sb, 0, wg * 16, wg ? 16 - kAhead : 16, wg ? kPauseG1 : -2, false, wg == 0, false, wg,
                          wg ? min((c + 2) & 7, 6) : c);
        int t = fresh_tid() & 127, lane = t & 31, g = lane >> 2, q = lane & 3;
        const int w = warp & 3;
        const uint32_t stg = sb + kStage + wg * 32768;
        auto tail = [&](int m, int k0, int k1) {
          wg_fence();
#pragma unroll
          for (int k = k0; k < k1; k++) {
            const uint64_t a = desc_kept(desc_lo(sb + kRing, 16), sb) + (4 - kAhead + (k >> 2)) * (40960 >> 4);
            wgmma_n192(acc[m], a + (m * 512 + (k & 3) * 2), a + (kToB + (k & 3) * 128));
          }
        };
        auto release = [&](int j, bool cond) { mbar_arrive_cluster_if(map_cta(sb + kBars + 8 * (4 + (j & 3)), lane & 1), cond); };
        if (wg) {
#pragma unroll
          for (int j = 32 - kAhead; j < 32; j++) {
            TST(2 * (j & 1));
            mbar_wait(sb + kBars + 8 * (j & 3), 1);
            TST(2 * (j & 1) + 1);
            tail(1, 4 * (j - 32 + kAhead), 4 * (j - 31 + kAhead));
            wg_commit();
            if (j == 32 - kAhead) {
              wg_wait<1>();
              release(j - 1, lane < 4);
              mbar_wait(sb + kBars + 8 * kResFreeBar, 0);
            }
          }
        } else {
          nb_arrive(kNbOrder + 1, 256);
          wg_wait<0>();
          release(15, lane < 2);
          if (t == 0) TSK(1);
        }
        TST(4);
        mbar_wait(sb + kBars + 8 * (kAuxBar + wg), 0);
        mbar_wait(sb + kBars + 8 * kStatBar, 0);
        {
          uint32_t am[4];
#pragma unroll
          for (int i = 0; i < 4; i++) {
            const float m1 = __uint_as_float(lds32(sb + kStat + (w * 16 + g) * 8 + 4 + (i >> 1) * 512 + (i & 1) * 64));
            const float m2 = bf_rest(m1), lo = q & 1 ? m2 : m1;
            am[i] = bf_upper(lo, q == 3 ? -bias : q == 2 ? bf_rest(m2) : lo);
          }
          const uint64_t db = (uint64_t)desc_lo(sb + kAug + wg * 4096, 1024) | (0x40000000ull << 32);
          TST(5);
          wg_fence();
          wgmma_n192_rs(acc[1], am[2], am[3], 0u, db);
          wg_commit();
          TST(6);
          wg_fence();
          wgmma_n192_rs(acc[0], am[0], am[1], 0u, db);
          wg_commit();
          if (wg) {
            tail(0, 0, 4 * kAhead);
            wg_commit();
            wg_wait<2>();
          } else {
            wg_wait<1>();
          }
          TST(8);
#pragma unroll
          for (int i = 0; i < 96; i++) asm volatile("" : "+f"(acc[1][i])::"memory");
        }
        t = fresh_tid() & 127, lane = t & 31;
        const uint32_t ep = lds32(sb + kEpoch);
        uint32_t pk[2][48];
        auto fold = [&](int pp, int jn, int hf) {
          const uint32_t v = pack_bf16(acc[pp][4 * jn + 2 * hf], acc[pp][4 * jn + 2 * hf + 1]);
          pk[pp][2 * jn + hf] = jn >= 16 ? movm(v) : v;
        };
        if (t == 96) TS(115 + wg);
#pragma unroll
        for (int jn = 8; jn < 24; jn++) fold(1, jn, 1);
        if (w < 3) {
#pragma unroll
          for (int i = 0; i < 4; i++)
            sts128(stg + (w + 5) * 2048 + i * 512 + lane * 16, make_uint4(pk[1][17 + 8 * i], pk[1][19 + 8 * i], pk[1][21 + 8 * i], pk[1][23 + 8 * i]));
        } else if (r < 14) {
          uint4* gh = SC_AT(halo, (wg * 128 + bid) * 192 + lane);
#pragma unroll
          for (int i = 0; i < 6; i++) st_b128(gh + i * 32, pk[1][17 + 6 * i], i < 5 ? pk[1][(19 + 6 * i) % 48] : ep, i < 5 ? pk[1][(21 + 6 * i) % 48] : ep, ep);
          if (wg == 0) {
#pragma unroll 1
            for (int i = 0; i < 6; i++, gh += 32) st_b128(gh + 128 * 192, 0, 0, 0, ep - 1);
          }
        }
        if (w == 3) nb_arrive(kNbHalo, 64);
        if (wg) nb_arrive(kNbOrder, 256);
        TST(9);
        if (t == 96) TS(111 + wg);
#pragma unroll
        for (int jn = 23; jn >= 0; jn--) {
          fold(1, jn, 0);
          if (jn < 8) fold(1, jn, 1);
        }
        t = fresh_tid() & 127, lane = t & 31, g = lane >> 2, q = lane & 3;
        const bool sel0 = 2 * q > g, sel1 = 2 * q + 1 > g, no_prev = (r < 2 && w == 0);
        const uint4 ones = lds128(sb + kOnes);
        const uint32_t lowmask = (sel0 ? 0x0000FFFFu : 0u) | (sel1 ? 0xFFFF0000u : 0u) | ones.y;
        float rs[4][2], rk[4][2];
#pragma unroll
        for (int i = 0; i < 4; i++) {
          const uint32_t a = sb + kStat + w * 128 + (i >> 1) * 512 + (i & 1) * 64;
          const float rq = __uint_as_float(lds32(a + g * 8)) * (0.17677669529663687f * 1.4426950408889634f);
          rk[i][0] = __uint_as_float(lds32(a + q * 16 - (sel0 ? 64 : 0)));
          rk[i][1] = __uint_as_float(lds32(a + q * 16 + 8 - (sel1 ? 64 : 0)));
          rs[i][0] = rk[i][0] * rq;
          rs[i][1] = rk[i][1] * rq;
        }
        {
          uint32_t all = ~0u;
#pragma unroll
          for (int i = 0; i < 48; i++) if (i < 16 || !(i & 1)) all &= pk[1][i];
          if (all == kPoison) sts32(sb + kZero + 8, 0);
        }
        TST(10);
        wg_wait<0>();
        TST(11);
#pragma unroll
        for (int j = 32 - kAhead; j < 32; j++) release(j, lane < 4 * wg && (w != 0 || j < 31));
#pragma unroll
        for (int i = 0; i < 96; i++) asm volatile("" : "+f"(acc[0][i])::"memory");
        if (t == 0 && wg) TSK(21);
#pragma unroll
        for (int jn = 8; jn < 24; jn++) fold(0, jn, 1);
#pragma unroll
        for (int i = 0; i < 4; i++)
          sts128(stg + (w + 1) * 2048 + i * 512 + lane * 16, make_uint4(pk[0][17 + 8 * i], pk[0][19 + 8 * i], pk[0][21 + 8 * i], pk[0][23 + 8 * i]));
#pragma unroll
        for (int jn = 23; jn >= 0; jn--) {
          fold(0, jn, 0);
          if (jn < 8) fold(0, jn, 1);
        }
        if (t == 0) TS(113 + wg);
        nb_sync(kNbWg + wg, 128);
        uint32_t hal[2][16];
        auto load_halo = [&](int m) {
#pragma unroll
          for (int i = 0; i < 4; i++) {
            const uint4 v = lds128(stg + w * 2048 + m * 8192 + i * 512 + lane * 16);
            uint32_t* h = &hal[m][i * 4];
            h[0] = v.x; h[1] = v.y; h[2] = v.z; h[3] = v.w;
          }
        };
        load_halo(1);
        if (w == 0) {
          nb_sync(kNbHalo + 1, 64);
          release(31, lane < 4 * wg);
        }
        load_halo(0);
        __syncwarp();
        if (t == 0) TS(2 + wg * 20);
        {
          uint32_t all = lowmask;
#pragma unroll
          for (int i = 0; i < 32; i++) if (i < 16 || !(i & 1)) all &= pk[0][i];
#pragma unroll
          for (int i = 0; i < 8; i++) all &= __float_as_uint(rs[i >> 1][i & 1]);
          if (all == kPoison) sts32(sb + kZero + 8, 0);
        }
        if (wg == 0) {
          const int t0 = fresh_tid();
          sts32(sb + kCs + t0 * 4, await_word<kBackoffNs>(SC_AT(wmean, c * 128 + t0), lds32(sb + kEpoch)));
          __syncwarp();
        }
        nb_sync(kNbWin, 256);
        if (t == 0) TS(9 + wg * 20);
        const uint32_t zero = lds32(sb + kZero);
        float s0[4][4], s1[4][4], s2[4][4];
#pragma unroll
        for (int k = 0; k < 4; k++) {
          pk[k >> 1][8 * (k & 1)] |= zero;
#pragma unroll
          for (int e = 0; e < 4; e++) s0[k][e] = s1[k][e] = s2[k][e] = 0.f;
        }
#pragma unroll
        for (int ks = 0; ks < 2; ks++)
#pragma unroll
          for (int k = 0; k < 4; k++) {
            const uint32_t* qf = &pk[k >> 1][8 * (k & 1) + 4 * ks];
            const uint32_t* kf = &pk[k >> 1][16 + 8 * (k & 1) + 4 * ks];
            const uint32_t* hf = &hal[k >> 1][4 * (k & 1) + 2 * ks];
            mma16816(s0[k], qf[0], qf[1], qf[2], qf[3], hf[0], hf[1]);
            mma16816(s1[k], qf[0], qf[1], qf[2], qf[3], kf[0], kf[2]);
            mma16816(s2[k], qf[0], qf[1], qf[2], qf[3], kf[1], kf[3]);
          }
        float ea[4][2], eb[4][2], ma[4], mb[4];
#pragma unroll
        for (int k = 0; k < 4; k++) {
          const float *ra = rs[k & 2], *rb = rs[(k & 2) + 1];
          if (no_prev && k < 2) s0[k][0] = s0[k][1] = -INFINITY;
          ea[k][0] = (sel0 ? s0[k][0] : s1[k][0]) * ra[0]; ea[k][1] = (sel1 ? s0[k][1] : s1[k][1]) * ra[1];
          eb[k][0] = (sel0 ? s1[k][2] : s2[k][2]) * rb[0]; eb[k][1] = (sel1 ? s1[k][3] : s2[k][3]) * rb[1];
          ma[k] = fmaxf(ea[k][0], ea[k][1]); mb[k] = fmaxf(eb[k][0], eb[k][1]);
        }
#pragma unroll
        for (int o = 1; o < 4; o <<= 1)
#pragma unroll
          for (int k = 0; k < 4; k++) {
            ma[k] = fmaxf(ma[k], __shfl_xor_sync(~0u, ma[k], o));
            mb[k] = fmaxf(mb[k], __shfl_xor_sync(~0u, mb[k], o));
          }
        float ov[4][4][4], ls[4][4];
        uint32_t all = 0;
#pragma unroll
        for (int k = 0; k < 4; k++) {
          const float *ra = rk[k & 2], *rb = rk[(k & 2) + 1];
          ea[k][0] = ex2(ea[k][0] - ma[k]); ea[k][1] = ex2(ea[k][1] - ma[k]);
          eb[k][0] = ex2(eb[k][0] - mb[k]); eb[k][1] = ex2(eb[k][1] - mb[k]);
          const uint32_t pa = pack_bf16(ea[k][0] * ra[0], ea[k][1] * ra[1]), pb = pack_bf16(eb[k][0] * rb[0], eb[k][1] * rb[1]);
          const uint32_t* vf = &pk[k >> 1][32 + 8 * (k & 1)];
          const uint32_t* hf = &hal[k >> 1][8 + 4 * (k & 1)];
#pragma unroll
          for (int d2 = 0; d2 < 2; d2++) {
#pragma unroll
            for (int e = 0; e < 4; e++) ov[k][d2][e] = ov[k][2 + d2][e] = 0.f;
            mma1688(ov[k][d2], hf[2 * d2], hf[2 * d2 + 1], pa & lowmask);
            mma1688(ov[k][2 + d2], vf[4 * d2], vf[4 * d2 + 2], pb & lowmask);
          }
#pragma unroll
          for (int d2 = 0; d2 < 2; d2++) {
            mma1688(ov[k][d2], vf[4 * d2], vf[4 * d2 + 2], pa & ~lowmask);
            mma1688(ov[k][2 + d2], vf[4 * d2 + 1], vf[4 * d2 + 3], pb & ~lowmask);
          }
          ls[k][0] = ls[k][1] = ls[k][2] = ls[k][3] = 0.f;
          mma16816(ls[k], ones.x, ones.y, ones.z, ones.w, pack_bf16(ea[k][0], ea[k][1]), pack_bf16(eb[k][0], eb[k][1]));
          if (k >= kDone) all |= pa & pb;
        }
#pragma unroll
        for (int k = 0; k < 4; k++) {
          if (k == kDone) {
            if (all == 0xFFFFFFFFu) sts32(sb + kZero + 8, 0);
            nb_arrive(kNbWin + 1, 256);
            all = 0;
          }
          all |= (__float_as_uint(ov[k][0][0]) & __float_as_uint(ov[k][1][0]) & __float_as_uint(ov[k][2][0])) &
                 (__float_as_uint(ov[k][3][0]) & __float_as_uint(ls[k][0]));
        }
        const uint32_t nil = lds32(sb + kZero);
        const uint32_t frag = stg + (w * 16 + (lane & 15)) * 128, frag_x = (lane >> 4) ^ (lane & 7);
        uint32_t after = all;
#pragma unroll
        for (int k = 0; k < 4; k++) {
          uint32_t h[2][4];
#pragma unroll
          for (int hf = 0; hf < 2; hf++) {
            const float i0 = rcp(__uint_as_float(__float_as_uint(ls[k][2 * hf]) | (after & nil)));
            const float i1 = rcp(__uint_as_float(__float_as_uint(ls[k][2 * hf + 1]) | (after & nil)));
#pragma unroll
            for (int e = 0; e < 4; e++) h[e >> 1][2 * (e & 1) + hf] = pack_bf16(ov[k][2 * hf + (e >> 1)][2 * (e & 1)] * i0, ov[k][2 * hf + (e >> 1)][2 * (e & 1) + 1] * i1);
            after = h[0][hf];
          }
#pragma unroll
          for (int d2 = 0; d2 < 2; d2++) stsm4_t(frag + (k >> 1) * 8192 + ((frag_x ^ ((k & 1) * 4 + d2 * 2)) << 4), h[d2][0], h[d2][1], h[d2][2], h[d2][3]);
        }
        fence_async_smem();
        if (wg) {
          __syncwarp();
          if (elect_one()) {
            tma_store2d(&p.o16, stg + w * 2048, (8 + c) * 64, r * 128 + w * 16);
            tma_store2d(&p.o16, stg + 8192 + w * 2048, (8 + c) * 64, r * 128 + 64 + w * 16);
            bulk_commit();
            bulk_wait_read();
            mbar_arrive(sb + kBars + 8 * kSentBar);
          }
          __syncwarp();
        } else {
          nb_arrive(kNbPub, 160);
        }
        if (t == 0) TS(3 + wg * 20);
        {
          const int l = fresh_tid() & 31;
          const uint32_t ep = lds32(sb + kEpoch);
          __syncwarp();
          const uint4 ua = lds128(sb + kCs + wg * 256 + (l & 7) * 32), ub = lds128(sb + kCs + wg * 256 + (l & 7) * 32 + 16);
          float mine = 0.f;
#pragma unroll 1
          for (int i = 0; i < 4; i++) {
            const int n = i * 4 + (l >> 3);
            float d[2];
#pragma unroll
            for (int m = 0; m < 2; m++) {
              const uint4 v = lds128(stg + w * 2048 + m * 8192 + n * 128 + (((l ^ n) & 7) << 4));
              float a = bf_lo(v.x) * __uint_as_float(ua.x), b = bf_hi(v.x) * __uint_as_float(ua.y);
              a = fmaf(bf_lo(v.y), __uint_as_float(ua.z), a); b = fmaf(bf_hi(v.y), __uint_as_float(ua.w), b);
              a = fmaf(bf_lo(v.z), __uint_as_float(ub.x), a); b = fmaf(bf_hi(v.z), __uint_as_float(ub.y), b);
              a = fmaf(bf_lo(v.w), __uint_as_float(ub.z), a); b = fmaf(bf_hi(v.w), __uint_as_float(ub.w), b);
              d[m] = a + b;
            }
            float e = (l & 4 ? d[1] : d[0]) + __shfl_xor_sync(~0u, l & 4 ? d[0] : d[1], 4);
            e += __shfl_xor_sync(~0u, e, 1);
            e += __shfl_xor_sync(~0u, e, 2);
            if (i == (l & 3)) mine = e;
          }
          uint2* dst = SC_AT(dot, (r * 16 + wg * 8 + c) * 128 + w * 16 + (l & 3) * 4 + (l & 4) * 16 + (l >> 3));
          send_word(dst, __float_as_uint(mine), ep);
          if (l == 0 && w == 0) TS(97 + wg);
          if (wg == 0) send_word(dst + 8 * 128, 0, ep - 1);
        }
        task = wg;
        sx = mx = bias = 0.f;
        continue;
      }

      if (task == 2 && wg) {
        const int t = fresh_tid() & 127;
        float sum = -__uint_as_float(lds32(sb + kStat + t * 8 + 4));
#pragma unroll 1
        for (int i = 0; i < 16; i += kGather) sum += sum_words<kGather>(SC_AT(dot, (r * 16 + i) * 128 + t), 128, lds32(sb + kEpoch));
        nb_sync(kNbWg + 1, 128);
        sts32(sb + kStat + t * 8 + 4, __float_as_uint(sum));
        nb_arrive(kNbMean, 256);
        if (t == 0) TS(99);
      }
      {
#pragma unroll 1
        for (int part = task != 2; part < 2; part++) {
          if ((tid & 127) == 0) TS(6 + 2 * task + wg * 20);
          if (task + part == 5) {
            mainloop<128, 0>(sc, acc, sb, 3, 0, 16, -2, false, true, false, 1);
            continue;
          }
          const int j0 = task == 3 ? 48 - wg * 16 : part == 0 ? 2 - 2 * wg : 18 - 14 * wg;
          mainloop<192, 0>(sc, acc, sb, 2, j0, task != 2 ? 16 : part == 0 ? 2 : 14, -2, false, true, part == 0, wg);
          if (part == 0 && wg == 0) {
            const int t = fresh_tid() & 127;
            const uint32_t ep = lds32(sb + kEpoch);
            {
              float s0 = 0.f, s1 = 0.f;
#pragma unroll 1
              for (int i = 0; i < 16; i++) {
                const uint4 v = lds128(sb + kStage + t * 128 + (i >> 3) * 16384 + (((i ^ t) & 7) << 4));
                const uint32_t u[4] = {v.x, v.y, v.z, v.w};
#pragma unroll
                for (int e = 0; e < 4; e++) {
                  s0 = fmaf(bf_lo(u[e]), bf_lo(u[e]), s0);
                  s1 = fmaf(bf_hi(u[e]), bf_hi(u[e]), s1);
                }
              }
              send_word(SC_AT(stat2, c * kS + r * 128 + t), __float_as_uint(s0 + s1), ep);
            }
            __nanosleep(kStatNs);
            const float sum = sum_words<8>(SC_AT(stat2, r * 128 + t), kS, ep);
            sts32(sb + kStat + t * 8, __float_as_uint(fmaf(sum, 1.f / kD, 1e-5f)));
            __syncwarp();
            if (elect_one()) {
              bulk_commit();
              bulk_wait_read();
              mbar_arrive(sb + kBars + 8 * kStatBar);
            }
            __syncwarp();
            if (t == 0) TS(37);
          }
        }
      }
      const int t = fresh_tid() & 127, w = warp & 3, lane = t & 31, g = lane >> 2;
      const uint32_t stg = sb + kStage + wg * 32768;
      uint32_t statv = sb + kStat + (w * 16 + g) * 8;
      const uint32_t frag = stg + (w * 16 + (lane & 15)) * 128;
      const uint32_t frag_x = (lane >> 4) ^ (lane & 7);
      const uint32_t priv = stg + (t & 96) * 64 + lane * 16;
      if (t == 0) TSK(7 + 2 * task + wg * 20);

      if (task == 4) {
        mbar_wait(sb + kBars + 8 * kResFreeBar, 1);
        mbar_wait(sb + kBars + 8 * (kStgBar + 1), 0);
      }
      asm volatile("" : "+r"(statv)::"memory");

      {
#pragma unroll
        for (int i = 0; i < 96; i++) asm volatile("sub.f32 %0, %0, %1;" : "+f"(acc[0][i]) : "f"(bias));
        auto next_rows = [&](int i) { asm volatile("sub.f32 %0, %1, %2;" : "=f"(acc[0][i]) : "f"(acc[1][i]), "f"(bias)); };
#pragma unroll 1
        for (int pp = 0; pp < 2; pp++) {
          TSG(pp);
          RowConst rc[2];
#pragma unroll
          for (int hf = 0; hf < 2; hf++) {
            const float2 st = lds64f_const(statv + pp * 512 + hf * 64);
            float rstd;
            asm("rsqrt.approx.ftz.f32 %0, %1;" : "=f"(rstd) : "f"(st.x));
            rc[hf] = {0.7978845608f * rstd, 0.0356774081f * rstd * rstd * rstd, 0.5f * rstd * rstd};
          }
#pragma unroll
          for (int j2 = 0; j2 < 4; j2++) {
            uint32_t hv[4];
#pragma unroll
            for (int jj = 0; jj < 2; jj++) {
              const int jn = 2 * j2 + jj;
#pragma unroll
              for (int hf = 0; hf < 2; hf++) {
                const float g0 = acc[0][4 * jn + 2 * hf], g1 = acc[0][4 * jn + 2 * hf + 1];
                const float u0 = acc[0][32 + 4 * jn + 2 * hf], u1 = acc[0][33 + 4 * jn + 2 * hf];
                hv[2 * jj + hf] = pack_bf16(g0 * u0 * gate_scale(g0, rc[hf]), g1 * u1 * gate_scale(g1, rc[hf]));
              }
            }
            stsm4(frag + 16384 + pp * 8192 + ((frag_x ^ (j2 * 2)) << 4), hv[0], hv[1], hv[2], hv[3]);
          }
          if (task < 4) {
            if (task == 2) {
#pragma unroll
              for (int j2 = 0; j2 < 4; j2++) {
                uint32_t hv[4];
#pragma unroll
                for (int jj = 0; jj < 2; jj++) {
                  const int jn = 16 + 2 * j2 + jj;
#pragma unroll
                  for (int hf = 0; hf < 2; hf++) {
                    const float t0 = acc[0][4 * jn + 2 * hf], t1 = acc[0][4 * jn + 2 * hf + 1];
                    hv[2 * jj + hf] = pack_bf16(t0 * gate_scale(t0, rc[hf]), t1 * gate_scale(t1, rc[hf]));
                  }
                }
                sts128(priv + pp * 8192 + j2 * 512, make_uint4(hv[0], hv[1], hv[2], hv[3]));
              }
            } else {
              uint4 park[4];
#pragma unroll
              for (int j2 = 0; j2 < 4; j2++) park[j2] = lds128(priv + pp * 8192 + j2 * 512);
              __syncwarp();
#pragma unroll
              for (int j2 = 0; j2 < 4; j2++) {
                const uint32_t pv[4] = {park[j2].x, park[j2].y, park[j2].z, park[j2].w};
                uint32_t hv[4];
#pragma unroll
                for (int jj = 0; jj < 2; jj++) {
                  const int jn = 16 + 2 * j2 + jj;
#pragma unroll
                  for (int hf = 0; hf < 2; hf++) {
                    const float t0 = acc[0][4 * jn + 2 * hf], t1 = acc[0][4 * jn + 2 * hf + 1];
                    asm("mul.rn.bf16x2 %0, %1, %2;" : "=r"(hv[2 * jj + hf]) : "r"(pack_bf16(t0, t1)), "r"(pv[2 * jj + hf]));
                  }
                }
                stsm4(frag + pp * 8192 + ((frag_x ^ (j2 * 2)) << 4), hv[0], hv[1], hv[2], hv[3]);
              }
            }
            if (pp == 1) break;
#pragma unroll
            for (int i = 64; i < 96; i++) next_rows(i);
          }
          if (pp == 1) break;
#pragma unroll
          for (int i = 0; i < 64; i++) next_rows(i);
        }
      }
      const int t3 = fresh_tid() & 127;
      uint4* part = SC_AT(part, bid * 1024 + (t3 & 96) * 8 + (t3 & 31));
      if (task == 2 && wg) {
#pragma unroll
        for (int k = 0; k < 8; k++) st_b128(part + k * 32, kPoison, kPoison, kPoison, kPoison);
      }
      fence_async_smem();
      nb_arrive(kNbPub + wg, 160);
      if (t == 0) TS(task == 4 ? 57 : 56 + task + wg * 2);
      if (task == 4) {
        mbar_wait(sb + kBars + 8 * kPartBar, 0);
        const bool none = lds32(sb + kPlan) == 0;
#pragma unroll 1
        for (int b = 1, spins = 0; b >= 0;) {
          uint4 v[4] = {};
          uint32_t top = 0;
          if (!none) {
#pragma unroll
            for (int k = 0; k < 4; k++) v[k] = ld_b128(part + (128 + k * 32));
          }
#pragma unroll
          for (int k = 0; k < 4; k++) {
            top = max(max(top, v[k].x), max(v[k].y, max(v[k].z, v[k].w)));
          }
          if (__any_sync(~0u, top == kPoison)) {
            if (++spins > 100000) __trap();
            __nanosleep(kPartNs);
            continue;
          }
#pragma unroll
          for (int k = 0; k < 4; k++) {
            uint32_t h[4];
            ldsm4(frag + 16384 + b * 8192 + ((frag_x ^ (k * 2)) << 4), h);
            asm("add.rn.bf16x2 %0, %0, %1;" : "+r"(v[k].x) : "r"(h[0]));
            asm("add.rn.bf16x2 %0, %0, %1;" : "+r"(v[k].y) : "r"(h[1]));
            asm("add.rn.bf16x2 %0, %0, %1;" : "+r"(v[k].z) : "r"(h[2]));
            asm("add.rn.bf16x2 %0, %0, %1;" : "+r"(v[k].w) : "r"(h[3]));
            sts128(stg + (t3 & 96) * 128 + (t3 & 31) * 16 + b * 2048 + k * 512, v[k]);
          }
          b--;
          part -= 128;
        }
        if (t == 0) TSK(56);
        nb_arrive(kNbPart, 256);
        break;
      }
      sx = mx = 0.f;
    }
  }
}

typedef CUresult (*EncodeTiledFn)(CUtensorMap*, CUtensorMapDataType, cuuint32_t, void*, const cuuint64_t*, const cuuint64_t*,
                                  const cuuint32_t*, const cuuint32_t*, CUtensorMapInterleave, CUtensorMapSwizzle,
                                  CUtensorMapL2promotion, CUtensorMapFloatOOBfill);

void encode(EncodeTiledFn fn, CUtensorMap* m, const void* base, int rank, cuuint64_t d0, cuuint64_t d1, cuuint64_t d2,
            cuuint64_t s1, cuuint64_t s2, cuuint32_t b2, cuuint32_t b1 = 64) {
  const cuuint64_t dims[3] = {d0, d1, d2}, strides[2] = {s1, s2};
  const cuuint32_t box[3] = {64, b1, b2}, es[3] = {1, 1, 1};
  fn(m, CU_TENSOR_MAP_DATA_TYPE_BFLOAT16, rank, const_cast<void*>(base), dims, strides, box, es, CU_TENSOR_MAP_INTERLEAVE_NONE,
     CU_TENSOR_MAP_SWIZZLE_128B, CU_TENSOR_MAP_L2_PROMOTION_L2_128B, CU_TENSOR_MAP_FLOAT_OOB_FILL_NONE);
}

}

extern "C" void kernel_launch(void* const* d_in, const int* in_sizes, int n_in, void* d_out, int out_size) {
  void* fnp = nullptr;
  cudaDriverEntryPointQueryResult qr;
  cudaGetDriverEntryPoint("cuTensorMapEncodeTiled", &fnp, cudaEnableDefault, &qr);
  EncodeTiledFn fn = (EncodeTiledFn)fnp;
  void *o, *h, *hh;
  cudaGetSymbolAddress(&o, g_o);
  cudaGetSymbolAddress(&h, g_h);
  cudaGetSymbolAddress(&hh, g_hh);

  Params p;
  Scratch* sc;
  cudaGetSymbolAddress((void**)&sc, g_scratch);
  encode(fn, &p.x, d_in[0], 3, kD, kS / 2, 2, 4 * kD, 2 * kD, 1, 128);
  encode(fn, &p.out, d_out, 3, kD, kS / 2, 2, 4 * kD, 2 * kD, 1, 16);
  encode(fn, &p.wqkv, d_in[1], 2, 3 * kD, kD, 1, 6 * kD, 0, 1);
  encode(fn, &p.wo, d_in[2], 2, kD, kD, 1, 2 * kD, 0, 1);
  encode(fn, &p.wd, d_in[6], 2, kD, kF, 1, 2 * kD, 0, 1);
  encode(fn, &p.wg, d_in[4], 2, kF, kD, 1, 2 * kF, 0, 1);
  encode(fn, &p.wu, d_in[5], 2, kF, kD, 1, 2 * kF, 0, 1);
  encode(fn, &p.o, o, 2, kD, kS, 1, 2 * kD, 0, 1, 128);
  encode(fn, &p.h, h, 2, kD, kS, 1, 2 * kD, 0, 1, 128);
  encode(fn, &p.hh, hh, 2, kF, kS, 1, 2 * kF, 0, 1, 128);
  encode(fn, &p.ost, o, 2, kD, kS, 1, 2 * kD, 0, 1);
  encode(fn, &p.o16, o, 2, kD, kS, 1, 2 * kD, 0, 1, 16);
  encode(fn, &p.h16, h, 2, kD, kS, 1, 2 * kD, 0, 1, 16);
  encode(fn, &p.hst, h, 2, kD, kS, 1, 2 * kD, 0, 1);
  encode(fn, &p.hhst, hh, 2, kF, kS, 1, 2 * kF, 0, 1);
  for (int c = 0; c < 8; c++) {
    for (int j = 0; j < 32; j++) p.g1[c][j] = g1_block(j, c) | (j >= 16 && (j < 20 || g1_block(j, c) >> 1 == c) ? kInPlace : 0);
    for (int j = 0; j < 16; j++) p.g2[c][j] = g2_block(j, c);
    for (int j = 0; j < 64; j++)
      p.g3[c][j] = g3_block(j, c) | ((0x000F000F003C000Full >> j & 1) && j != 28 + c ? kInPlace : 0) | g3_tile(j) << 5;
  }
  for (int i = 0; i < 56; i++) {
    const int b = p.g4[i] = g4_block(i);
    p.g4in[i] = b % 7 == 0 ? b / 7 | kInO | kMark : b % 7 == 3 ? (8 + b / 7) | kInO : b | (b == 4 || b == 6 ? kMark : 0);
  }
  p.wop = (const uint4*)d_in[2];
  p.wgp = (const uint4*)d_in[4];
  p.wup = (const uint4*)d_in[5];

  int dev = 0, sms = 0;
  cudaGetDevice(&dev);
  cudaDeviceGetAttribute(&sms, cudaDevAttrMultiProcessorCount, dev);
  auto* kernel = sms == 132 ? fused_block_kernel<true> : fused_block_kernel<false>;
  cudaFuncSetAttribute(kernel, cudaFuncAttributeMaxDynamicSharedMemorySize, kSmemBytes);
  kernel<<<132, kThreads, kSmemBytes, cudaStreamPerThread>>>(sc, (const __nv_bfloat16*)d_in[0], (const __nv_bfloat16*)d_in[1],
                                                                  (__nv_bfloat16*)d_out, p);
}
```

```cpp
#include <cuda_runtime.h>
#include <cuda_bf16.h>
#include <cuda.h>
#include <stddef.h>
#include <stdint.h>

namespace {

constexpr int kS = 2048, kD = 1024, kF = 3584;
constexpr int kThreads = 384;

constexpr int kRing = 0;
constexpr int kStage = 163840;
constexpr int kAug = kStage + 16384;
constexpr int kOwn = kStage + 32768;
constexpr int kFill = kStage + 24576;
constexpr int kCs = kStage + 65536;
constexpr int kStat = kCs + 1536;
constexpr int kBars = kStat + 1024;
constexpr int kSmemBytes = kBars + 512;
constexpr int kResBar = 38;
constexpr int kAuxBar = 39;
constexpr int kStgBar = 41;
constexpr int kResFreeBar = 43;
constexpr int kStatBar = 44;
constexpr int kPartBar = 45;
constexpr int kWaveBar = 46;
constexpr int kHalfBar = 49;
constexpr int kSentBar = 51;
constexpr int kLandBar = 52;
constexpr int kRowBar = 57;
constexpr int kNumBars = 58;
static_assert(kNumBars == 4 + 3 * 18, "barrier initialisation is split 4 + 3 x 18");
__host__ __device__ constexpr int bar_count(int i) {
  const int ph = i < 8 ? 0 : i < 18 ? 1 : i < 26 ? 2 : 3, base = ph * 9 - (ph & 1);
  return i < 38 ? (i - base < 4 + (ph & 1) + (ph == 3) ? 2 : ph == 0 ? 16 : 8) : i == kResFreeBar || i == kStatBar || (i >= kHalfBar && i < kLandBar) ? 4 : 1;
}
__host__ __device__ constexpr uint64_t bar_shifts(int first) {
  uint64_t m = 0;
  for (int i = 17; i >= 0; i--) {
    const int n = bar_count(first + i);
    m = m << 3 | (n == 16 ? 4 : n == 8 ? 3 : n >> 1);
  }
  return m;
}
constexpr int kScale = kCs + 512;
constexpr int kPlan = kBars + 472;
constexpr int kOnes = kBars + 480;
constexpr int kZero = kBars + 496;
constexpr int kRole = kBars + 508;
constexpr int kEpoch = kBars + 500;
__device__ __forceinline__ int ring_base(int ph) { return ph * 9 - (ph & 1); }
constexpr int kWide = 25;
constexpr int kFirstShared = 15;
constexpr int kNbOrder = 1;
constexpr int kNbWg = 3;
constexpr int kNbPub = 5;
constexpr int kNbWin = 7;
constexpr int kNbSelf = 13;
constexpr int kNbMean = 12;
constexpr int kNbPart = 11;
constexpr int kNbHalo = 9;

constexpr int kFlO = 0;
constexpr int kFlHH = 3;
constexpr int kFlRow = 32;
constexpr int kNumFlags = 16 * kFlRow;

constexpr int kPauseG1 = 7;
constexpr int kPauseG2 = 0;
constexpr int kAhead = 2;
constexpr int kSplit = 13;
constexpr int kTail = 4;
constexpr int kPartAt = 2;
constexpr int kShare = 5;
constexpr int kMost = 8;
constexpr int kBudget = 376;
constexpr int kStepNs = 167;
constexpr int kRemain = 65500;
constexpr int kDone = 3;
constexpr int kPfG1 = 14, kPfG3 = 18;
constexpr int kBackoffNs = 200;
constexpr int kPaceNs = 300;
constexpr int kPartNs = 500;
constexpr int kFillNs = 500;
constexpr int kHaloNs = 150;
constexpr int kGateONs = 150;
constexpr int kGateHNs = 150;
constexpr int kHoldNs = 1200;
constexpr int kSampleNs = 1000;
constexpr int kStatNs = 1500;
constexpr int kGather = 8;
constexpr int kRowNs = 800;
constexpr float kBias1 = 512.f, kBias2 = 512.f, kBias3 = 32768.f;

struct Scratch {
  uint32_t flags[kNumFlags];
  uint32_t epoch[32];
  uint4 stat1[kS];
  uint2 stat2[8 * kS];
  uint4 cs[2 * 8 * 96];
  uint2 wmean[8 * 128];
  uint2 dot[16 * 16 * 128];
  uint2 finish[128];
  uint2 plan[16];
  uint4 halo[2 * 16 * 8 * 6 * 32];
  uint4 part[128 * 8 * 128];
};
struct Params {
  CUtensorMap x, wqkv, o, wo, h, wg, wu, hh, wd, out;
  CUtensorMap ost, hst, hhst;
  CUtensorMap o16, h16;
  const uint4 *wop, *wgp, *wup;
  uint8_t g1[8][32], g2[8][16], g3[8][64], g4[56], g4in[56];
};

__device__ __align__(256) __nv_bfloat16 g_o[kS * kD];
__device__ __align__(256) __nv_bfloat16 g_h[kS * kD];
__device__ __align__(256) __nv_bfloat16 g_hh[kS * kF];
__device__ __align__(256) Scratch g_scratch;

template <bool BY_SM>
__device__ __forceinline__ int role_id() {
  uint32_t sm;
  asm("mov.u32 %0, %%smid;" : "=r"(sm));
  const int tpc = (BY_SM ? sm : blockIdx.x) >> 1, rank = blockIdx.x & 1;
  if ((tpc | 1) == 61) return 8 + 2 * tpc + rank;
  const int u = tpc - 32, s7 = (u * 37) >> 8;
  const int g = tpc < 32 ? tpc & 7 : tpc < 60 ? 1 + u - 7 * s7 : 0, s = tpc < 32 ? tpc >> 3 : tpc < 60 ? 4 + s7 : tpc - 58;
  return (g * 2 + rank) * 8 + s;
}
#define TS(i) do { } while (0)
#define TSK(i) do { } while (0)
#define TSS(i) do { } while (0)
#define TST(i)
#define TSG(i)

__device__ __forceinline__ uint32_t smem_u32(const void* p) { return (uint32_t)__cvta_generic_to_shared(p); }
template <class T>
__device__ __forceinline__ T* plus(T* p, uint32_t n) {
  uint64_t r;
  asm("{\n.reg .b32 lo, hi;\nmov.b64 {lo, hi}, %1;\nadd.cc.u32 lo, lo, %2;\naddc.u32 hi, hi, 0;\nmov.b64 %0, {lo, hi};\n}\n"
      : "=l"(r) : "l"(p), "r"(n * (uint32_t)sizeof(T)));
  return (T*)r;
}
#define SC_AT(member, n) ((decltype(+sc->member))((char*)plus((decltype(+sc->member))sc, n) + offsetof(Scratch, member)))
__device__ __forceinline__ void mbar_init(uint32_t bar, uint32_t cnt) {
  asm volatile("mbarrier.init.shared::cta.b64 [%0], %1;" ::"r"(bar), "r"(cnt));
}
__device__ __forceinline__ void mbar_expect_tx(uint32_t bar, uint32_t bytes) {
  asm volatile("mbarrier.arrive.expect_tx.shared::cta.b64 _, [%0], %1;" ::"r"(bar), "r"(bytes) : "memory");
}
__device__ __forceinline__ uint32_t map_cta(uint32_t addr, uint32_t cta) {
  uint32_t r;
  asm("mapa.shared::cluster.u32 %0, %1, %2;" : "=r"(r) : "r"(addr), "r"(cta));
  return r;
}
__device__ __forceinline__ void mbar_arrive_cluster_if(uint32_t bar, bool cond) {
  asm volatile("{\n.reg .pred p;\nsetp.ne.u32 p, %1, 0;\n@p mbarrier.arrive.shared::cluster.b64 _, [%0];\n}\n"
               ::"r"(bar), "r"((uint32_t)cond) : "memory");
}
__device__ __forceinline__ void mbar_wait(uint32_t bar, uint32_t parity) {
  asm volatile("{\n.reg .pred p;\nLAB_WAIT:\nmbarrier.try_wait.parity.shared::cta.b64 p, [%0], %1;\n@!p bra LAB_WAIT;\n}\n"
               ::"r"(bar), "r"(parity) : "memory");
  return;
  asm volatile("{\n.reg .pred p;\n.reg .u32 c;\nmov.u32 c, 0;\n"
               "LAB_WAIT:\nmbarrier.try_wait.parity.shared::cta.b64 p, [%0], %1;\n@p bra LAB_DONE;\n"
               "add.u32 c, c, 1;\nsetp.lt.u32 p, c, 2000000;\n@p bra LAB_WAIT;\ntrap;\nLAB_DONE:\n}\n"
               ::"r"(bar), "r"(parity) : "memory");
}
__device__ __forceinline__ void mbar_arrive(uint32_t bar) {
  asm volatile("mbarrier.arrive.shared::cta.b64 _, [%0];" ::"r"(bar) : "memory");
}
__device__ __forceinline__ void flag_signal(uint32_t* flag) {
  asm volatile("red.release.gpu.global.add.u32 [%0], 1;" ::"l"(flag) : "memory");
}
__device__ __forceinline__ void st_b128(uint4* p, uint32_t a, uint32_t b, uint32_t c, uint32_t d) {
  asm volatile("{\n.reg .b128 t;\n.reg .b64 lo, hi;\nmov.b64 lo, {%1,%2};\nmov.b64 hi, {%3,%4};\nmov.b128 t, {lo, hi};\n"
               "st.relaxed.gpu.global.b128 [%0], t;\n}\n" ::"l"(p), "r"(a), "r"(b), "r"(c), "r"(d) : "memory");
}
__device__ __forceinline__ uint4 ld_b128(const uint4* p) {
  uint4 v;
  asm volatile("{\n.reg .b128 t;\n.reg .b64 lo, hi;\nld.relaxed.gpu.global.b128 t, [%4];\nmov.b128 {lo, hi}, t;\n"
               "mov.b64 {%0,%1}, lo;\nmov.b64 {%2,%3}, hi;\n}\n" : "=r"(v.x), "=r"(v.y), "=r"(v.z), "=r"(v.w) : "l"(p) : "memory");
  return v;
}
__device__ __forceinline__ uint32_t ld_epoch(Scratch* sc) {
  uint32_t v;
  asm volatile("ld.relaxed.gpu.global.u32 %0, [%1];" : "=r"(v) : "l"(sc->epoch) : "memory");
  return v + 1;
}
__device__ __forceinline__ void flag_wait(uint32_t* flag, uint32_t target) {
  asm volatile("{\n.reg .pred p;\n.reg .u32 c, v;\nmov.u32 c, 0;\n"
               "LAB_WAIT:\nld.relaxed.gpu.global.u32 v, [%0];\nsub.u32 v, v, %1;\nsetp.ge.s32 p, v, 0;\n@p bra LAB_DONE;\n"
               "add.u32 c, c, 1;\nsetp.lt.u32 p, c, 4000000;\n@p bra LAB_WAIT;\ntrap;\nLAB_DONE:\n}\n"
               ::"l"(flag), "r"(target) : "memory");
}
__device__ __forceinline__ void send_word(uint2* p, uint32_t v, uint32_t tag) {
  asm volatile("{\n.reg .b64 t;\nmov.b64 t, {%1, %2};\nst.relaxed.gpu.global.b64 [%0], t;\n}\n" ::"l"(p), "r"(v), "r"(tag) : "memory");
}
template <int NS = 0>
__device__ __forceinline__ uint32_t await_word(const uint2* p, uint32_t tag) {
  uint32_t v;
  asm volatile("{\n.reg .pred p;\n.reg .u32 c, g;\n.reg .b64 t;\nmov.u32 c, 0;\n"
               "LAB_WAIT:\nld.relaxed.gpu.global.b64 t, [%1];\nmov.b64 {%0, g}, t;\nsetp.eq.u32 p, g, %2;\n@p bra LAB_DONE;\n"
               "nanosleep.u32 %3;\nadd.u32 c, c, 1;\nsetp.lt.u32 p, c, 4000000;\n@p bra LAB_WAIT;\ntrap;\nLAB_DONE:\n}\n"
               : "=r"(v) : "l"(p), "r"(tag), "n"(NS) : "memory");
  return v;
}
template <int N>
__device__ __forceinline__ float sum_words(const uint2* src, int stride, uint32_t tag) {
  float sum;
  uint32_t bad;
  int spins = 0;
#pragma unroll 1
  do {
    if (++spins > 2000000) __trap();
    bad = 0;
    sum = 0.f;
#pragma unroll
    for (int i = 0; i < N; i++) {
      uint32_t v, g;
      asm volatile("{\n.reg .b64 t;\nld.relaxed.gpu.global.b64 t, [%2];\nmov.b64 {%0, %1}, t;\n}\n" : "=r"(v), "=r"(g) : "l"(src + i * stride) : "memory");
      sum += __uint_as_float(v);
      bad |= g ^ tag;
    }
    bad = __any_sync(~0u, bad != 0);
    if (bad) __nanosleep(kBackoffNs);
  } while (bad);
  return sum;
}
__device__ __forceinline__ uint32_t global_ns() {
  uint32_t v;
  asm volatile("mov.u32 %0, %%globaltimer_lo;" : "=r"(v));
  return v;
}
__device__ __forceinline__ int fresh_tid() {
  int v;
  asm volatile("mov.u32 %0, %%tid.x;" : "=r"(v));
  return v;
}
constexpr uint32_t kPoison = 0xFFFFFFFFu;
__device__ __forceinline__ bool elect_one() {
  uint32_t p;
  asm volatile("{\n.reg .pred P;\nelect.sync _|P, 0xffffffff;\nselp.u32 %0, 1, 0, P;\n}\n" : "=r"(p));
  return p != 0;
}
__device__ __forceinline__ void fence_async() { asm volatile("fence.acquire.gpu;\nfence.proxy.async.global;" ::: "memory"); }
__device__ __forceinline__ void fence_async_smem() { asm volatile("fence.proxy.async.shared::cta;" ::: "memory"); }
__device__ __forceinline__ void nb_sync(int id, int n) { asm volatile("bar.sync %0, %1;" ::"r"(id), "r"(n) : "memory"); }
__device__ __forceinline__ void nb_arrive(int id, int n) { asm volatile("bar.arrive %0, %1;" ::"r"(id), "r"(n) : "memory"); }

__device__ __forceinline__ void tma2d(uint32_t dst, const CUtensorMap* m, int c0, int c1, uint32_t bar) {
  asm volatile("cp.async.bulk.tensor.2d.shared::cluster.global.mbarrier::complete_tx::bytes [%0], [%1, {%3, %4}], [%2];"
               ::"r"(dst), "l"(m), "r"(bar), "r"(c0), "r"(c1) : "memory");
}
__device__ __forceinline__ void tma2d_mc(uint32_t dst, const CUtensorMap* m, int c0, int c1, uint32_t bar) {
  asm volatile("cp.async.bulk.tensor.2d.shared::cluster.global.mbarrier::complete_tx::bytes.multicast::cluster"
               " [%0], [%1, {%3, %4}], [%2], %5;"
               ::"r"(dst), "l"(m), "r"(bar), "r"(c0), "r"(c1), "h"((uint16_t)3) : "memory");
}
__device__ __forceinline__ void tma3d(uint32_t dst, const CUtensorMap* m, int c0, int c1, int c2, uint32_t bar) {
  asm volatile("cp.async.bulk.tensor.3d.shared::cluster.global.mbarrier::complete_tx::bytes [%0], [%1, {%3, %4, %5}], [%2];"
               ::"r"(dst), "l"(m), "r"(bar), "r"(c0), "r"(c1), "r"(c2) : "memory");
}
__device__ __forceinline__ void tma_store2d(const CUtensorMap* m, uint32_t src, int c0, int c1) {
  asm volatile("cp.async.bulk.tensor.2d.global.shared::cta.bulk_group [%0, {%2, %3}], [%1];"
               ::"l"(m), "r"(src), "r"(c0), "r"(c1) : "memory");
}
__device__ __forceinline__ void tma_store3d(const CUtensorMap* m, uint32_t src, int c0, int c1, int c2) {
  asm volatile("cp.async.bulk.tensor.3d.global.shared::cta.bulk_group [%0, {%2, %3, %4}], [%1];"
               ::"l"(m), "r"(src), "r"(c0), "r"(c1), "r"(c2) : "memory");
}
__device__ __forceinline__ void tma_prefetch2d(const CUtensorMap* m, int c0, int c1) {
  asm volatile("cp.async.bulk.prefetch.tensor.2d.L2.global [%0, {%1, %2}];" ::"l"(m), "r"(c0), "r"(c1) : "memory");
}
__device__ __forceinline__ void prefetch_map(const CUtensorMap* m) { asm volatile("prefetch.tensormap [%0];" ::"l"(m) : "memory"); }
__device__ __forceinline__ void bulk_commit() { asm volatile("cp.async.bulk.commit_group;" ::: "memory"); }
__device__ __forceinline__ void bulk_wait_all() { asm volatile("cp.async.bulk.wait_group 0;" ::: "memory"); }
__device__ __forceinline__ void bulk_wait_read() { asm volatile("cp.async.bulk.wait_group.read 0;" ::: "memory"); }
__device__ __forceinline__ void prefetch_l2(const void* p) { asm volatile("prefetch.global.L2 [%0];" ::"l"(p)); }
__device__ __forceinline__ void cluster_arrive() { asm volatile("barrier.cluster.arrive.relaxed.aligned;" ::: "memory"); }
__device__ __forceinline__ void cluster_wait() { asm volatile("barrier.cluster.wait.aligned;" ::: "memory"); }

__device__ __forceinline__ void wg_fence() { asm volatile("wgmma.fence.sync.aligned;" ::: "memory"); }
__device__ __forceinline__ void wg_commit() { asm volatile("wgmma.commit_group.sync.aligned;" ::: "memory"); }
template <int N> __device__ __forceinline__ void wg_wait() { asm volatile("wgmma.wait_group.sync.aligned %0;" ::"n"(N) : "memory"); }
__device__ __forceinline__ uint32_t desc_lo(uint32_t addr, uint32_t lbo) { return ((addr & 0x3FFFF) >> 4) | ((lbo >> 4) << 16); }
__device__ __forceinline__ uint64_t desc(uint32_t lo) { return (uint64_t)lo | (0x40000040ull << 32); }
__device__ __forceinline__ uint64_t desc_kept(uint32_t lo, uint32_t sb, int id = 0) { return (uint64_t)lo | (uint64_t)(0x40000040u | sb >> (31 - id)) << 32; }
constexpr int kToB = (16384 >> 4) + ((8192 - 16) >> 4 << 16);

__device__ __forceinline__ void wgmma_n128(float (&d)[96], uint64_t da, uint64_t db, int add = 1) {
  asm volatile(
      "{\n.reg .pred p;\nsetp.ne.b32 p, %66, 0;\n"
      "wgmma.mma_async.sync.aligned.m64n128k16.f32.bf16.bf16 {"
      "%0, %1, %2, %3, %4, %5, %6, %7, %8, %9, %10, %11, %12, %13, %14, %15, "
      "%16, %17, %18, %19, %20, %21, %22, %23, %24, %25, %26, %27, %28, %29, %30, %31, "
      "%32, %33, %34, %35, %36, %37, %38, %39, %40, %41, %42, %43, %44, %45, %46, %47, "
      "%48, %49, %50, %51, %52, %53, %54, %55, %56, %57, %58, %59, %60, %61, %62, %63}, "
      "%64, %65, p, 1, 1, 0, 1;\n}\n"
      :
        "+f"(d[0]), "+f"(d[1]), "+f"(d[2]), "+f"(d[3]), "+f"(d[4]), "+f"(d[5]), "+f"(d[6]), "+f"(d[7]),
        "+f"(d[8]), "+f"(d[9]), "+f"(d[10]), "+f"(d[11]), "+f"(d[12]), "+f"(d[13]), "+f"(d[14]), "+f"(d[15]),
        "+f"(d[16]), "+f"(d[17]), "+f"(d[18]), "+f"(d[19]), "+f"(d[20]), "+f"(d[21]), "+f"(d[22]), "+f"(d[23]),
        "+f"(d[24]), "+f"(d[25]), "+f"(d[26]), "+f"(d[27]), "+f"(d[28]), "+f"(d[29]), "+f"(d[30]), "+f"(d[31]),
        "+f"(d[32]), "+f"(d[33]), "+f"(d[34]), "+f"(d[35]), "+f"(d[36]), "+f"(d[37]), "+f"(d[38]), "+f"(d[39]),
        "+f"(d[40]), "+f"(d[41]), "+f"(d[42]), "+f"(d[43]), "+f"(d[44]), "+f"(d[45]), "+f"(d[46]), "+f"(d[47]),
        "+f"(d[48]), "+f"(d[49]), "+f"(d[50]), "+f"(d[51]), "+f"(d[52]), "+f"(d[53]), "+f"(d[54]), "+f"(d[55]),
        "+f"(d[56]), "+f"(d[57]), "+f"(d[58]), "+f"(d[59]), "+f"(d[60]), "+f"(d[61]), "+f"(d[62]), "+f"(d[63])
      : "l"(da), "l"(db), "r"(add));
}

__device__ __forceinline__ void wgmma_n192(float (&d)[96], uint64_t da, uint64_t db, int add = 1) {
  asm volatile(
      "{\n.reg .pred p;\nsetp.ne.b32 p, %98, 0;\n"
      "wgmma.mma_async.sync.aligned.m64n192k16.f32.bf16.bf16 {"
      "%0, %1, %2, %3, %4, %5, %6, %7, %8, %9, %10, %11, %12, %13, %14, %15, "
      "%16, %17, %18, %19, %20, %21, %22, %23, %24, %25, %26, %27, %28, %29, %30, %31, "
      "%32, %33, %34, %35, %36, %37, %38, %39, %40, %41, %42, %43, %44, %45, %46, %47, "
      "%48, %49, %50, %51, %52, %53, %54, %55, %56, %57, %58, %59, %60, %61, %62, %63, "
      "%64, %65, %66, %67, %68, %69, %70, %71, %72, %73, %74, %75, %76, %77, %78, %79, "
      "%80, %81, %82, %83, %84, %85, %86, %87, %88, %89, %90, %91, %92, %93, %94, %95}, "
      "%96, %97, p, 1, 1, 0, 1;\n}\n"
      :
        "+f"(d[0]), "+f"(d[1]), "+f"(d[2]), "+f"(d[3]), "+f"(d[4]), "+f"(d[5]), "+f"(d[6]), "+f"(d[7]),
        "+f"(d[8]), "+f"(d[9]), "+f"(d[10]), "+f"(d[11]), "+f"(d[12]), "+f"(d[13]), "+f"(d[14]), "+f"(d[15]),
        "+f"(d[16]), "+f"(d[17]), "+f"(d[18]), "+f"(d[19]), "+f"(d[20]), "+f"(d[21]), "+f"(d[22]), "+f"(d[23]),
        "+f"(d[24]), "+f"(d[25]), "+f"(d[26]), "+f"(d[27]), "+f"(d[28]), "+f"(d[29]), "+f"(d[30]), "+f"(d[31]),
        "+f"(d[32]), "+f"(d[33]), "+f"(d[34]), "+f"(d[35]), "+f"(d[36]), "+f"(d[37]), "+f"(d[38]), "+f"(d[39]),
        "+f"(d[40]), "+f"(d[41]), "+f"(d[42]), "+f"(d[43]), "+f"(d[44]), "+f"(d[45]), "+f"(d[46]), "+f"(d[47]),
        "+f"(d[48]), "+f"(d[49]), "+f"(d[50]), "+f"(d[51]), "+f"(d[52]), "+f"(d[53]), "+f"(d[54]), "+f"(d[55]),
        "+f"(d[56]), "+f"(d[57]), "+f"(d[58]), "+f"(d[59]), "+f"(d[60]), "+f"(d[61]), "+f"(d[62]), "+f"(d[63]),
        "+f"(d[64]), "+f"(d[65]), "+f"(d[66]), "+f"(d[67]), "+f"(d[68]), "+f"(d[69]), "+f"(d[70]), "+f"(d[71]),
        "+f"(d[72]), "+f"(d[73]), "+f"(d[74]), "+f"(d[75]), "+f"(d[76]), "+f"(d[77]), "+f"(d[78]), "+f"(d[79]),
        "+f"(d[80]), "+f"(d[81]), "+f"(d[82]), "+f"(d[83]), "+f"(d[84]), "+f"(d[85]), "+f"(d[86]), "+f"(d[87]),
        "+f"(d[88]), "+f"(d[89]), "+f"(d[90]), "+f"(d[91]), "+f"(d[92]), "+f"(d[93]), "+f"(d[94]), "+f"(d[95])
      : "l"(da), "l"(db), "r"(add));
}

__device__ __forceinline__ void wgmma_n192_any(float (&d)[96], uint64_t da, uint64_t db) {
  asm volatile(
      "wgmma.mma_async.sync.aligned.m64n192k16.f32.bf16.bf16 {"
      "%0, %1, %2, %3, %4, %5, %6, %7, %8, %9, %10, %11, %12, %13, %14, %15, "
      "%16, %17, %18, %19, %20, %21, %22, %23, %24, %25, %26, %27, %28, %29, %30, %31, "
      "%32, %33, %34, %35, %36, %37, %38, %39, %40, %41, %42, %43, %44, %45, %46, %47, "
      "%48, %49, %50, %51, %52, %53, %54, %55, %56, %57, %58, %59, %60, %61, %62, %63, "
      "%64, %65, %66, %67, %68, %69, %70, %71, %72, %73, %74, %75, %76, %77, %78, %79, "
      "%80, %81, %82, %83, %84, %85, %86, %87, %88, %89, %90, %91, %92, %93, %94, %95}, "
      "%96, %97, 0, 1, 1, 0, 1;\n"
      :
        "=f"(d[0]), "=f"(d[1]), "=f"(d[2]), "=f"(d[3]), "=f"(d[4]), "=f"(d[5]), "=f"(d[6]), "=f"(d[7]),
        "=f"(d[8]), "=f"(d[9]), "=f"(d[10]), "=f"(d[11]), "=f"(d[12]), "=f"(d[13]), "=f"(d[14]), "=f"(d[15]),
        "=f"(d[16]), "=f"(d[17]), "=f"(d[18]), "=f"(d[19]), "=f"(d[20]), "=f"(d[21]), "=f"(d[22]), "=f"(d[23]),
        "=f"(d[24]), "=f"(d[25]), "=f"(d[26]), "=f"(d[27]), "=f"(d[28]), "=f"(d[29]), "=f"(d[30]), "=f"(d[31]),
        "=f"(d[32]), "=f"(d[33]), "=f"(d[34]), "=f"(d[35]), "=f"(d[36]), "=f"(d[37]), "=f"(d[38]), "=f"(d[39]),
        "=f"(d[40]), "=f"(d[41]), "=f"(d[42]), "=f"(d[43]), "=f"(d[44]), "=f"(d[45]), "=f"(d[46]), "=f"(d[47]),
        "=f"(d[48]), "=f"(d[49]), "=f"(d[50]), "=f"(d[51]), "=f"(d[52]), "=f"(d[53]), "=f"(d[54]), "=f"(d[55]),
        "=f"(d[56]), "=f"(d[57]), "=f"(d[58]), "=f"(d[59]), "=f"(d[60]), "=f"(d[61]), "=f"(d[62]), "=f"(d[63]),
        "=f"(d[64]), "=f"(d[65]), "=f"(d[66]), "=f"(d[67]), "=f"(d[68]), "=f"(d[69]), "=f"(d[70]), "=f"(d[71]),
        "=f"(d[72]), "=f"(d[73]), "=f"(d[74]), "=f"(d[75]), "=f"(d[76]), "=f"(d[77]), "=f"(d[78]), "=f"(d[79]),
        "=f"(d[80]), "=f"(d[81]), "=f"(d[82]), "=f"(d[83]), "=f"(d[84]), "=f"(d[85]), "=f"(d[86]), "=f"(d[87]),
        "=f"(d[88]), "=f"(d[89]), "=f"(d[90]), "=f"(d[91]), "=f"(d[92]), "=f"(d[93]), "=f"(d[94]), "=f"(d[95])
      : "l"(da), "l"(db));
}

__device__ __forceinline__ void wgmma_n192_rs(float (&d)[96], uint32_t a0, uint32_t a1, uint32_t a23, uint64_t db) {
  asm volatile(
      "wgmma.mma_async.sync.aligned.m64n192k16.f32.bf16.bf16 {"
      "%0, %1, %2, %3, %4, %5, %6, %7, %8, %9, %10, %11, %12, %13, %14, %15, "
      "%16, %17, %18, %19, %20, %21, %22, %23, %24, %25, %26, %27, %28, %29, %30, %31, "
      "%32, %33, %34, %35, %36, %37, %38, %39, %40, %41, %42, %43, %44, %45, %46, %47, "
      "%48, %49, %50, %51, %52, %53, %54, %55, %56, %57, %58, %59, %60, %61, %62, %63, "
      "%64, %65, %66, %67, %68, %69, %70, %71, %72, %73, %74, %75, %76, %77, %78, %79, "
      "%80, %81, %82, %83, %84, %85, %86, %87, %88, %89, %90, %91, %92, %93, %94, %95}, "
      "{%96, %97, %98, %98}, %99, 1, 1, 1, 1;\n"
      :
        "+f"(d[0]), "+f"(d[1]), "+f"(d[2]), "+f"(d[3]), "+f"(d[4]), "+f"(d[5]), "+f"(d[6]), "+f"(d[7]),
        "+f"(d[8]), "+f"(d[9]), "+f"(d[10]), "+f"(d[11]), "+f"(d[12]), "+f"(d[13]), "+f"(d[14]), "+f"(d[15]),
        "+f"(d[16]), "+f"(d[17]), "+f"(d[18]), "+f"(d[19]), "+f"(d[20]), "+f"(d[21]), "+f"(d[22]), "+f"(d[23]),
        "+f"(d[24]), "+f"(d[25]), "+f"(d[26]), "+f"(d[27]), "+f"(d[28]), "+f"(d[29]), "+f"(d[30]), "+f"(d[31]),
        "+f"(d[32]), "+f"(d[33]), "+f"(d[34]), "+f"(d[35]), "+f"(d[36]), "+f"(d[37]), "+f"(d[38]), "+f"(d[39]),
        "+f"(d[40]), "+f"(d[41]), "+f"(d[42]), "+f"(d[43]), "+f"(d[44]), "+f"(d[45]), "+f"(d[46]), "+f"(d[47]),
        "+f"(d[48]), "+f"(d[49]), "+f"(d[50]), "+f"(d[51]), "+f"(d[52]), "+f"(d[53]), "+f"(d[54]), "+f"(d[55]),
        "+f"(d[56]), "+f"(d[57]), "+f"(d[58]), "+f"(d[59]), "+f"(d[60]), "+f"(d[61]), "+f"(d[62]), "+f"(d[63]),
        "+f"(d[64]), "+f"(d[65]), "+f"(d[66]), "+f"(d[67]), "+f"(d[68]), "+f"(d[69]), "+f"(d[70]), "+f"(d[71]),
        "+f"(d[72]), "+f"(d[73]), "+f"(d[74]), "+f"(d[75]), "+f"(d[76]), "+f"(d[77]), "+f"(d[78]), "+f"(d[79]),
        "+f"(d[80]), "+f"(d[81]), "+f"(d[82]), "+f"(d[83]), "+f"(d[84]), "+f"(d[85]), "+f"(d[86]), "+f"(d[87]),
        "+f"(d[88]), "+f"(d[89]), "+f"(d[90]), "+f"(d[91]), "+f"(d[92]), "+f"(d[93]), "+f"(d[94]), "+f"(d[95])
      : "r"(a0), "r"(a1), "r"(a23), "l"(db));
}

__device__ __forceinline__ uint32_t pack_bf16(float lo, float hi) {
  uint32_t r;
  asm("cvt.rn.bf16x2.f32 %0, %1, %2;" : "=r"(r) : "f"(hi), "f"(lo));
  return r;
}
__device__ __forceinline__ float bf_lo(uint32_t v) { return __uint_as_float(v << 16); }
__device__ __forceinline__ float bf_hi(uint32_t v) { return __uint_as_float(v & 0xFFFF0000u); }
__device__ __forceinline__ float ex2(float x) { float r; asm("ex2.approx.ftz.f32 %0, %1;" : "=f"(r) : "f"(x)); return r; }
__device__ __forceinline__ float rcp(float x) { float r; asm("rcp.approx.ftz.f32 %0, %1;" : "=f"(r) : "f"(x)); return r; }
__device__ __forceinline__ uint32_t movm(uint32_t a) {
  uint32_t d;
  asm volatile("movmatrix.sync.aligned.m8n8.trans.b16 %0, %1;" : "=r"(d) : "r"(a));
  return d;
}
__device__ __forceinline__ void mma16816(float (&c)[4], uint32_t a0, uint32_t a1, uint32_t a2, uint32_t a3, uint32_t b0, uint32_t b1) {
  asm volatile("mma.sync.aligned.m16n8k16.row.col.f32.bf16.bf16.f32 {%0,%1,%2,%3}, {%4,%5,%6,%7}, {%8,%9}, {%0,%1,%2,%3};"
               : "+f"(c[0]), "+f"(c[1]), "+f"(c[2]), "+f"(c[3]) : "r"(a0), "r"(a1), "r"(a2), "r"(a3), "r"(b0), "r"(b1));
}
__device__ __forceinline__ void mma1688(float (&c)[4], uint32_t a0, uint32_t a1, uint32_t b0) {
  asm volatile("mma.sync.aligned.m16n8k8.row.col.f32.bf16.bf16.f32 {%0,%1,%2,%3}, {%4,%5}, {%6}, {%0,%1,%2,%3};"
               : "+f"(c[0]), "+f"(c[1]), "+f"(c[2]), "+f"(c[3]) : "r"(a0), "r"(a1), "r"(b0));
}
__device__ __forceinline__ void stsm4(uint32_t addr, uint32_t a, uint32_t b, uint32_t c, uint32_t d) {
  asm volatile("stmatrix.sync.aligned.m8n8.x4.shared.b16 [%0], {%1,%2,%3,%4};" ::"r"(addr), "r"(a), "r"(b), "r"(c), "r"(d) : "memory");
}
__device__ __forceinline__ void stsm4_t(uint32_t addr, uint32_t a, uint32_t b, uint32_t c, uint32_t d) {
  asm volatile("stmatrix.sync.aligned.m8n8.x4.trans.shared.b16 [%0], {%1,%2,%3,%4};" ::"r"(addr), "r"(a), "r"(b), "r"(c), "r"(d) : "memory");
}
__device__ __forceinline__ void ldsm4(uint32_t addr, uint32_t (&v)[4]) {
  asm volatile("ldmatrix.sync.aligned.m8n8.x4.shared.b16 {%0,%1,%2,%3}, [%4];"
               : "=r"(v[0]), "=r"(v[1]), "=r"(v[2]), "=r"(v[3]) : "r"(addr) : "memory");
}
__device__ __forceinline__ void sts128(uint32_t addr, uint4 v) {
  asm volatile("st.shared.v4.b32 [%0], {%1,%2,%3,%4};" ::"r"(addr), "r"(v.x), "r"(v.y), "r"(v.z), "r"(v.w) : "memory");
}
__device__ __forceinline__ uint4 lds128(uint32_t addr) {
  uint4 v;
  asm volatile("ld.shared.v4.b32 {%0,%1,%2,%3}, [%4];" : "=r"(v.x), "=r"(v.y), "=r"(v.z), "=r"(v.w) : "r"(addr) : "memory");
  return v;
}
__device__ __forceinline__ void sts64(uint32_t addr, uint32_t a, uint32_t b) {
  asm volatile("st.shared.v2.b32 [%0], {%1,%2};" ::"r"(addr), "r"(a), "r"(b) : "memory");
}
__device__ __forceinline__ void sts32(uint32_t addr, uint32_t a) { asm volatile("st.shared.b32 [%0], %1;" ::"r"(addr), "r"(a) : "memory"); }
__device__ __forceinline__ uint32_t lds32(uint32_t addr) {
  uint32_t v;
  asm volatile("ld.shared.b32 %0, [%1];" : "=r"(v) : "r"(addr) : "memory");
  return v;
}
__device__ __forceinline__ float2 lds64f_const(uint32_t addr) {
  float2 v;
  asm("ld.shared.v2.f32 {%0,%1}, [%2];" : "=f"(v.x), "=f"(v.y) : "r"(addr));
  return v;
}
template <int N, bool PAIR>
__device__ __forceinline__ void load_tagged(uint3 (&out)[N], const uint4* src, int stride, uint32_t tag, const uint4* last = nullptr) {
  uint32_t bad;
  int spins = 0;
#pragma unroll 1
  do {
    if (++spins > 2000000) __trap();
    bad = 0;
#pragma unroll
    for (int i = 0; i < N; i++) {
      const uint4 v = ld_b128(N == 5 && i == 4 ? last : src + i * stride);
      out[i] = make_uint3(v.x, v.y, v.z);
      bad |= (v.w ^ tag) | (PAIR ? v.z ^ tag : 0);
    }
    if (N == 4) bad = __any_sync(~0u, bad != 0);
    if (bad) __nanosleep(kBackoffNs);
  } while (bad);
}
__device__ __forceinline__ void sts64f(uint32_t addr, float2 v) { sts64(addr, __float_as_uint(v.x), __float_as_uint(v.y)); }
__device__ __forceinline__ float bf_rest(float v) { return v - __uint_as_float(__float_as_uint(v) & 0xFFFF0000u); }
__device__ __forceinline__ uint32_t bf_upper(float lo, float hi) { return __byte_perm(__float_as_uint(lo), __float_as_uint(hi), 0x7632); }
__device__ __forceinline__ float low_peak(uint4 v) {
  asm("max.xorsign.abs.bf16x2 %0, %0, %1;" : "+r"(v.x) : "r"(v.y));
  asm("max.xorsign.abs.bf16x2 %0, %0, %1;" : "+r"(v.z) : "r"(v.w));
  asm("max.xorsign.abs.bf16x2 %0, %0, %1;" : "+r"(v.x) : "r"(v.z));
  asm("max.xorsign.abs.bf16x2 %0, %0, %1;" : "+r"(v.x) : "r"(v.x << 16));
  return __uint_as_float(__reduce_min_sync(~0u, v.x & 0x7FFF0000u));
}
__device__ __forceinline__ float bias_at(float v) { return __uint_as_float((__float_as_uint(fminf(v, 1e37f)) & 0x7F800000u) | 0x00400000u); }
__device__ __forceinline__ float copy_of(uint32_t v, uint32_t zero, int id) {
  float r;
  asm("{\n.reg .b32 t;\nlop3.b32 t, %1, %2, %3, 0xEA;\nmov.b32 %0, t;\n}\n" : "=f"(r) : "r"(zero), "r"(id + 1), "r"(v));
  return r;
}
struct RowConst {
  float k0, k1, half;
};
__device__ __forceinline__ float gate_scale(float t, const RowConst& k) {
  float th;
  asm("tanh.approx.f32 %0, %1;" : "=f"(th) : "f"(t * fmaf(t * t, k.k1, k.k0)));
  return fmaf(th, k.half, k.half);
}

template <int N>
__device__ __forceinline__ void mma_k16(float (&acc)[2][96], uint32_t a, uint32_t b, int kk, int add = 1) {
#pragma unroll
  for (int m = 0; m < 2; m++) {
    const uint64_t da = desc(a) + (m * 512 + kk * 2), db = desc(b) + kk * 128;
    if (N == 128) wgmma_n128(acc[m], da, db); else wgmma_n192(acc[m], da, db, add);
  }
}

__device__ __forceinline__ void stage_quarter(const float* acc, uint32_t frag, uint32_t frag_x, int b, const uint4* add = nullptr) {
#pragma unroll
  for (int j = 0; j < 4; j++) {
    const float* v = acc + 8 * j;
    uint32_t h[4] = {pack_bf16(v[0], v[1]), pack_bf16(v[2], v[3]), pack_bf16(v[4], v[5]), pack_bf16(v[6], v[7])};
    if (add) {
      const uint32_t a[4] = {add[j].x, add[j].y, add[j].z, add[j].w};
#pragma unroll
      for (int e = 0; e < 4; e++) asm("add.rn.bf16x2 %0, %0, %1;" : "+r"(h[e]) : "r"(a[e]));
    }
    stsm4(frag + b * 8192 + ((frag_x ^ (j * 2)) << 4), h[0], h[1], h[2], h[3]);
  }
}

inline int g1_block(int j, int c) { return j < 16 ? j : ((j + 12) & 15) ^ (c == 5 && j >= 28 ? 2 : 0); }
inline int g2_block(int j, int c) { return j < 8 ? j : j == 8 ? 8 + c : j - (j - 9 < c); }
inline int g3_tile(int j) { return j < 4 ? j >> 1 : j < 18 ? 0 : j >> 4; }
inline int g3_block(int j, int c) {
  const int i = j < 32 ? (j < 16 ? 0xDCBA976543218080ull : 0x7654321BA9FEDCFEull) >> 4 * (j & 15) : j + (~j >> 2 & 4), o = i & 7;
  return 2 * (j < 32 && (o == c || o == 0) ? c - o : o) + (i >> 3 & 1);
}
inline int g4_block(int i) {
  const int n = i * 43 >> 7, j = i - 3 * n, m = j ? n : n + (16 - kFirstShared / 3);
  return i < 48 ? 7 * (m & 7) + 3 * (m >> 3 & 1) + j : 7 * i - 330;
}

constexpr int kInPlace = 16, kInO = 64, kMark = 128;

template <int N, int TAIL>
__device__ __forceinline__ void mainloop(Scratch* sc, float (&acc)[2][96], uint32_t sb, int ph, int j0, int nsteps, int pause_at, bool last,
                                         bool hand_over, bool local, int wg, int own = -1, const CUtensorMap* out = nullptr, int out_col = 0,
                                         int out_row = 0, int warp = 0, __nv_bfloat16* outp = nullptr) {
  constexpr int NSLOT = N == 128 ? 5 : 4, SLOT = N == 128 ? 32768 : 40960;
  const int lane = fresh_tid() & 31;
  const uint32_t full = sb + kBars + 8 * ring_base(ph);
  const uint32_t empty = map_cta(full + 8 * (NSLOT + (ph == 3)), lane & 1);
  const uint32_t ring = desc_lo(sb + kRing, 16);
  int bi = j0 % NSLOT, par = (j0 / NSLOT) & 1;
  const int release_end = lane < (N == 192 && !hand_over ? 4 : 2) ? (last ? nsteps - 1 - NSLOT : nsteps) : 0;
  uint32_t rel = empty;
  const uint32_t special = ph == 0 && wg == 0 ? 3 : pause_at < 0 ? 1 : 1 | 2 << pause_at;
  int i = 0;
#pragma unroll 1
  for (;;) {
    const int end = TAIL <= 0 ? nsteps : !own ? nsteps - TAIL - 1 : i ? i + 2 : kFirstShared;
#pragma unroll 1
    do {
      uint32_t a = ring + bi * (SLOT >> 4), b = a + kToB;
      if (TAIL > 0 ? i == 0 : special >> i & 1) {
        if (i == 0) nb_sync(kNbOrder + wg, ph == 0 && wg == 0 ? 160 : 256);
        else if (ph == 0 && wg == 0) cluster_wait();
        else if (ph < 2) nb_sync(kNbWin + 1, 256);
      }
      if (N == 192 && local) {
        a = ring + ((kStage + i * 16384) >> 4);
        b = ring + bi * (32768 >> 4) + desc_lo(32768, 8192) - desc_lo(0, 16);
      }
      if (ph == 0 && i >> 1 == own) a = ring + ((kOwn + (i & 1) * 16384) >> 4);
      if (ph == 1 && i == 8) a = ring + ((kStage + 32768) >> 4);
      mbar_wait(full + 8 * bi, par);
      if (N == 192 && local) mbar_wait(sb + kBars + 8 * (kHalfBar + i), 0);
      const bool release = (uint32_t)(i - 1) < (uint32_t)release_end;
      wg_fence();
      mma_k16<N>(acc, a, b, 0, ph == 0 ? i | wg : 1);
      mma_k16<N>(acc, a, b, 1);
      wg_commit();
      wg_wait<1>();
      mbar_arrive_cluster_if(rel, release);
      wg_fence();
      mma_k16<N>(acc, a, b, 2);
      mma_k16<N>(acc, a, b, 3);
      wg_commit();
      rel = empty + 8 * bi;
      if (++bi == NSLOT + (TAIL > 0 && i >= kWide - 16)) { bi = 0; par ^= 1; }
      if (ph < 2 && i == pause_at) nb_arrive(kNbWin, 256);
    } while (++i < end);
    if (TAIL <= 0 || own-- == 0) break;
    const uint32_t a = ring + bi * (SLOT >> 4);
    mbar_wait(full + 8 * bi, par);
    wg_fence();
#pragma unroll
    for (int k = 0; k < 4; k++) wgmma_n128(acc[1], desc(a) + (512 + k * 2), desc(a + kToB) + k * 128);
    wg_commit();
    wg_wait<1>();
    mbar_arrive_cluster_if(rel, lane < 2);
    rel = empty + 8 * bi;
    if (++bi == NSLOT + 1) { bi = 0; par ^= 1; }
    i++;
  }
  if (TAIL < 0) return;
  if (TAIL > 0) {
    uint32_t at[TAIL + 2];
    bi = par = 0;
    const int t = fresh_tid() & 127;
    uint32_t frag = sb + kStage + ((t >> 5) * 16 + (t & 15)) * 128, frag_x = ((t >> 4) & 1) ^ (t & 7);
    const uint32_t back = sb + kStage + (t >> 5) * 2048 + ((t >> 3) & 3) * 128, back_x = ((t ^ (t >> 3 & 3)) & 7) << 4;
    outp = plus(outp, (2 * (out_row + (t >> 5) * 16 + ((t >> 3) & 3)) + (blockIdx.x & 1)) * kD + out_col + (t & 7) * 8);
    auto rows = [&](int m, int i0, int i1) {
      wg_fence();
#pragma unroll
      for (int i = 4 * i0; i < 4 * i1; i++)
        wgmma_n128(acc[m], desc_kept(ring, sb, m) + (at[i >> 2] + m * 512 + (i & 3) * 2), desc_kept(ring, sb, m) + (at[i >> 2] + kToB + (i & 3) * 128));
      wg_commit();
    };
    uint4 part[8];
#pragma unroll
    for (int i = 0; i <= TAIL; i++) {
      at[i] = bi * (SLOT >> 4);
      mbar_wait(full + 8 * bi, par);
      if (++bi == NSLOT) { bi = 0; par ^= 1; }
      rows(0, i, i + 1);
      if (i == kPartAt) nb_sync(kNbPart, 256);
      if (i == kPartAt || i == kPartAt + 1) {
#pragma unroll
        for (int k = 4 * (i - kPartAt); k < 4 * (i - kPartAt + 1); k++) part[k] = lds128(sb + kStage + 32768 + (t >> 5) * 4096 + (t & 31) * 16 + k * 512);
      }
    }
    rows(1, 0, 2);
#pragma unroll
    for (int b = 0; b < 4; b++) {
      if (b == 0) wg_wait<1>();
      if (b == 1) rows(1, 3, 4);
      if (b == 2) wg_wait<0>();
      if (!(b & 1)) {
#pragma unroll
        for (int i = 0; i < 64; i++) asm volatile("" : "+f"(acc[b >> 1][i])::"memory");
        if (t == 0) TSS(b);
      }
      stage_quarter(&acc[b >> 1][32 * (b & 1)], frag, frag_x, b, b < 2 ? &part[4 * b] : nullptr);
      if (b == 3) {
        __syncwarp();
        uint4 v[4];
#pragma unroll
        for (int i = 0; i < 4; i++) v[i] = lds128(back + b * 8192 + i * 512 + ((i & 1) ? back_x ^ 64 : back_x));
#pragma unroll
        for (int i = 0; i < 4; i++) __stcs((uint4*)(outp + ((b >> 1) * 128 + i * 8) * kD + (b & 1) * 64), v[i]);
        if (t == 0) TSS(4 + b);
        continue;
      }
      if (b < 2) rows(1, 2 + 2 * b, 3 + 2 * b);
      fence_async_smem();
      __syncwarp();
      if (elect_one()) tma_store3d(out, sb + kStage + b * 8192 + warp * 2048, out_col + (b & 1) * 64, out_row + (b >> 1) * 64 + warp * 16, blockIdx.x & 1);
      __syncwarp();
      if (t == 0) TSS(4 + b);
    }
    if (elect_one()) {
      bulk_commit();
      bulk_wait_read();
    }
    if (t == 0) TSS(1);
    return;
  }
  if (hand_over) nb_arrive(kNbOrder + (wg ^ 1), 256);
  if (N == 192 && !local) {
    if (j0 < 32) mbar_wait(sb + kBars + 8 * kStatBar, 1);
    mbar_wait(sb + kBars + 8 * (kStgBar + wg), ((j0 >> 5) ^ wg ^ 1) & 1);
  }
  wg_wait<0>();
  mbar_arrive_cluster_if(rel, release_end == nsteps);
#pragma unroll
  for (int i = 0; i < N / 2; i++) asm volatile("" : "+f"(acc[0][i]), "+f"(acc[1][i])::"memory");
}

template <int PH>
struct Ring {
  static constexpr int NSLOT = 4 + (PH & 1), SLOT = PH & 1 ? 32768 : 40960;
  uint32_t full, dst0;
  int j = PH == 0 ? 4 : 0, bi = 0, par = PH == 0 ? 0 : 1;
  __device__ __forceinline__ Ring(uint32_t sb, uint32_t ofs) : full(sb + kBars + 8 * (PH * 9 - (PH & 1))), dst0(sb + kRing + ofs) {}
  __device__ __forceinline__ uint32_t bar() const { return full + 8 * bi; }
  __device__ __forceinline__ uint32_t dst() const { return dst0 + bi * SLOT; }
  __device__ __forceinline__ void acquire_first() const {
    const bool first = j < NSLOT;
    mbar_wait(full + (first ? 8 * min(j, 3) - 32 : 8 * (NSLOT + (PH == 3) + bi)), PH == 2 && first ? 0 : par);
  }
  __device__ __forceinline__ void acquire() const { mbar_wait(full + 8 * (NSLOT + (PH == 3) + bi), par); }
  __device__ __forceinline__ void next() {
    j++;
    if (++bi == NSLOT + (PH == 3 && j > kWide)) { bi = 0; par ^= 1; }
  }
};

__device__ __forceinline__ void check_blocks(const Params& p, Scratch* sc, uint32_t sb, int r, int c, bool g3, uint32_t& par) {
  const int lane = fresh_tid() & 31, nslot = g3 ? 4 : 5, slot_bytes = g3 ? 40960 : 32768;
  const uint32_t mine = (lane >> 2) * 132 + (lane & 3) * 32, ring_end = sb + kRing + kStage + mine;
  const uint32_t to_full = 8 * (kLandBar - (g3 ? ring_base(2) : ring_base(1)));
  uint32_t src = sb + kRing + mine + (g3 ? 0 : 4 * 32768);
  int bi = g3 ? 0 : 4, spins = 0;
#pragma unroll 1
  for (int i = g3 ? 2 : 9; i < 16;) {
    const uint32_t land = sb + kBars + 8 * (kLandBar + bi);
    mbar_wait(land, (par >> bi) & 1);
    uint32_t v[16];
#pragma unroll
    for (int k = 0; k < 16; k++) v[k] = lds32(src + k * 1024);
#pragma unroll
    for (int k = 0; k < 5; k++) v[k] = max(max(v[3 * k + 1], v[3 * k + 2]), k ? v[3 * k] : max(v[0], v[15]));
    const bool again = __any_sync(~0u, max(max(max(v[0], v[1]), v[2]), max(v[3], v[4])) == kPoison);
    asm volatile("{\n.reg .pred p;\nsetp.eq.u32 p, %1, 0;\n@p mbarrier.arrive.shared::cta.b64 _, [%0];\n}\n"
                 ::"r"(land - to_full), "r"(lane + again) : "memory");
    par ^= 1u << bi;
    if (again) {
      if (++spins > 100000) __trap();
      if (elect_one()) {
        mbar_expect_tx(land, 16384);
        tma2d(src - mine, g3 ? &p.h : &p.o, ((g3 ? p.g3[c][i + 2] : p.g2[c][i]) & 15) * 64, r * 128, land);
      }
      nb_sync(kNbSelf + 1, 32);
      continue;
    }
    if (lane == 0 && (i == 2 || i == 3 || (!g3 && (i == 9 || i == 12)))) TS(i < 4 ? 88 + 2 * i : i == 9 ? 120 : 122);
    i++;
    if (++bi == nslot) bi = 0;
    src += slot_bytes;
    if (src == ring_end) src -= kStage;
  }
}

__device__ __forceinline__ void colsum_cta(const Params& p, Scratch* sc, uint32_t sb, int warp, int bid) {
  constexpr int kSlots = 4, kSlot = 49152;
  constexpr int kRows = kMost * 16384, kIn = (kCs - kRows) / 8192;
  const int lane = threadIdx.x & 31, c0 = (bid - 128) * 2;
  const uint32_t full = sb + kBars, empty = full + 8 * kSlots;
  const uint32_t event = full + 64, rfull = full + 128, rempty = full + 256;
  if (threadIdx.x == 0) {
#pragma unroll 1
    for (int i = 0; i < 48; i++) mbar_init(full + 8 * i, i & (i < 16 ? 4 : 32) ? 8 : 1);
    asm volatile("fence.mbarrier_init.release.cluster;" ::: "memory");
  }
  __syncthreads();
  const uint32_t ep = ld_epoch(sc);
  if (warp == 8) {
    if (elect_one()) {
#pragma unroll 1
      for (int n = 0; n < 32 + kSlots; n++) {
        const int u = n >> 4, c = c0 + ((n >> 3) & 1), k0 = (n & 7) * 128, slot = n & (kSlots - 1);
        const uint32_t bar = full + 8 * slot;
        mbar_wait(empty + 8 * slot, ((n / kSlots) & 1) ^ 1);
        if (u == 2) continue;
        mbar_expect_tx(bar, 49152);
#pragma unroll
        for (int a = 0; a < 6; a++) tma2d(sb + slot * kSlot + a * 8192, &p.wqkv, ((a % 3) * 16 + u * 8 + c) * 64, k0 + (a / 3) * 64, bar);
      }
      mbar_arrive(event);
#pragma unroll 1
      for (int i = 0; i < 4 * kMost; i++) tma_prefetch2d(&p.wd, (c0 * 2 + (i & 3)) * 64, (i >> 2) * (7 * 64));
      mbar_wait(event + 8, 0);
      asm volatile("fence.proxy.async.global;" ::: "memory");
      int slot = 0, par = 1, w = 0;
#pragma unroll 1
      for (int job = 0; job < 32; job++) {
        const int k = lds32(sb + kPlan + (job >> 4) * 4) >> (job & 14) * 2 & 15;
        if (job == 16) {
          mbar_wait(rempty + 8 * (slot ? slot - 1 : kIn - 1), par ^ (slot != 0));
          w = 0;
        }
#pragma unroll 1
        for (int i = 0; i < k; i++) {
          const uint32_t bar = rfull + 8 * slot;
          mbar_wait(bar + 128, par);
          mbar_expect_tx(bar, w < kMost ? 24576 : 8192);
          tma2d(sb + kRows + slot * 8192, &p.ost, i * 64, (job & 15) * 128, bar);
          if (w < kMost) {
#pragma unroll
            for (int a = 0; a < 2; a++)
              tma2d(sb + w * 16384 + a * 8192, &p.wd, ((c0 + (job >> 4)) * 2 + a) * 64, w * (7 * 64), bar);
            w++;
          }
          if (++slot == kIn) { slot = 0; par ^= 1; }
        }
      }
    }
  } else if (warp < 8) {
    uint32_t src[3];
#pragma unroll
    for (int j = 0; j < 3; j++) src[j] = sb + ((warp * 3 + j) >> 3) * 8192 + lane * 128 + ((((warp * 3 + j) & 7) ^ (lane & 7)) << 4);
    const uint32_t ones = 0x3F803F80u;
#pragma unroll 1
    for (int s = 0; s < 32; s++) {
      float a[3][2][4] = {};
#pragma unroll 1
      for (;; s++) {
        const int slot = s & (kSlots - 1);
        mbar_wait(full + 8 * slot, (s / kSlots) & 1);
        uint32_t b[3][4][4];
#pragma unroll
        for (int j = 0; j < 3; j++)
#pragma unroll
          for (int k = 0; k < 4; k++)
            asm volatile("ldmatrix.sync.aligned.m8n8.x4.trans.shared.b16 {%0,%1,%2,%3}, [%4];"
                         : "=r"(b[j][k][0]), "=r"(b[j][k][1]), "=r"(b[j][k][2]), "=r"(b[j][k][3])
                         : "r"(src[j] + slot * kSlot + (k >> 1) * 24576 + (k & 1) * 4096) : "memory");
        __syncwarp();
        if (lane == 0) mbar_arrive(empty + 8 * slot);
#pragma unroll
        for (int k = 0; k < 4; k++)
#pragma unroll
          for (int j = 0; j < 3; j++) {
            mma16816(a[j][0], ones, ones, ones, ones, b[j][k][0], b[j][k][1]);
            mma16816(a[j][1], ones, ones, ones, ones, b[j][k][2], b[j][k][3]);
          }
        if ((s & 7) == 7) break;
      }
      {
        if (lane < 12) {
          const int j = lane >> 2;
          const float x = j == 0 ? a[0][0][0] + a[0][1][0] : j == 1 ? a[1][0][0] + a[1][1][0] : a[2][0][0] + a[2][1][0];
          const float y = j == 0 ? a[0][0][1] + a[0][1][1] : j == 1 ? a[1][0][1] + a[1][1][1] : a[2][0][1] + a[2][1][1];
          const float x1 = bf_rest(x), y1 = bf_rest(y);
          st_b128(SC_AT(cs, ((s >> 4) * 8 + c0 + ((s >> 3) & 1)) * 96 + warp * 12 + lane), bf_upper(x, y),
                  bf_upper(x1, y1), bf_upper(bf_rest(x1), bf_rest(y1)), ep);
        }
        if (threadIdx.x == 0 && (s & 8)) TSK(s >> 4);
      }
    }
    const int wg = warp >> 2;
    mbar_wait(event + 8, 0);
#pragma unroll 1
    for (int job = wg, first = 0; job < 32; job += 2) {
      const int k = __shfl_sync(~0u, lds32(sb + kPlan + (job >> 4) * 4), 0) >> (job & 14) * 2 & 15;
      if (k == 0) continue;
      float acc[96];
#pragma unroll
      for (int i = 0; i < 64; i++) asm volatile("" : "=f"(acc[i]));
      static_assert(kIn == 12, "");
      int slot = first + wg * k, par = slot * 171 >> 11, i = 0;
      slot -= par * kIn;
      first += 2 * k;
      uint32_t done = 0;
      if (job) nb_sync(kNbOrder + wg, 256);
#pragma unroll 1
      do {
        mbar_wait(rfull + 8 * slot, par & 1);
        wg_fence();
#pragma unroll
        for (int kk = 0; kk < 4; kk++)
          wgmma_n128(acc, desc(desc_lo(sb + kRows, 16) + slot * 512) + kk * 2, desc(desc_lo(sb, 8192) + i * 1024) + kk * 128, kk | i);
        wg_commit();
        wg_wait<1>();
        if (lane < 2 && i) mbar_arrive(done);
        done = rempty + 8 * slot;
        if (++slot == kIn) { slot = 0; par++; }
      } while (++i < k);
      nb_arrive(kNbOrder + (wg ^ 1), 256);
      uint4* dst = SC_AT(part, ((job & 15) * 8 + c0 + (job >> 4)) * 1024 + (warp & 3) * 256 + lane);
      wg_wait<0>();
#pragma unroll
      for (int i = 0; i < 64; i++) asm volatile("" : "+f"(acc[i])::"memory");
      if (lane < 2) mbar_arrive(done);
#pragma unroll
      for (int i = 0; i < 8; i++) {
        const float* v = &acc[8 * i];
        asm volatile("st.relaxed.gpu.global.v4.b32 [%0], {%1, %2, %3, %4};"
                     ::"l"(dst + i * 32),
                     "r"(pack_bf16(v[0], v[1])), "r"(pack_bf16(v[2], v[3])), "r"(pack_bf16(v[4], v[5])), "r"(pack_bf16(v[6], v[7])) : "memory");
      }
    }
    if (threadIdx.x == 128) TSK(7);
  } else if (warp == 10) {
    mbar_wait(event, 0);
    int late = await_word<500>(sc->finish + (uint32_t)((lane & 15) * 8 + c0 + (lane >> 4)), ep);
    __nanosleep(1000);
    flag_wait(sc->flags + kFlHH + (lane & 15) * kFlRow, ep * 8);
    __syncwarp();
    late -= __shfl_sync(~0u, late, 0);
    late = max(late, __shfl_xor_sync(~0u, late, 1));
    late = max(min(late - (__reduce_add_sync(~0u, late) >> 5) + kShare * kStepNs, 4096), -4096);
    int k;
#pragma unroll 1
    do {
      k = min(max((late * (8192 / kStepNs) >> 13) + 1, (lane & 14) == 0), kMost);
      late -= kStepNs / 4;
    } while (__reduce_add_sync(~0u, k ? max(2 * k, k + 4) : 0) > kBudget);
    k <<= (lane & 14) * 2;
#pragma unroll
    for (int o = 2; o < 16; o <<= 1) k |= __shfl_xor_sync(~0u, k, o);
    asm volatile("fence.acquire.gpu;" ::: "memory");
    send_word(sc->plan + (uint32_t)(c0 + (lane >> 4)), k, ep);
    sts32(sb + kPlan + (lane >> 4) * 4, k);
    __syncwarp();
    if (lane == 0) mbar_arrive(event + 8);
  }
}

#define PROF_BEGIN
template <bool BY_SM>
__global__ void __cluster_dims__(2, 1, 1) __launch_bounds__(kThreads, 1) fused_block_kernel(Scratch* sc, const __nv_bfloat16* xp, const __nv_bfloat16* wqkvp, __nv_bfloat16* outp,
                                                                   const __grid_constant__ Params p) {
  extern __shared__ __align__(1024) uint8_t smem_raw[];
  if (threadIdx.x == 256) {
    prefetch_map(&p.x);
    prefetch_map(&p.wqkv);
  }
  if (threadIdx.x < 56) {
    const int l = threadIdx.x & 31, b = blockIdx.x & 127;
    if (threadIdx.x < 32) prefetch_l2(xp + (b * 16 + (l & 15)) * kD + (l >> 4) * 64);
    else prefetch_l2(wqkvp + b * (3 * kD) + (l >> 3) * kD + (l & 7) * 64);
  }
  const uint32_t sb = smem_u32(smem_raw);
  const int bid = role_id<BY_SM>();
  const int r = bid >> 3, c = bid & 7, rank = blockIdx.x & 1;
  auto first_fill = [&](int j) {
    const uint32_t fb = sb + kBars + 8 * j, dst = sb + kRing + j * 40960;
    mbar_expect_tx(fb, 40960);
    tma3d(j >> 1 == c ? sb + kOwn + (j & 1) * 16384 : dst, &p.x, j * 64, (r >> 1) * 128, rank, fb);
#pragma unroll
    for (int a = 0; a < 3; a++) tma2d(dst + 16384 + a * 8192, &p.wqkv, a * kD + c * 64, j * 64, fb);
    mbar_arrive(fb);
  };
  const int tid = threadIdx.x, warp = __shfl_sync(~0u, tid >> 5, 0), wg = warp >> 2;
  if (bid >= 128) {
    if (tid == 0) PROF_BEGIN;
    colsum_cta(p, sc, sb, warp, bid);
    return;
  }
  if (wg == 2) {
    if (warp == 8 && elect_one()) {
      mbar_init(sb + kBars, 2);
      asm volatile("fence.mbarrier_init.release.cluster;" ::: "memory");
      first_fill(0);
#pragma unroll
      for (int j = 1; j < 4; j++) mbar_init(sb + kBars + 8 * j, 2);
      asm volatile("fence.mbarrier_init.release.cluster;" ::: "memory");
      TSS(0);
    }
    __syncwarp();
    if (warp == 8) nb_arrive(kNbOrder, 160);
    asm volatile("setmaxnreg.dec.sync.aligned.u32 40;");
    if (warp == 8) {
      cluster_arrive();
      if (elect_one()) {
#pragma unroll 1
        for (int j = 1; j < 4; j++) first_fill(j);
        TSS(1);
      }
      __syncwarp();
    } else {
      if (elect_one()) {
        uint64_t shifts = warp == 9 ? bar_shifts(4) : warp == 10 ? bar_shifts(22) : bar_shifts(40);
#pragma unroll 1
        for (int i = 0; i < 18; i++, shifts >>= 3) mbar_init(sb + kBars + 8 * (18 * warp - 158 + i), 1u << (shifts & 7));
        if (warp == 10) asm volatile("mbarrier.arrive.shared::cta.b64 _, [%0], 2;" ::"r"(sb + kBars + 8 * 31) : "memory");
        sts32(sb + kZero, 0);
        sts32(sb + kScale + 4, 0);
        sts32(sb + kRole, bid);
        sts128(sb + kOnes, make_uint4(0x3F803F80u, 0, 0, 0x3F803F80u));
        asm volatile("fence.mbarrier_init.release.cluster;" ::: "memory");
      }
      __syncwarp();
      cluster_arrive();
    }
    cluster_wait();
    const uint32_t ep = ld_epoch(sc);
    if (tid == 320) sts32(sb + kEpoch, ep);
    if (tid == 320) PROF_BEGIN;
    const int pw = warp & 3;
    if (pw == 0) {
      if (elect_one()) {
        const int row = r * 128;
        const uint32_t land = sb + kBars + 8 * kLandBar;
#pragma unroll 1
        for (Ring<0> q(sb, 0); q.j < 32; q.next()) {
          q.acquire();
          const int kb = p.g1[c][q.j];
          if (kb & kInPlace) { mbar_arrive(q.bar()); continue; }
          mbar_expect_tx(q.bar(), 16384);
          tma3d(kb >> 1 == c ? sb + kOwn + (kb & 1) * 16384 : q.dst(), &p.x, kb * 64, (r >> 1) * 128, rank, q.bar());
        }
        prefetch_map(&p.o);
        prefetch_map(&p.o16);
        flag_wait(sc->flags + kFlO + r * kFlRow, ep * 8);
        fence_async();
        TS(40);
#pragma unroll 1
        for (Ring<1> q(sb, 0); q.j < 16; q.next()) {
          q.acquire_first();
          if (q.j == 8) {
            prefetch_map(&p.wg);
            prefetch_map(&p.wu);
            prefetch_map(&p.h);
            prefetch_map(&p.h16);
            mbar_wait(sb + kBars + 8 * kSentBar, 0);
            mbar_arrive(q.bar());
            mbar_arrive(sb + kBars + 8 * (kStgBar + 1));
            __nanosleep(kGateONs);
            continue;
          }
          const uint32_t bar = q.j < 8 ? q.bar() : land + 8 * q.bi;
          if (q.j == 9) TS(41);
          mbar_expect_tx(bar, 16384);
          tma2d(q.dst(), &p.o, p.g2[c][q.j] * 64, row, bar);
        }
#pragma unroll 1
        for (Ring<2> q(sb, 0); q.j < 64; q.next()) {
          q.acquire_first();
          const int kb = p.g3[c][q.j];
          if (kb & kInPlace) { mbar_arrive(q.bar()); continue; }
          if (q.j == 4) { __nanosleep(kGateHNs); TS(42); }
          const uint32_t bar = q.j < 18 ? land + 8 * q.bi : q.bar();
          mbar_expect_tx(bar, 16384);
          tma2d(q.dst(), &p.h, (kb & 15) * 64, row, bar);
        }
        prefetch_map(&p.hh);
        prefetch_map(&p.out);
        Ring<3> q(sb, 0);
#pragma unroll 1
        for (; q.j < 16; q.next()) {
          q.acquire_first();
          if (q.j == 0) { mbar_arrive(q.bar()); continue; }
          mbar_expect_tx(q.bar(), 16384);
          tma2d(q.dst(), &p.h, ((q.j + 9) & 15) * 64, row, q.bar());
        }
        uint32_t wave = sb + kBars + 8 * kWaveBar;
        mbar_wait(wave, 0);
        fence_async();
        int share = lds32(sb + kPlan);
#pragma unroll 1
        for (; q.j < 72; q.next()) {
          const int kb = p.g4in[q.j - 16];
          if (kb >> 6 == kMark >> 6) {
            wave += 8;
            mbar_wait(wave, 0);
            fence_async();
          }
          q.acquire();
          const bool half = kb >= (kMark | kInO) && --share >= 0;
          mbar_expect_tx(q.bar(), half ? 8192 : 16384);
          tma2d(q.dst() + half * 8192, half ? &p.ost : kb & kInO ? &p.o : &p.hh, (kb & 63) * 64, row + half * 64, q.bar());
        }
      }
    } else if (pw == 1) {
      if (elect_one()) {
        const int rp = r >> 1;
#pragma unroll 1
        for (Ring<0> q(sb, 16384); q.j < 32; q.next()) {
          q.acquire();
          mbar_expect_tx(q.bar(), 24576);
          const int col = ((q.j >> 4) * 8 + c) * 64, k0 = (p.g1[c][q.j] & 15) * 64;
          tma2d_mc(q.dst() + rank * 8192, &p.wqkv, rank * kD + col, k0, q.bar());
          if ((q.j & 1) == rank) tma2d_mc(q.dst() + 16384, &p.wqkv, 2 * kD + col, k0, q.bar());
          if (q.j == max(r, 4))
            for (int a = 0; a < 3; a++) tma_prefetch2d(&p.wqkv, a * kD + (8 + c) * 64, ((r + 12) & 15) * 64);
          const int d = q.j - kPfG1 - (r >> 2);
          if (d == 0 || d == 6) {
            const int f = c * 7 + (d >> 1);
            tma_prefetch2d(&p.wg, f * 64, r * 64);
            tma_prefetch2d(&p.wu, f * 64, r * 64);
            tma_prefetch2d(&p.wg, (f + 1) * 64, r * 64);
          }
        }
#pragma unroll 1
        for (Ring<1> q(sb, 16384 + rank * 8192); q.j < 16; q.next()) {
          q.acquire_first();
          mbar_expect_tx(q.bar(), 16384);
          tma2d_mc(q.dst(), &p.wo, (c * 2 + rank) * 64, p.g2[c][q.j] * 64, q.bar());
        }
        const CUtensorMap* mine = rank ? &p.wu : &p.wg;
#pragma unroll 1
        for (Ring<2> q(sb, 16384); q.j < 64; q.next()) {
          const int kb = p.g3[c][q.j], tile = kb >> 5, f0 = c * 7 + (tile & 1) * 3, fp = f0 + (tile & 2);
          const int k0 = (kb & 15) * 64;
          q.acquire_first();
          mbar_expect_tx(q.bar(), 24576);
          const uint32_t dst = q.j < 4 ? sb + kRing + (q.j + 1) * 32768 : q.dst();
          tma2d_mc(dst + rank * 8192, mine, fp * 64, k0, q.bar());
          if ((q.j & 1) == rank) tma2d_mc(dst + 16384, tile & 2 ? &p.wu : &p.wg, (f0 + 1) * 64, k0, q.bar());
          const int d = q.j - kPfG3 - (r >> 2);
          if (d >= 0 && !(d & 15)) {
            const int f = c * 7 + (d == 0 ? 2 : d == 16 ? 5 : 6);
            tma_prefetch2d(&p.wg, f * 64, r * 64);
            tma_prefetch2d(&p.wu, f * 64, r * 64);
            if (d != 32) tma_prefetch2d(&p.wu, (f - 1) * 64, r * 64);
          }
        }
        Ring<3> q(sb, 16384 + rank * 8192);
#pragma unroll 1
        for (; q.j < 16; q.next()) {
          q.acquire_first();
          mbar_expect_tx(q.bar(), 16384);
          tma2d_mc(q.dst(), mine, (c * 7 + 6) * 64, ((q.j + 9) & 15) * 64, q.bar());
          if (q.j >> 1 == rp) tma_prefetch2d(&p.wd, (c * 2 + rank) * 64, p.g4[q.j] * 64);
        }
#pragma unroll 1
        for (; q.j < 72; q.next()) {
          q.acquire();
          mbar_expect_tx(q.bar(), 16384);
          tma2d_mc(q.dst(), &p.wd, (c * 2 + rank) * 64, p.g4[q.j - 16] * 64, q.bar());
          if ((q.j & 15) >> 1 == rp && q.j < 56) tma_prefetch2d(&p.wd, (c * 2 + rank) * 64, p.g4[q.j] * 64);
        }
      }
    } else {
      const int cw = pw - 2;
      const uint32_t stg = sb + kStage + cw * 32768, rb = sb + kBars + 8 * kResBar;
      uint32_t land_par = 0;
      sts64(sb + kPlan, global_ns(), clock());
      if (cw == 0) {
#pragma unroll 1
        for (int i = 0; i < 16; i++) sts128(sb + kFill + i * 512 + (tid & 31) * 16, make_uint4(kPoison, kPoison, kPoison, kPoison));
        __nanosleep(kSampleNs);
        const uint32_t l15 = tid & 15;
        const uint4 os = __ldg(plus(p.wop, (tid & 31) * 128 + c * 16 + l15));
        const uint4 gs = __ldg(plus(tid & 16 ? p.wup : p.wgp, l15 * 451 + c * 56));
        const uint4 ws = __ldg(plus((const uint4*)wqkvp, (tid & 7) * 385 + (tid & 24) * 16 + (8 + c) * 8));
        const float wo = low_peak(os);
        sts128(sb + kScale, make_uint4(__float_as_uint(wo * kBias3 * low_peak(gs)), __float_as_uint(low_peak(ws) * kBias1) | 1, __float_as_uint(wo * kBias2), 0));
        if (tid == 320) TS(93);
        if (elect_one()) {
          const uint4* rows = plus(p.wop, (c * 64 + (r & 7) * 8 + (r >> 3) * 512) * 128);
          asm volatile("cp.async.bulk.prefetch.L2.global [%0], 16384;" ::"l"(rows) : "memory");
          __nanosleep(kRowNs);
          mbar_expect_tx(sb + kBars + 8 * kRowBar, 16384);
          asm volatile("cp.async.bulk.shared::cluster.global.mbarrier::complete_tx::bytes [%0], [%1], 16384, [%2];"
                       ::"r"(stg), "l"(rows), "r"(sb + kBars + 8 * kRowBar) : "memory");
        }
        nb_sync(kNbSelf, 32);
      }
      {
        mbar_wait(sb + kBars + 8 * kRowBar, 0);
        float s = 0.f;
#pragma unroll 1
        for (int i = 0; i < 16; i++) {
          const uint4 v = lds128(sb + kStage + (tid & 56) * 256 + (tid & 7) * 16 + i * 128);
          s += ((bf_lo(v.x) + bf_hi(v.x)) + (bf_lo(v.y) + bf_hi(v.y))) + ((bf_lo(v.z) + bf_hi(v.z)) + (bf_lo(v.w) + bf_hi(v.w)));
        }
#pragma unroll
        for (int o = 1; o < 8; o <<= 1) s += __shfl_xor_sync(~0u, s, o);
        send_word(SC_AT(wmean, c * 128 + r * 8 + (tid >> 3 & 7)), __float_as_uint(s * (1.f / kD)), ep);
        if (tid == 320) TS(109);
      }
#pragma unroll 1
      for (int ev = -1; ev < 4; ev++) {
        const bool quads = cw == 0 && ev == 1;
        if (ev >= cw && !quads) nb_sync(kNbPub + cw, 160);
        if (ev >= cw && elect_one()) {
          if (quads) {
            mbar_wait(sb + kBars + 8 * (kHalfBar + 1), 0);
#pragma unroll 1
            for (int i = 0; i < 2; i++) {
              __nanosleep(i ? kPaceNs : kHoldNs);
              tma_store2d(&p.hst, stg + 16384 + i * 8192, c * 128 + 64, r * 128 + i * 64);
              TS(100 + i);
            }
            bulk_commit();
            bulk_wait_read();
            mbar_arrive(sb + kBars + 8 * kStgBar);
          } else {
            if (ev == 1) {
              const uint32_t now = global_ns();
              const float left = (float)(now - lds32(sb + kPlan)) * (float)kRemain * rcp((float)((uint32_t)clock() - lds32(sb + kPlan + 4)));
              send_word(sc->finish + (uint32_t)bid, now + (uint32_t)left, ep);
            }
            const int it = ev - 2 + cw, f0 = c * 7 + (1 - cw) * 3, fp = it == 2 ? c * 7 + 6 : it ? f0 + 2 : c + 8 - 8 * cw;
            const bool is_o = ev == 0;
            const CUtensorMap* m = it <= 0 ? &p.ost : &p.hhst;
            const int b0 = is_o ? c : f0 + 1, b1 = fp;
#pragma unroll 1
            for (int i = is_o || it == 1 ? 0 : 2; i < (is_o ? 2 : 4); i++) {
              tma_store2d(m, stg + i * 8192, (i < 2 ? b0 : b1) * 64, r * 128 + (i & 1) * 64);
              if (!is_o) {
                bulk_commit();
                bulk_wait_read();
                __nanosleep(kPaceNs);
              }
            }
            bulk_commit();
            bulk_wait_all();
            mbar_arrive(sb + kBars + 8 * (kStgBar + cw));
            if (ev == 3 + cw) {
#pragma unroll
              for (int i = 0; i < 2; i++) asm volatile("mbarrier.arrive.shared::cluster.b64 _, [%0], 4;" ::"r"(map_cta(sb + kBars + 8 * 37, i)) : "memory");
            }
            flag_signal(SC_AT(flags, kFlHH + ev * 2 - 3 + cw + r * kFlRow));
            TS(44 + cw * 8 + ev);
            if (ev == 2 && cw) {
              sts32(sb + kPlan, await_word(sc->plan + (uint32_t)c, ep) >> (r >> 1) * 4 & 15);
              mbar_expect_tx(rb, 16384);
#pragma unroll 1
              for (int i = 0; i < 2; i++) tma2d(stg + 8192 + i * 16384, &p.hst, c * 128 + i * 64, r * 128 + 64, rb);
            }
          }
        }
        nb_sync(kNbSelf + cw, 32);
        if (ev >= 2 && ev + cw >= 3 && elect_one()) {
          const int wv = cw == 0 ? 3 : ev == 2 ? 0 : 4;
#pragma unroll 1
          for (int i = wv; i <= max(wv, 2); i++) flag_wait(SC_AT(flags, kFlHH + i + r * kFlRow), ep * 8);
          fence_async();
          mbar_arrive(sb + kBars + 8 * (kWaveBar + (wv >> 1)));
          if (wv == 4) {
            mbar_expect_tx(sb + kBars + 8 * kPartBar, 16384);
#pragma unroll 1
            for (int i = 0; i < 2; i++) tma2d(stg + 16384 + i * 8192, &p.hst, c * 128 + i * 64, r * 128, sb + kBars + 8 * kPartBar);
          }
        }
        nb_sync(kNbSelf + cw, 32);
#pragma unroll 1
        for (int sub = 0; ev < cw; sub++) {
          nb_sync(kNbSelf + cw, 32);
          if (ev == 0) check_blocks(p, sc, sb, r, c, sub, land_par);
          const int u = ev < 0 ? cw : 2, lane = fresh_tid() & 31;
          if (u == 1 && !sub) {
            uint3 st[5];
            load_tagged<5, true>(st, SC_AT(stat1, r * 128 + lane), 32, ep, SC_AT(stat1, (r < 2 ? r : r - 2) * 128 + (lane & 7)) + 120);
#pragma unroll
            for (int i = 0; i < 4; i++) sts64(sb + kStat + (i * 32 + lane) * 8, st[i].x, st[i].y);
            sts64(sb + kStat - 64 + (lane & 7) * 8, st[4].x, st[4].y);
            nb_sync(kNbSelf + cw, 32);
            if (lane < 4) mbar_arrive(sb + kBars + 8 * kStatBar);
            if (lane == 0) TS(17);
          }
          if (u == 1) {
            const uint4* gh = SC_AT(halo, (sub * 128 + bid) * 192 + lane) - 16 * 192;
            uint4 hv[6] = {};
            nb_sync(kNbHalo, 64);
            uint32_t ns = sub ? kHaloNs : 2 * kBackoffNs;
#pragma unroll 1
            for (int spins = 0; r >= 2; spins++) {
              if (ns) __nanosleep(ns);
              ns = sub ? 0 : kBackoffNs;
              if (spins > 2000000) __trap();
#pragma unroll
              for (int i = 0; i < 6; i++) hv[i] = ld_b128(gh + i * 32);
              uint32_t bad = (hv[5].y ^ ep) | (hv[5].z ^ ep);
#pragma unroll
              for (int i = 0; i < 6; i++) bad |= hv[i].w ^ ep;
              if (!__any_sync(~0u, bad != 0)) break;
            }
            const uint32_t dst = sb + kStage + sub * 32768 + lane * 16;
            sts128(dst, make_uint4(hv[0].x, hv[0].y, hv[0].z, hv[1].x));
            sts128(dst + 512, make_uint4(hv[1].y, hv[1].z, hv[2].x, hv[2].y));
            sts128(dst + 1024, make_uint4(hv[2].z, hv[3].x, hv[3].y, hv[3].z));
            sts128(dst + 1536, make_uint4(hv[4].x, hv[4].y, hv[4].z, hv[5].x));
            nb_arrive(kNbHalo + 1, 64);
            if (lane == 0) TS(123 + sub);
          }
          if (sub) break;
          if (ev == 0) continue;
          uint3 v[3];
          load_tagged<3, false>(v, SC_AT(cs, c * 96 + u * 768 + lane), 32, ep);
#pragma unroll
          for (int i = 0; i < 3; i++)
#pragma unroll
            for (int k = 0; k < 8; k++)
              sts32(sb + kAug + cw * 4096 + i * 1024 + k * 128 + ((lane * 4) ^ (k * 16)), k == 7 ? 0x3F803F80u : k == 4 || k == 6 ? v[i].z : k & 1 && k != 5 ? v[i].y : v[i].x);
          fence_async_smem();
          nb_sync(kNbSelf + cw, 32);
          if (lane == 0) { mbar_arrive(sb + kBars + 8 * (kAuxBar + cw)); TS(104 + u); }
        }
        nb_sync(kNbSelf + cw, 32);
        if (ev < 0 && cw == 0 && elect_one()) {
#pragma unroll 1
          for (int i = 0; i < 6; i++) {
            __nanosleep(i == 0 ? (c >> 1) * (kFillNs / 4) : kFillNs);
            tma_store2d(i < 2 ? &p.ost : &p.hst, sb + kFill, i < 2 ? (8 + c) * 64 : (c * 2 - 1 + (i >> 1)) * 64, r * 128 + (i & 1) * 64);
            bulk_commit();
          }
          uint32_t peer;
          asm volatile("ld.shared::cluster.b32 %0, [%1];" : "=r"(peer) : "r"(map_cta(sb + kRole, rank ^ 1)) : "memory");
          if (peer != (bid ^ 8)) __trap();
          TS(90);
        }
        nb_sync(kNbSelf + cw, 32);
      }
    }
  } else {
    if (tid == 0) TSS(2);
    cluster_arrive();
    float bias = 0.f;
    float sx = 0.f, mx = 0.f;
    asm volatile("setmaxnreg.inc.sync.aligned.u32 232;");
    if (tid == 0) TSS(4);
    int task;
    asm volatile("mov.u32 %0, %1;" : "=r"(task) : "r"(8 - wg));

#pragma unroll 1
    for (task = __shfl_sync(~0u, task, 0);; task++) {
      if (task == 1 + wg || task == 9 - wg) {
        const int t = fresh_tid();
        uint4 scale;
        do scale = lds128(sb + kScale);
        while (scale.y == 0);
        __syncwarp();
        const float peak = low_peak(lds128(sb + (task > 5 ? kRing : kStage + wg * 32768) + (t & 126) * 64 + (t & 14) * 8 + (t & 1) * 8192));
        bias = bias_at(peak * __uint_as_float(task > 5 ? scale.y : scale.x));
        sts32(sb + kScale + 16 + warp * 4, __float_as_uint(bias_at(peak * __uint_as_float(scale.z))));
        __syncwarp();
        if (t == 128 && task > 5) TS(95);
      }
      if (wg == 0 && (task == 1 || task == 4)) {
        float acc[2][96];
        const int t = fresh_tid() & 127;
        const uint32_t frag = sb + kOwn + ((t >> 5) * 16 + (t & 15)) * 128, frag_x = ((t >> 4) & 1) ^ (t & 7);
        TSG(2);
        if (task == 4) mbar_wait(sb + kBars + 8 * kResBar, 0);
        const uint32_t means = sb + kStat + ((t >> 5) * 16 + (t >> 2 & 7)) * 8 + 4;
        float add[2];
#pragma unroll
        for (int i = 0; i < 2; i++) add[i] = __uint_as_float(lds32(task == 1 ? sb + kScale + 16 + warp * 4 : means + 512 + i * 64));
        auto residual = [&](int m) {
#pragma unroll
          for (int i = 0; i < 8; i++) {
            uint32_t v[4];
            ldsm4(frag + (i >> 2) * 16384 + m * 8192 + ((frag_x ^ (i * 2 & 6)) << 4), v);
#pragma unroll
            for (int e = 0; e < 4; e++) {
              float* d = &acc[m][8 * i + 2 * e];
              asm("shl.b32 %0, %1, 16;" : "=f"(d[0]) : "r"(v[e]));
              asm("and.b32 %0, %1, 0xFFFF0000;" : "=f"(d[1]) : "r"(v[e]));
              asm("add.f32 %0, %0, %1;" : "+f"(d[0]) : "f"(add[e & 1]));
              asm("add.f32 %0, %0, %1;" : "+f"(d[1]) : "f"(add[e & 1]));
            }
          }
        };
        residual(1);
        if (task == 1) {
          residual(0);
        } else {
          const uint32_t m0 = lds32(means), m1 = lds32(means + 64), z = fresh_tid() >> 10;
#pragma unroll
          for (int i = 0; i < 64; i++) acc[0][i] = copy_of(i & 2 ? m1 : m0, z, i);
        }
        __syncwarp();
        if ((t & 31) == 0) mbar_arrive(sb + kBars + 8 * kResFreeBar);
        TSG(4);
        if ((tid & 127) == 0) TS(task == 1 ? 6 : 14);
        if (task == 4) {
          mainloop<128, kTail>(sc, acc, sb, 3, 16, 56, -2, true, false, false, 0, __shfl_sync(~0u, lds32(sb + kPlan), 0), &p.out, c * 128, (r >> 1) * 128, warp, outp);
          if ((tid & 127) == 0) TSK(15);
          if (fresh_tid() == 0) {
            if (bid == 0) __stcg(sc->epoch, lds32(sb + kEpoch));
            TSK(19);
          }
          break;
        }
        mainloop<128, -1>(sc, acc, sb, 1, 0, 15, kPauseG2, false, true, false, 0);
        const int t2 = fresh_tid() & 127;
        const uint32_t frag2 = sb + kStage + ((t2 >> 5) * 16 + (t2 & 15)) * 128, frag2_x = ((t2 >> 4) & 1) ^ (t2 & 7);
        const uint32_t empty = map_cta(sb + kBars + 8 * (ring_base(1) + 5), t2 & 1);
        mbar_wait(sb + kBars + 8 * kStgBar, 0);
        float sub[4];
        auto terms = [&] {
          const float bias2 = __uint_as_float(lds32(sb + kScale + 16 + warp * 4));
#pragma unroll
          for (int i = 0; i < 4; i++) sub[i] = __uint_as_float(lds32(sb + kStat + ((t2 >> 5) * 16 + (t2 >> 2 & 7)) * 8 + 4 + (i >> 1) * 512 + (i & 1) * 64)) + bias2;
        };
        mbar_wait(sb + kBars + 8 * ring_base(1), 1);
#pragma unroll
        for (int m = 0; m < 2; m++) {
          const uint32_t a = desc_lo(sb + kRing, 16);
          wg_fence();
#pragma unroll
          for (int k = 0; k < 4; k++) wgmma_n128(acc[m], desc_kept(a, sb) + (m * 512 + k * 2), desc_kept(a, sb) + (kToB + k * 128));
          wg_commit();
          if (m) {
            nb_arrive(kNbOrder + 1, 256);
            if (t2 == 0) TS(107);
            nb_sync(kNbMean, 256);
            if (t2 == 0) TS(108);
            terms();
          }
          wg_wait<1>();
          if (!m) mbar_arrive_cluster_if(empty + 8 * 4, (t2 & 31) < 2);
        }
#pragma unroll
        for (int b = 0; b < 4; b++) {
          if (b == 1) {
            wg_wait<0>();
            if (t2 == 0) TSK(7);
          }
          if (b < 2) {
#pragma unroll
            for (int i = 0; i < 64; i++) asm volatile("" : "+f"(acc[b][i])::"memory");
          }
#pragma unroll
          for (int i = 32 * (b >> 1); i < 32 * (b >> 1) + 32; i++) acc[b & 1][i] -= sub[(b & 1) * 2 + (i >> 1 & 1)];
          stage_quarter(&acc[b & 1][32 * (b >> 1)], frag2, frag2_x, b);
          if (b & 1) {
            fence_async_smem();
            __syncwarp();
            if (elect_one()) {
              mbar_arrive(sb + kBars + 8 * (kHalfBar + (b >> 1)));
#pragma unroll
              for (int m = 0; m < 2; m++)
                if (b == 1) tma_store2d(&p.h16, sb + kStage + m * 8192 + warp * 2048, c * 128, r * 128 + m * 64 + warp * 16);
            }
            __syncwarp();
          }
        }
        if (t2 == 0) TS(8);
        sx = mx = 0.f;
        continue;
      }
      float acc[2][96];
      if (task == 8 + wg) {
        wg_fence();
#pragma unroll
        for (int m = 0; m < 2; m++) wgmma_n192_any(acc[m], desc(64 + m), desc(64 + m));
        wg_commit();
        wg_wait<0>();
#pragma unroll
        for (int i = 0; i < 96; i++) asm volatile("" : "+f"(acc[0][i]), "+f"(acc[1][i])::"memory");
      } else {
        const uint32_t z = fresh_tid() >> 10;
#pragma unroll
        for (int i = 0; i < 96; i++) {
#pragma unroll
          for (int m = 0; m < 2; m++)
            acc[m][i] = copy_of(__float_as_uint(bias), z, 2 * i + m);
        }
      }
      if (task > 5) {
        if (wg) {
          if (task == 7) cluster_wait();
          if (tid == 128 && task == 7) { TSS(5); TSK(69); }
          const int t = fresh_tid() & 127, lr = c * 16 + (t >> 3);
          uint32_t pf = t < 64 ? (bid * 16 + (t >> 2)) * kD + (t & 3) * 64 : (r * 48 + t - 64) * kD + c * 64;
          const uint32_t src = sb + kRing + lr * 128 + (((t ^ lr) & 7) << 4), empty = map_cta(sb + kBars + 8 * 4, t & 1), zero = fresh_tid() >> 10;
#pragma unroll 1
          for (int j = task == 7 ? 0 : kSplit; j < (task == 7 ? kSplit : 16); j++) {
            mbar_wait(sb + kBars + 8 * (j & 3), (j >> 2) & 1);
            if (j < 2 && t == 0) TS(102 + j);
            const uint4 v = lds128(src + (j >> 1 == c ? kOwn + (j & 1) * 16384 : (j & 3) * 40960));
            __syncwarp();
            mbar_arrive_cluster_if(empty + 8 * (j & 3) + (v.x & zero), (t & 31) < 2);
            if ((j == 0 || j == 3 || j == 6) && t < 112) { pf += t < 64 ? 256 : 256 * 3 * kD; prefetch_l2(plus(t < 64 ? xp : wqkvp, pf)); }
            const uint32_t u[4] = {v.x, v.y, v.z, v.w};
#pragma unroll
            for (int e = 0; e < 4; e++) {
              const float d0 = bf_lo(u[e]), d1 = bf_hi(u[e]);
              sx += d0 + d1;
              mx = fmaf(d1, d1, fmaf(d0, d0, mx));
            }
          }
          if (task == 7) {
            if (t == 0) TS(96);
            continue;
          }
#pragma unroll
          for (int o = 4; o > 0; o >>= 1) { sx += __shfl_xor_sync(~0u, sx, o); mx += __shfl_xor_sync(~0u, mx, o); }
          const float mean = sx * (1.f / kD);
          float rstd;
          asm("rsqrt.approx.ftz.f32 %0, %1;" : "=f"(rstd) : "f"(fmaxf(mx * (1.f / kD) - mean * mean, 0.f) + 1e-5f));
          const uint32_t ep = lds32(sb + kEpoch);
          const int t2 = fresh_tid();
          if ((t2 & 7) == 0) st_b128(SC_AT(stat1, bid * 16 + (t2 >> 3 & 15)), __float_as_uint(rstd), __float_as_uint(-mean), ep, ep);
          if (t == 0) TS(16);
        }
        if (tid == 0) TSS(6);
        mainloop<192, -1>(sc, acc, sb, 0, wg * 16, wg ? 16 - kAhead : 16, wg ? kPauseG1 : -2, false, wg == 0, false, wg,
                          wg ? min((c + 2) & 7, 6) : c);
        int t = fresh_tid() & 127, lane = t & 31, g = lane >> 2, q = lane & 3;
        const int w = warp & 3;
        const uint32_t stg = sb + kStage + wg * 32768;
        auto tail = [&](int m, int k0, int k1) {
          wg_fence();
#pragma unroll
          for (int k = k0; k < k1; k++) {
            const uint64_t a = desc_kept(desc_lo(sb + kRing, 16), sb) + (4 - kAhead + (k >> 2)) * (40960 >> 4);
            wgmma_n192(acc[m], a + (m * 512 + (k & 3) * 2), a + (kToB + (k & 3) * 128));
          }
        };
        auto release = [&](int j, bool cond) { mbar_arrive_cluster_if(map_cta(sb + kBars + 8 * (4 + (j & 3)), lane & 1), cond); };
        if (wg) {
#pragma unroll
          for (int j = 32 - kAhead; j < 32; j++) {
            TST(2 * (j & 1));
            mbar_wait(sb + kBars + 8 * (j & 3), 1);
            TST(2 * (j & 1) + 1);
            tail(1, 4 * (j - 32 + kAhead), 4 * (j - 31 + kAhead));
            wg_commit();
            if (j == 32 - kAhead) {
              wg_wait<1>();
              release(j - 1, lane < 4);
              mbar_wait(sb + kBars + 8 * kResFreeBar, 0);
            }
          }
        } else {
          nb_arrive(kNbOrder + 1, 256);
          wg_wait<0>();
          release(15, lane < 2);
          if (t == 0) TSK(1);
        }
        TST(4);
        mbar_wait(sb + kBars + 8 * (kAuxBar + wg), 0);
        mbar_wait(sb + kBars + 8 * kStatBar, 0);
        {
          uint32_t am[4];
#pragma unroll
          for (int i = 0; i < 4; i++) {
            const float m1 = __uint_as_float(lds32(sb + kStat + (w * 16 + g) * 8 + 4 + (i >> 1) * 512 + (i & 1) * 64));
            const float m2 = bf_rest(m1), lo = q & 1 ? m2 : m1;
            am[i] = bf_upper(lo, q == 3 ? -bias : q == 2 ? bf_rest(m2) : lo);
          }
          const uint64_t db = (uint64_t)desc_lo(sb + kAug + wg * 4096, 1024) | (0x40000000ull << 32);
          TST(5);
          wg_fence();
          wgmma_n192_rs(acc[1], am[2], am[3], 0u, db);
          wg_commit();
          TST(6);
          wg_fence();
          wgmma_n192_rs(acc[0], am[0], am[1], 0u, db);
          wg_commit();
          if (wg) {
            tail(0, 0, 4 * kAhead);
            wg_commit();
            wg_wait<2>();
          } else {
            wg_wait<1>();
          }
          TST(8);
#pragma unroll
          for (int i = 0; i < 96; i++) asm volatile("" : "+f"(acc[1][i])::"memory");
        }
        t = fresh_tid() & 127, lane = t & 31;
        const uint32_t ep = lds32(sb + kEpoch);
        uint32_t pk[2][48];
        auto fold = [&](int pp, int jn, int hf) {
          const uint32_t v = pack_bf16(acc[pp][4 * jn + 2 * hf], acc[pp][4 * jn + 2 * hf + 1]);
          pk[pp][2 * jn + hf] = jn >= 16 ? movm(v) : v;
        };
        if (t == 96) TS(115 + wg);
#pragma unroll
        for (int jn = 8; jn < 24; jn++) fold(1, jn, 1);
        if (w < 3) {
#pragma unroll
          for (int i = 0; i < 4; i++)
            sts128(stg + (w + 5) * 2048 + i * 512 + lane * 16, make_uint4(pk[1][17 + 8 * i], pk[1][19 + 8 * i], pk[1][21 + 8 * i], pk[1][23 + 8 * i]));
        } else if (r < 14) {
          uint4* gh = SC_AT(halo, (wg * 128 + bid) * 192 + lane);
#pragma unroll
          for (int i = 0; i < 6; i++) st_b128(gh + i * 32, pk[1][17 + 6 * i], i < 5 ? pk[1][(19 + 6 * i) % 48] : ep, i < 5 ? pk[1][(21 + 6 * i) % 48] : ep, ep);
          if (wg == 0) {
#pragma unroll 1
            for (int i = 0; i < 6; i++, gh += 32) st_b128(gh + 128 * 192, 0, 0, 0, ep - 1);
          }
        }
        if (w == 3) nb_arrive(kNbHalo, 64);
        if (wg) nb_arrive(kNbOrder, 256);
        TST(9);
        if (t == 96) TS(111 + wg);
#pragma unroll
        for (int jn = 23; jn >= 0; jn--) {
          fold(1, jn, 0);
          if (jn < 8) fold(1, jn, 1);
        }
        t = fresh_tid() & 127, lane = t & 31, g = lane >> 2, q = lane & 3;
        const bool sel0 = 2 * q > g, sel1 = 2 * q + 1 > g, no_prev = (r < 2 && w == 0);
        const uint4 ones = lds128(sb + kOnes);
        const uint32_t lowmask = (sel0 ? 0x0000FFFFu : 0u) | (sel1 ? 0xFFFF0000u : 0u) | ones.y;
        float rs[4][2], rk[4][2];
#pragma unroll
        for (int i = 0; i < 4; i++) {
          const uint32_t a = sb + kStat + w * 128 + (i >> 1) * 512 + (i & 1) * 64;
          const float rq = __uint_as_float(lds32(a + g * 8)) * (0.17677669529663687f * 1.4426950408889634f);
          rk[i][0] = __uint_as_float(lds32(a + q * 16 - (sel0 ? 64 : 0)));
          rk[i][1] = __uint_as_float(lds32(a + q * 16 + 8 - (sel1 ? 64 : 0)));
          rs[i][0] = rk[i][0] * rq;
          rs[i][1] = rk[i][1] * rq;
        }
        {
          uint32_t all = ~0u;
#pragma unroll
          for (int i = 0; i < 48; i++) if (i < 16 || !(i & 1)) all &= pk[1][i];
          if (all == kPoison) sts32(sb + kZero + 8, 0);
        }
        TST(10);
        wg_wait<0>();
        TST(11);
#pragma unroll
        for (int j = 32 - kAhead; j < 32; j++) release(j, lane < 4 * wg && (w != 0 || j < 31));
#pragma unroll
        for (int i = 0; i < 96; i++) asm volatile("" : "+f"(acc[0][i])::"memory");
        if (t == 0 && wg) TSK(21);
#pragma unroll
        for (int jn = 8; jn < 24; jn++) fold(0, jn, 1);
#pragma unroll
        for (int i = 0; i < 4; i++)
          sts128(stg + (w + 1) * 2048 + i * 512 + lane * 16, make_uint4(pk[0][17 + 8 * i], pk[0][19 + 8 * i], pk[0][21 + 8 * i], pk[0][23 + 8 * i]));
#pragma unroll
        for (int jn = 23; jn >= 0; jn--) {
          fold(0, jn, 0);
          if (jn < 8) fold(0, jn, 1);
        }
        if (t == 0) TS(113 + wg);
        nb_sync(kNbWg + wg, 128);
        uint32_t hal[2][16];
        auto load_halo = [&](int m) {
#pragma unroll
          for (int i = 0; i < 4; i++) {
            const uint4 v = lds128(stg + w * 2048 + m * 8192 + i * 512 + lane * 16);
            uint32_t* h = &hal[m][i * 4];
            h[0] = v.x; h[1] = v.y; h[2] = v.z; h[3] = v.w;
          }
        };
        load_halo(1);
        if (w == 0) {
          nb_sync(kNbHalo + 1, 64);
          release(31, lane < 4 * wg);
        }
        load_halo(0);
        __syncwarp();
        if (t == 0) TS(2 + wg * 20);
        {
          uint32_t all = lowmask;
#pragma unroll
          for (int i = 0; i < 32; i++) if (i < 16 || !(i & 1)) all &= pk[0][i];
#pragma unroll
          for (int i = 0; i < 8; i++) all &= __float_as_uint(rs[i >> 1][i & 1]);
          if (all == kPoison) sts32(sb + kZero + 8, 0);
        }
        if (wg == 0) {
          const int t0 = fresh_tid();
          sts32(sb + kCs + t0 * 4, await_word<kBackoffNs>(SC_AT(wmean, c * 128 + t0), lds32(sb + kEpoch)));
          __syncwarp();
        }
        nb_sync(kNbWin, 256);
        if (t == 0) TS(9 + wg * 20);
        const uint32_t zero = lds32(sb + kZero);
        float s0[4][4], s1[4][4], s2[4][4];
#pragma unroll
        for (int k = 0; k < 4; k++) {
          pk[k >> 1][8 * (k & 1)] |= zero;
#pragma unroll
          for (int e = 0; e < 4; e++) s0[k][e] = s1[k][e] = s2[k][e] = 0.f;
        }
#pragma unroll
        for (int ks = 0; ks < 2; ks++)
#pragma unroll
          for (int k = 0; k < 4; k++) {
            const uint32_t* qf = &pk[k >> 1][8 * (k & 1) + 4 * ks];
            const uint32_t* kf = &pk[k >> 1][16 + 8 * (k & 1) + 4 * ks];
            const uint32_t* hf = &hal[k >> 1][4 * (k & 1) + 2 * ks];
            mma16816(s0[k], qf[0], qf[1], qf[2], qf[3], hf[0], hf[1]);
            mma16816(s1[k], qf[0], qf[1], qf[2], qf[3], kf[0], kf[2]);
            mma16816(s2[k], qf[0], qf[1], qf[2], qf[3], kf[1], kf[3]);
          }
        float ea[4][2], eb[4][2], ma[4], mb[4];
#pragma unroll
        for (int k = 0; k < 4; k++) {
          const float *ra = rs[k & 2], *rb = rs[(k & 2) + 1];
          if (no_prev && k < 2) s0[k][0] = s0[k][1] = -INFINITY;
          ea[k][0] = (sel0 ? s0[k][0] : s1[k][0]) * ra[0]; ea[k][1] = (sel1 ? s0[k][1] : s1[k][1]) * ra[1];
          eb[k][0] = (sel0 ? s1[k][2] : s2[k][2]) * rb[0]; eb[k][1] = (sel1 ? s1[k][3] : s2[k][3]) * rb[1];
          ma[k] = fmaxf(ea[k][0], ea[k][1]); mb[k] = fmaxf(eb[k][0], eb[k][1]);
        }
#pragma unroll
        for (int o = 1; o < 4; o <<= 1)
#pragma unroll
          for (int k = 0; k < 4; k++) {
            ma[k] = fmaxf(ma[k], __shfl_xor_sync(~0u, ma[k], o));
            mb[k] = fmaxf(mb[k], __shfl_xor_sync(~0u, mb[k], o));
          }
        float ov[4][4][4], ls[4][4];
        uint32_t all = 0;
#pragma unroll
        for (int k = 0; k < 4; k++) {
          const float *ra = rk[k & 2], *rb = rk[(k & 2) + 1];
          ea[k][0] = ex2(ea[k][0] - ma[k]); ea[k][1] = ex2(ea[k][1] - ma[k]);
          eb[k][0] = ex2(eb[k][0] - mb[k]); eb[k][1] = ex2(eb[k][1] - mb[k]);
          const uint32_t pa = pack_bf16(ea[k][0] * ra[0], ea[k][1] * ra[1]), pb = pack_bf16(eb[k][0] * rb[0], eb[k][1] * rb[1]);
          const uint32_t* vf = &pk[k >> 1][32 + 8 * (k & 1)];
          const uint32_t* hf = &hal[k >> 1][8 + 4 * (k & 1)];
#pragma unroll
          for (int d2 = 0; d2 < 2; d2++) {
#pragma unroll
            for (int e = 0; e < 4; e++) ov[k][d2][e] = ov[k][2 + d2][e] = 0.f;
            mma1688(ov[k][d2], hf[2 * d2], hf[2 * d2 + 1], pa & lowmask);
            mma1688(ov[k][2 + d2], vf[4 * d2], vf[4 * d2 + 2], pb & lowmask);
          }
#pragma unroll
          for (int d2 = 0; d2 < 2; d2++) {
            mma1688(ov[k][d2], vf[4 * d2], vf[4 * d2 + 2], pa & ~lowmask);
            mma1688(ov[k][2 + d2], vf[4 * d2 + 1], vf[4 * d2 + 3], pb & ~lowmask);
          }
          ls[k][0] = ls[k][1] = ls[k][2] = ls[k][3] = 0.f;
          mma16816(ls[k], ones.x, ones.y, ones.z, ones.w, pack_bf16(ea[k][0], ea[k][1]), pack_bf16(eb[k][0], eb[k][1]));
          if (k >= kDone) all |= pa & pb;
        }
#pragma unroll
        for (int k = 0; k < 4; k++) {
          if (k == kDone) {
            if (all == 0xFFFFFFFFu) sts32(sb + kZero + 8, 0);
            nb_arrive(kNbWin + 1, 256);
            all = 0;
          }
          all |= (__float_as_uint(ov[k][0][0]) & __float_as_uint(ov[k][1][0]) & __float_as_uint(ov[k][2][0])) &
                 (__float_as_uint(ov[k][3][0]) & __float_as_uint(ls[k][0]));
        }
        const uint32_t nil = lds32(sb + kZero);
        const uint32_t frag = stg + (w * 16 + (lane & 15)) * 128, frag_x = (lane >> 4) ^ (lane & 7);
        uint32_t after = all;
#pragma unroll
        for (int k = 0; k < 4; k++) {
          uint32_t h[2][4];
#pragma unroll
          for (int hf = 0; hf < 2; hf++) {
            const float i0 = rcp(__uint_as_float(__float_as_uint(ls[k][2 * hf]) | (after & nil)));
            const float i1 = rcp(__uint_as_float(__float_as_uint(ls[k][2 * hf + 1]) | (after & nil)));
#pragma unroll
            for (int e = 0; e < 4; e++) h[e >> 1][2 * (e & 1) + hf] = pack_bf16(ov[k][2 * hf + (e >> 1)][2 * (e & 1)] * i0, ov[k][2 * hf + (e >> 1)][2 * (e & 1) + 1] * i1);
            after = h[0][hf];
          }
#pragma unroll
          for (int d2 = 0; d2 < 2; d2++) stsm4_t(frag + (k >> 1) * 8192 + ((frag_x ^ ((k & 1) * 4 + d2 * 2)) << 4), h[d2][0], h[d2][1], h[d2][2], h[d2][3]);
        }
        fence_async_smem();
        if (wg) {
          __syncwarp();
          if (elect_one()) {
            tma_store2d(&p.o16, stg + w * 2048, (8 + c) * 64, r * 128 + w * 16);
            tma_store2d(&p.o16, stg + 8192 + w * 2048, (8 + c) * 64, r * 128 + 64 + w * 16);
            bulk_commit();
            bulk_wait_read();
            mbar_arrive(sb + kBars + 8 * kSentBar);
          }
          __syncwarp();
        } else {
          nb_arrive(kNbPub, 160);
        }
        if (t == 0) TS(3 + wg * 20);
        {
          const int l = fresh_tid() & 31;
          const uint32_t ep = lds32(sb + kEpoch);
          __syncwarp();
          const uint4 ua = lds128(sb + kCs + wg * 256 + (l & 7) * 32), ub = lds128(sb + kCs + wg * 256 + (l & 7) * 32 + 16);
          float mine = 0.f;
#pragma unroll 1
          for (int i = 0; i < 4; i++) {
            const int n = i * 4 + (l >> 3);
            float d[2];
#pragma unroll
            for (int m = 0; m < 2; m++) {
              const uint4 v = lds128(stg + w * 2048 + m * 8192 + n * 128 + (((l ^ n) & 7) << 4));
              float a = bf_lo(v.x) * __uint_as_float(ua.x), b = bf_hi(v.x) * __uint_as_float(ua.y);
              a = fmaf(bf_lo(v.y), __uint_as_float(ua.z), a); b = fmaf(bf_hi(v.y), __uint_as_float(ua.w), b);
              a = fmaf(bf_lo(v.z), __uint_as_float(ub.x), a); b = fmaf(bf_hi(v.z), __uint_as_float(ub.y), b);
              a = fmaf(bf_lo(v.w), __uint_as_float(ub.z), a); b = fmaf(bf_hi(v.w), __uint_as_float(ub.w), b);
              d[m] = a + b;
            }
            float e = (l & 4 ? d[1] : d[0]) + __shfl_xor_sync(~0u, l & 4 ? d[0] : d[1], 4);
            e += __shfl_xor_sync(~0u, e, 1);
            e += __shfl_xor_sync(~0u, e, 2);
            if (i == (l & 3)) mine = e;
          }
          uint2* dst = SC_AT(dot, (r * 16 + wg * 8 + c) * 128 + w * 16 + (l & 3) * 4 + (l & 4) * 16 + (l >> 3));
          send_word(dst, __float_as_uint(mine), ep);
          if (l == 0 && w == 0) TS(97 + wg);
          if (wg == 0) send_word(dst + 8 * 128, 0, ep - 1);
        }
        task = wg;
        sx = mx = bias = 0.f;
        continue;
      }

      if (task == 2 && wg) {
        const int t = fresh_tid() & 127;
        float sum = -__uint_as_float(lds32(sb + kStat + t * 8 + 4));
#pragma unroll 1
        for (int i = 0; i < 16; i += kGather) sum += sum_words<kGather>(SC_AT(dot, (r * 16 + i) * 128 + t), 128, lds32(sb + kEpoch));
        nb_sync(kNbWg + 1, 128);
        sts32(sb + kStat + t * 8 + 4, __float_as_uint(sum));
        nb_arrive(kNbMean, 256);
        if (t == 0) TS(99);
      }
      {
#pragma unroll 1
        for (int part = task != 2; part < 2; part++) {
          if ((tid & 127) == 0) TS(6 + 2 * task + wg * 20);
          if (task + part == 5) {
            mainloop<128, 0>(sc, acc, sb, 3, 0, 16, -2, false, true, false, 1);
            continue;
          }
          const int j0 = task == 3 ? 48 - wg * 16 : part == 0 ? 2 - 2 * wg : 18 - 14 * wg;
          mainloop<192, 0>(sc, acc, sb, 2, j0, task != 2 ? 16 : part == 0 ? 2 : 14, -2, false, true, part == 0, wg);
          if (part == 0 && wg == 0) {
            const int t = fresh_tid() & 127;
            const uint32_t ep = lds32(sb + kEpoch);
            {
              float s0 = 0.f, s1 = 0.f;
#pragma unroll 1
              for (int i = 0; i < 16; i++) {
                const uint4 v = lds128(sb + kStage + t * 128 + (i >> 3) * 16384 + (((i ^ t) & 7) << 4));
                const uint32_t u[4] = {v.x, v.y, v.z, v.w};
#pragma unroll
                for (int e = 0; e < 4; e++) {
                  s0 = fmaf(bf_lo(u[e]), bf_lo(u[e]), s0);
                  s1 = fmaf(bf_hi(u[e]), bf_hi(u[e]), s1);
                }
              }
              send_word(SC_AT(stat2, c * kS + r * 128 + t), __float_as_uint(s0 + s1), ep);
            }
            __nanosleep(kStatNs);
            const float sum = sum_words<8>(SC_AT(stat2, r * 128 + t), kS, ep);
            sts32(sb + kStat + t * 8, __float_as_uint(fmaf(sum, 1.f / kD, 1e-5f)));
            __syncwarp();
            if (elect_one()) {
              bulk_commit();
              bulk_wait_read();
              mbar_arrive(sb + kBars + 8 * kStatBar);
            }
            __syncwarp();
            if (t == 0) TS(37);
          }
        }
      }
      const int t = fresh_tid() & 127, w = warp & 3, lane = t & 31, g = lane >> 2;
      const uint32_t stg = sb + kStage + wg * 32768;
      uint32_t statv = sb + kStat + (w * 16 + g) * 8;
      const uint32_t frag = stg + (w * 16 + (lane & 15)) * 128;
      const uint32_t frag_x = (lane >> 4) ^ (lane & 7);
      const uint32_t priv = stg + (t & 96) * 64 + lane * 16;
      if (t == 0) TSK(7 + 2 * task + wg * 20);

      if (task == 4) {
        mbar_wait(sb + kBars + 8 * kResFreeBar, 1);
        mbar_wait(sb + kBars + 8 * (kStgBar + 1), 0);
      }
      asm volatile("" : "+r"(statv)::"memory");

      {
#pragma unroll
        for (int i = 0; i < 96; i++) asm volatile("sub.f32 %0, %0, %1;" : "+f"(acc[0][i]) : "f"(bias));
        auto next_rows = [&](int i) { asm volatile("sub.f32 %0, %1, %2;" : "=f"(acc[0][i]) : "f"(acc[1][i]), "f"(bias)); };
#pragma unroll 1
        for (int pp = 0; pp < 2; pp++) {
          TSG(pp);
          RowConst rc[2];
#pragma unroll
          for (int hf = 0; hf < 2; hf++) {
            const float2 st = lds64f_const(statv + pp * 512 + hf * 64);
            float rstd;
            asm("rsqrt.approx.ftz.f32 %0, %1;" : "=f"(rstd) : "f"(st.x));
            rc[hf] = {0.7978845608f * rstd, 0.0356774081f * rstd * rstd * rstd, 0.5f * rstd * rstd};
          }
#pragma unroll
          for (int j2 = 0; j2 < 4; j2++) {
            uint32_t hv[4];
#pragma unroll
            for (int jj = 0; jj < 2; jj++) {
              const int jn = 2 * j2 + jj;
#pragma unroll
              for (int hf = 0; hf < 2; hf++) {
                const float g0 = acc[0][4 * jn + 2 * hf], g1 = acc[0][4 * jn + 2 * hf + 1];
                const float u0 = acc[0][32 + 4 * jn + 2 * hf], u1 = acc[0][33 + 4 * jn + 2 * hf];
                hv[2 * jj + hf] = pack_bf16(g0 * u0 * gate_scale(g0, rc[hf]), g1 * u1 * gate_scale(g1, rc[hf]));
              }
            }
            stsm4(frag + 16384 + pp * 8192 + ((frag_x ^ (j2 * 2)) << 4), hv[0], hv[1], hv[2], hv[3]);
          }
          if (task < 4) {
            if (task == 2) {
#pragma unroll
              for (int j2 = 0; j2 < 4; j2++) {
                uint32_t hv[4];
#pragma unroll
                for (int jj = 0; jj < 2; jj++) {
                  const int jn = 16 + 2 * j2 + jj;
#pragma unroll
                  for (int hf = 0; hf < 2; hf++) {
                    const float t0 = acc[0][4 * jn + 2 * hf], t1 = acc[0][4 * jn + 2 * hf + 1];
                    hv[2 * jj + hf] = pack_bf16(t0 * gate_scale(t0, rc[hf]), t1 * gate_scale(t1, rc[hf]));
                  }
                }
                sts128(priv + pp * 8192 + j2 * 512, make_uint4(hv[0], hv[1], hv[2], hv[3]));
              }
            } else {
              uint4 park[4];
#pragma unroll
              for (int j2 = 0; j2 < 4; j2++) park[j2] = lds128(priv + pp * 8192 + j2 * 512);
              __syncwarp();
#pragma unroll
              for (int j2 = 0; j2 < 4; j2++) {
                const uint32_t pv[4] = {park[j2].x, park[j2].y, park[j2].z, park[j2].w};
                uint32_t hv[4];
#pragma unroll
                for (int jj = 0; jj < 2; jj++) {
                  const int jn = 16 + 2 * j2 + jj;
#pragma unroll
                  for (int hf = 0; hf < 2; hf++) {
                    const float t0 = acc[0][4 * jn + 2 * hf], t1 = acc[0][4 * jn + 2 * hf + 1];
                    asm("mul.rn.bf16x2 %0, %1, %2;" : "=r"(hv[2 * jj + hf]) : "r"(pack_bf16(t0, t1)), "r"(pv[2 * jj + hf]));
                  }
                }
                stsm4(frag + pp * 8192 + ((frag_x ^ (j2 * 2)) << 4), hv[0], hv[1], hv[2], hv[3]);
              }
            }
            if (pp == 1) break;
#pragma unroll
            for (int i = 64; i < 96; i++) next_rows(i);
          }
          if (pp == 1) break;
#pragma unroll
          for (int i = 0; i < 64; i++) next_rows(i);
        }
      }
      const int t3 = fresh_tid() & 127;
      uint4* part = SC_AT(part, bid * 1024 + (t3 & 96) * 8 + (t3 & 31));
      if (task == 2 && wg) {
#pragma unroll
        for (int k = 0; k < 8; k++) st_b128(part + k * 32, kPoison, kPoison, kPoison, kPoison);
      }
      fence_async_smem();
      nb_arrive(kNbPub + wg, 160);
      if (t == 0) TS(task == 4 ? 57 : 56 + task + wg * 2);
      if (task == 4) {
        mbar_wait(sb + kBars + 8 * kPartBar, 0);
        const bool none = lds32(sb + kPlan) == 0;
#pragma unroll 1
        for (int b = 1, spins = 0; b >= 0;) {
          uint4 v[4] = {};
          uint32_t top = 0;
          if (!none) {
#pragma unroll
            for (int k = 0; k < 4; k++) v[k] = ld_b128(part + (128 + k * 32));
          }
#pragma unroll
          for (int k = 0; k < 4; k++) {
            top = max(max(top, v[k].x), max(v[k].y, max(v[k].z, v[k].w)));
          }
          if (__any_sync(~0u, top == kPoison)) {
            if (++spins > 100000) __trap();
            __nanosleep(kPartNs);
            continue;
          }
#pragma unroll
          for (int k = 0; k < 4; k++) {
            uint32_t h[4];
            ldsm4(frag + 16384 + b * 8192 + ((frag_x ^ (k * 2)) << 4), h);
            asm("add.rn.bf16x2 %0, %0, %1;" : "+r"(v[k].x) : "r"(h[0]));
            asm("add.rn.bf16x2 %0, %0, %1;" : "+r"(v[k].y) : "r"(h[1]));
            asm("add.rn.bf16x2 %0, %0, %1;" : "+r"(v[k].z) : "r"(h[2]));
            asm("add.rn.bf16x2 %0, %0, %1;" : "+r"(v[k].w) : "r"(h[3]));
            sts128(stg + (t3 & 96) * 128 + (t3 & 31) * 16 + b * 2048 + k * 512, v[k]);
          }
          b--;
          part -= 128;
        }
        if (t == 0) TSK(56);
        nb_arrive(kNbPart, 256);
        break;
      }
      sx = mx = 0.f;
    }
  }
}

typedef CUresult (*EncodeTiledFn)(CUtensorMap*, CUtensorMapDataType, cuuint32_t, void*, const cuuint64_t*, const cuuint64_t*,
                                  const cuuint32_t*, const cuuint32_t*, CUtensorMapInterleave, CUtensorMapSwizzle,
                                  CUtensorMapL2promotion, CUtensorMapFloatOOBfill);

void encode(EncodeTiledFn fn, CUtensorMap* m, const void* base, int rank, cuuint64_t d0, cuuint64_t d1, cuuint64_t d2,
            cuuint64_t s1, cuuint64_t s2, cuuint32_t b2, cuuint32_t b1 = 64) {
  const cuuint64_t dims[3] = {d0, d1, d2}, strides[2] = {s1, s2};
  const cuuint32_t box[3] = {64, b1, b2}, es[3] = {1, 1, 1};
  fn(m, CU_TENSOR_MAP_DATA_TYPE_BFLOAT16, rank, const_cast<void*>(base), dims, strides, box, es, CU_TENSOR_MAP_INTERLEAVE_NONE,
     CU_TENSOR_MAP_SWIZZLE_128B, CU_TENSOR_MAP_L2_PROMOTION_L2_128B, CU_TENSOR_MAP_FLOAT_OOB_FILL_NONE);
}

}

extern "C" void kernel_launch(void* const* d_in, const int* in_sizes, int n_in, void* d_out, int out_size) {
  void* fnp = nullptr;
  cudaDriverEntryPointQueryResult qr;
  cudaGetDriverEntryPoint("cuTensorMapEncodeTiled", &fnp, cudaEnableDefault, &qr);
  EncodeTiledFn fn = (EncodeTiledFn)fnp;
  void *o, *h, *hh;
  cudaGetSymbolAddress(&o, g_o);
  cudaGetSymbolAddress(&h, g_h);
  cudaGetSymbolAddress(&hh, g_hh);

  Params p;
  Scratch* sc;
  cudaGetSymbolAddress((void**)&sc, g_scratch);
  encode(fn, &p.x, d_in[0], 3, kD, kS / 2, 2, 4 * kD, 2 * kD, 1, 128);
  encode(fn, &p.out, d_out, 3, kD, kS / 2, 2, 4 * kD, 2 * kD, 1, 16);
  encode(fn, &p.wqkv, d_in[1], 2, 3 * kD, kD, 1, 6 * kD, 0, 1);
  encode(fn, &p.wo, d_in[2], 2, kD, kD, 1, 2 * kD, 0, 1);
  encode(fn, &p.wd, d_in[6], 2, kD, kF, 1, 2 * kD, 0, 1);
  encode(fn, &p.wg, d_in[4], 2, kF, kD, 1, 2 * kF, 0, 1);
  encode(fn, &p.wu, d_in[5], 2, kF, kD, 1, 2 * kF, 0, 1);
  encode(fn, &p.o, o, 2, kD, kS, 1, 2 * kD, 0, 1, 128);
  encode(fn, &p.h, h, 2, kD, kS, 1, 2 * kD, 0, 1, 128);
  encode(fn, &p.hh, hh, 2, kF, kS, 1, 2 * kF, 0, 1, 128);
  encode(fn, &p.ost, o, 2, kD, kS, 1, 2 * kD, 0, 1);
  encode(fn, &p.o16, o, 2, kD, kS, 1, 2 * kD, 0, 1, 16);
  encode(fn, &p.h16, h, 2, kD, kS, 1, 2 * kD, 0, 1, 16);
  encode(fn, &p.hst, h, 2, kD, kS, 1, 2 * kD, 0, 1);
  encode(fn, &p.hhst, hh, 2, kF, kS, 1, 2 * kF, 0, 1);
  for (int c = 0; c < 8; c++) {
    for (int j = 0; j < 32; j++) p.g1[c][j] = g1_block(j, c) | (j >= 16 && (j < 20 || g1_block(j, c) >> 1 == c) ? kInPlace : 0);
    for (int j = 0; j < 16; j++) p.g2[c][j] = g2_block(j, c);
    for (int j = 0; j < 64; j++)
      p.g3[c][j] = g3_block(j, c) | ((0x000F000F003C000Full >> j & 1) && j != 28 + c ? kInPlace : 0) | g3_tile(j) << 5;
  }
  for (int i = 0; i < 56; i++) {
    const int b = p.g4[i] = g4_block(i);
    p.g4in[i] = b % 7 == 0 ? b / 7 | kInO | kMark : b % 7 == 3 ? (8 + b / 7) | kInO : b | (b == 4 || b == 6 ? kMark : 0);
  }
  p.wop = (const uint4*)d_in[2];
  p.wgp = (const uint4*)d_in[4];
  p.wup = (const uint4*)d_in[5];

  int dev = 0, sms = 0;
  cudaGetDevice(&dev);
  cudaDeviceGetAttribute(&sms, cudaDevAttrMultiProcessorCount, dev);
  auto* kernel = sms == 132 ? fused_block_kernel<true> : fused_block_kernel<false>;
  cudaFuncSetAttribute(kernel, cudaFuncAttributeMaxDynamicSharedMemorySize, kSmemBytes);
  kernel<<<132, kThreads, kSmemBytes, cudaStreamPerThread>>>(sc, (const __nv_bfloat16*)d_in[0], (const __nv_bfloat16*)d_in[1],
                                                                  (__nv_bfloat16*)d_out, p);
}
```
